```python
import torch

def _softmax(x, axis=-1):
    return torch.softmax(x, dim=axis)
def _gelu(x):
    return torch.nn.functional.gelu(x, approximate="tanh")
def _silu(x):
    return torch.nn.functional.silu(x)
def _sigmoid(x):
    return torch.sigmoid(x)
def _layernorm(x, axis=-1, eps=1e-5):
    m = x.mean(dim=axis, keepdim=True)
    v = x.var(dim=axis, keepdim=True, unbiased=False)
    return (x - m) / torch.sqrt(v + eps)
def _scatter_add(tgt, idx, src, axis=0):
    return tgt.clone().index_add_(axis, idx, src)
def _segment_sum(src, seg, n):
    out = torch.zeros((n,) + src.shape[1:], dtype=src.dtype)
    return out.index_add_(0, seg, src)
def _pad(x, pw):
    flat = tuple(v for pair in reversed(pw) for v in pair)
    return torch.nn.functional.pad(x, flat)

kernel_name = 'gated_mix__spectral_fnet__moe_arch_mod__prompt'

def setup_inputs():

    _w = (lambda a: (lambda t: t.to(torch.bfloat16) if t.is_floating_point() else t)(torch.as_tensor(a)))
    def _A_setup():
        B, S, D = 1, 2048, 512
        ns = torch.arange(S)[:, None] * torch.arange(S)[None, :]
        nd = torch.arange(D)[:, None] * torch.arange(D)[None, :]
        Ws_re = torch.cos(-2.0 * torch.pi * ns / S).to(float)
        Ws_im = torch.sin(-2.0 * torch.pi * ns / S).to(float)
        Wd_re = torch.cos(-2.0 * torch.pi * nd / D).to(float)
        Wd_im = torch.sin(-2.0 * torch.pi * nd / D).to(float)
        return {
            "x": _w((lambda *s: torch.randn(*s, dtype=torch.bfloat16) * 0.05)(B, S, D)),
            "dft_seq_re": _w(Ws_re),
            "dft_seq_im": _w(Ws_im),
            "dft_hid_re": _w(Wd_re),
            "dft_hid_im": _w(Wd_im),
        }
    _A_in = _A_setup()

    def _B_setup():
        B, S, D, F, C = 1, 2048, 512, 1792, 1
        return {
            "x": _w((lambda *s: torch.randn(*s, dtype=torch.bfloat16) * 0.05)(B, S, D)),
            "w_r": _w((lambda *s: torch.randn(*s, dtype=torch.bfloat16) * 1.6)(D)),
            "w_gate": _w((lambda *s: torch.randn(*s, dtype=torch.bfloat16) * 1.6)(D, F)),
            "w_up": _w((lambda *s: torch.randn(*s, dtype=torch.bfloat16) * 1.6)(D, F)),
            "w_down": _w((lambda *s: torch.randn(*s, dtype=torch.bfloat16) * 1.6)(F, D)),
        }
    _B_in = _B_setup()

    return {
        "A_x": _A_in["x"],
        "A_dft_seq_re": _A_in["dft_seq_re"],
        "A_dft_seq_im": _A_in["dft_seq_im"],
        "A_dft_hid_re": _A_in["dft_hid_re"],
        "A_dft_hid_im": _A_in["dft_hid_im"],
        "B_x": _B_in["x"],
        "B_w_r": _B_in["w_r"],
        "B_w_gate": _B_in["w_gate"],
        "B_w_up": _B_in["w_up"],
        "B_w_down": _B_in["w_down"],
        "gate_w": _w((lambda *s: torch.randn(*s, dtype=torch.bfloat16) * 0.05)(512) * 16.0),
    }

def reference(A_x, A_dft_seq_re, A_dft_seq_im, A_dft_hid_re, A_dft_hid_im, B_x, B_w_r, B_w_gate, B_w_up, B_w_down, gate_w):
    def _A_ref(x, dft_seq_re, dft_seq_im, dft_hid_re, dft_hid_im):
        a = torch.einsum("bsd,ed->bse", x, dft_hid_re)
        b = torch.einsum("bsd,ed->bse", x, dft_hid_im)
        y = torch.einsum("ts,bse->bte", dft_seq_re, a) - torch.einsum("ts,bse->bte", dft_seq_im, b)
        return y

    def _B_ref(x, w_r, w_gate, w_up, w_down):
        B, S, D = x.shape
        C = 1
        r = x @ w_r
        idx = torch.argsort(-r, axis=-1)[:, :C]
        idx_e = (lambda x, n, axis: torch.repeat_interleave(x, n, dim=axis))(idx.reshape(B, C, 1), D, axis=2)
        x_sel = (lambda x, i, axis: torch.take_along_dim(x, i, dim=axis))(x, idx_e, axis=1)
        g = _silu(x_sel @ w_gate)
        u = x_sel @ w_up
        y = (g * u) @ w_down
        r_sel = _sigmoid((lambda x, i, axis: torch.take_along_dim(x, i, dim=axis))(r, idx, axis=1))
        y = y * r_sel.reshape(B, C, 1)
        b_off = (torch.arange(B) * S).reshape(B, 1)
        flat_idx = (idx + b_off).reshape(B * C)
        zero = (x * 0.0).reshape(B * S, D)
        upd = _scatter_add(zero, flat_idx, y.reshape(B * C, D), axis=0)
        return x + upd.reshape(B, S, D)

    x = A_x
    g = _sigmoid((x * gate_w).sum(-1, keepdims=True))
    a = _A_ref(x, A_dft_seq_re, A_dft_seq_im, A_dft_hid_re, A_dft_hid_im)
    b = _B_ref(x, B_w_r, B_w_gate, B_w_up, B_w_down)
    return g * a + (1 - g) * b
```

```cpp
#include <cuda_runtime.h>
#include <cuda.h>
#include <cuda_bf16.h>
#include <stdint.h>

typedef __nv_bfloat16 bf16;

constexpr int S_ = 2048, D_ = 512, F_ = 1792;
constexpr int NCTA = 128;
constexpr int NTHREADS = 512;
#define NA 6
constexpr int NSTAGE = NA;
constexpr int NB = 12 - NA;
__host__ __device__ constexpr int a_addr(int s) { return s % NA * 16384; }
__host__ __device__ constexpr int b_dep(int s) { return s > 37 - NA ? s - 6 : s - NB; }
__host__ __device__ constexpr int b_addr(int s) { return s > 37 - NA ? a_addr(s - 6) : (NA + s % NB) * 16384; }
constexpr int REGION = 32768;
constexpr int FFN_CTAS = F_ / 16;
constexpr uint32_t SPIN_LIMIT = 1u << 16;

#define SPRINT 5
#define R6POS 2
#define HOLD 0
#define EREL 1
#define D_RD0 1130
#define D_RD1 1980
#define STP 170
#define PREW 0
#define XLD 14
#define L_RD0 3150
#define L_RD1 3730
#define SRC(i, tn) ((i) + ((i) >= (tn)))
#define LTP STP
#define ESEND 6
#define LSEND 3
#define LT0 450
#define XPOS 7
#define MARG 0
#define STP0 60
#define ET1 600
#define ETIME(k) ((k) < 4 ? (k) * STP0 : ET1 + ((k) - 4) * STP)
#define PDEL 500
#define T_D4 0
#define T_D5 1500
#define T_D6 1700
#define T_D7 2400
#define LTP0 LTP
#define LT1 (LT0 + 4 * LTP0)
#define LTIME(k) ((k) < 4 ? LT0 + (k) * LTP0 : LT1 + ((k) - 4) * LTP)
#define SG 130
#define NPACE (NA + 3)
#define XN 4
#define XD 2
#define PACE 400
#define PFW 14
#define P_1 650
#define P_D 430
#define PF0 2
#define T_1 700
#define T_2 1100
#define POLL_NS 100
#define ROUTER_T0 3000
#define ROUTER_DT 350
#define WPF 0
#define FFN_PH (FFN_DT / 4)
#define WD_T0 3000
#define WD_DT 300
#define PF_T0 5500
#define PF_DT 900
#define FFN_T0 6500
#define FFN_DT 900
#define SUM_T0 14000
#define PFD_T0 12500
#define PFD_DT 250
#define RC 168
#define RS_ 112
#define RU 64
#define PROMOC CU_TENSOR_MAP_L2_PROMOTION_L2_128B
#define STR2(x) #x
#define STR(x) STR2(x)

static_assert(SPRINT == 5, "release pattern");
constexpr int SP0 = 32 - SPRINT;

constexpr int OFF_MISC = 7 * REGION;
constexpr int B_FULL = OFF_MISC;
constexpr int B_S1 = B_FULL + 64;
constexpr int B_S2 = B_S1 + 8;
constexpr int B_D6 = B_S2 + 8;
constexpr int B_EPOCH = B_D6 + 8;
constexpr int B_GATE = B_EPOCH + 8;
constexpr int B_SIDE = B_GATE + 8;
constexpr int B_HX = B_SIDE + 8;
constexpr int B_FFN = B_HX + 8;
constexpr int B_EMPTY = B_FFN + 32;
constexpr int B_EA = B_EMPTY + 64;
constexpr int B_PRE = B_EA + 8;
constexpr int B_X = B_PRE + 8;
constexpr int B_XF = B_X + 16;
constexpr int B_LAND = B_XF + 8;
constexpr int B_VAL = B_LAND + 48;
constexpr int B_DL = B_VAL + 96;
constexpr int B_S3 = B_DL + 32;
constexpr int B_R6 = B_S3 + 8;
constexpr int M_EPOCH = B_R6 + 8;
constexpr int M_KEY = M_EPOCH + 4;
constexpr int M_ROLE = M_KEY + 4;
constexpr int M_HX = OFF_MISC + 480;
constexpr int M_G = OFF_MISC + 736;
constexpr int M_UPD = M_G + 512;
constexpr int M_RED = M_UPD + 512;
constexpr int M_PROF = M_RED + 512;
constexpr int SMEM_BYTES = 232448;
static_assert(M_PROF + 512 <= SMEM_BYTES && M_ROLE + 4 <= M_HX, "smem");

struct Params {
    const bf16 *cpf[2], *x, *gate_w, *w_r, *wg, *wu, *wd, *dre, *dim;
    bf16* out;
    CUtensorMap mCre, mCim, mX2, mX, mDre, mDim, mF, mWg, mWu, mWd;
};

__device__ __align__(1024) uint4 g_frag[NCTA * 2 * 8 * 128];
__device__ __align__(128) uint4 g_xch[NCTA * 8 * 128];
__device__ __align__(128) unsigned int g_hint[NCTA * 256];
__device__ __align__(128) unsigned int g_gate[S_];
__device__ __align__(128) unsigned int g_part[FFN_CTAS / 2 * D_];
__device__ __align__(128) unsigned int g_phint[4 * 16 * 8];
__device__ __align__(128) unsigned int g_upd[D_];
__device__ __align__(128) unsigned int g_keys[8 * NCTA];
__device__ __align__(128) unsigned int g_epoch[NCTA + 4];
#define g_ab g_frag

__device__ __forceinline__ uint32_t smem_u32(const void* p) { return (uint32_t)__cvta_generic_to_shared(p); }
__device__ __forceinline__ void mbar_init(uint32_t bar, uint32_t cnt) {
    asm volatile("mbarrier.init.shared::cta.b64 [%0], %1;" ::"r"(bar), "r"(cnt) : "memory");
}
__device__ __forceinline__ void mbar_expect_tx(uint32_t bar, uint32_t bytes) {
    asm volatile("mbarrier.arrive.expect_tx.shared::cta.b64 _, [%0], %1;" ::"r"(bar), "r"(bytes) : "memory");
}
__device__ __forceinline__ void mbar_arrive(uint32_t bar) {
    asm volatile("mbarrier.arrive.shared::cta.b64 _, [%0];" ::"r"(bar) : "memory");
}
__device__ __forceinline__ void mbar_arrive_if(uint32_t bar, bool pred) {
    asm volatile("{.reg .pred p; setp.ne.b32 p, %1, 0; @p mbarrier.arrive.shared::cta.b64 _, [%0];}" ::"r"(bar), "r"((int)pred) : "memory");
}
__device__ __forceinline__ void mbar_arrive_warp(uint32_t bar) {
    __syncwarp();
    mbar_arrive_if(bar, (threadIdx.x & 31) == 0);
}
__device__ __forceinline__ void mbar_arrive_cluster_if(uint32_t bar, bool pred) {
    asm volatile("{.reg .pred p; setp.ne.b32 p, %1, 0; @p mbarrier.arrive.shared::cluster.b64 _, [%0], 1;}"
                 ::"r"(bar), "r"((int)pred) : "memory");
}
__device__ __forceinline__ uint32_t mapa(uint32_t a, uint32_t cta) {
    uint32_t r;
    asm volatile("mapa.shared::cluster.u32 %0, %1, %2;" : "=r"(r) : "r"(a), "r"(cta));
    return r;
}
__device__ __forceinline__ bool mbar_try(uint32_t bar, uint32_t parity) {
    uint32_t ok;
    asm volatile("{.reg .pred p; mbarrier.try_wait.parity.shared::cta.b64 p, [%1], %2; selp.u32 %0,1,0,p;}"
                 : "=r"(ok) : "r"(bar), "r"(parity) : "memory");
    return ok;
}
__device__ __forceinline__ bool mbar_test(uint32_t bar, uint32_t parity) {
    uint32_t ok;
    asm volatile("{.reg .pred p; mbarrier.test_wait.parity.shared::cta.b64 p, [%1], %2; selp.u32 %0,1,0,p;}"
                 : "=r"(ok) : "r"(bar), "r"(parity) : "memory");
    return ok;
}
__device__ __forceinline__ void mbar_wait(uint32_t bar, uint32_t parity) {
    uint32_t n = 0;
#pragma unroll 1
    while (!mbar_try(bar, parity)) { if (++n > SPIN_LIMIT) break; }
}
__device__ __forceinline__ void mbar_wait_cluster(uint32_t bar, uint32_t parity) {
    uint32_t n = 0, ok;
#pragma unroll 1
    do {
        asm volatile("{.reg .pred p; mbarrier.try_wait.parity.acquire.cluster.shared::cta.b64 p, [%1], %2; selp.u32 %0,1,0,p;}"
                     : "=r"(ok) : "r"(bar), "r"(parity) : "memory");
        if (++n > SPIN_LIMIT) break;
    } while (!ok);
}
__device__ __forceinline__ void tma2d(uint32_t dst, const CUtensorMap* m, int c0, int c1, uint32_t bar) {
    asm volatile("cp.async.bulk.tensor.2d.shared::cluster.global.mbarrier::complete_tx::bytes [%0], [%1, {%3,%4}], [%2];"
                 ::"r"(dst), "l"(m), "r"(bar), "r"(c0), "r"(c1) : "memory");
}
__device__ __forceinline__ void tma2d_elect(uint32_t dst, const CUtensorMap* m, int c0, int c1, uint32_t bar) {
    asm volatile("{.reg .pred p; elect.sync _|p, 0xffffffff;"
                 " @p cp.async.bulk.tensor.2d.shared::cluster.global.mbarrier::complete_tx::bytes [%0], [%1, {%3,%4}], [%2];}"
                 ::"r"(dst), "l"(m), "r"(bar), "r"(c0), "r"(c1) : "memory");
}
__device__ __forceinline__ void tma2d_pair_elect(uint32_t dst, const CUtensorMap* m, int c0, int c1, uint32_t bar) {
    asm volatile("{.reg .pred p; elect.sync _|p, 0xffffffff;"
                 " @p cp.async.bulk.tensor.2d.shared::cluster.global.mbarrier::complete_tx::bytes.multicast::cluster"
                 " [%0], [%1, {%3,%4}], [%2], %5;}" ::"r"(dst), "l"(m), "r"(bar), "r"(c0), "r"(c1), "h"((uint16_t)3) : "memory");
}
__device__ __forceinline__ void mbar_expect_tx_elect(uint32_t bar, uint32_t bytes) {
    asm volatile("{.reg .pred p; elect.sync _|p, 0xffffffff; @p mbarrier.arrive.expect_tx.shared::cta.b64 _, [%0], %1;}"
                 ::"r"(bar), "r"(bytes) : "memory");
}
__device__ __forceinline__ void tma3d(uint32_t dst, const CUtensorMap* m, int row, int chunk, uint32_t bar) {
    asm volatile("cp.async.bulk.tensor.3d.shared::cluster.global.mbarrier::complete_tx::bytes [%0], [%1, {%3,%4,%5}], [%2];"
                 ::"r"(dst), "l"(m), "r"(bar), "r"(0), "r"(row), "r"(chunk) : "memory");
}
__device__ __forceinline__ void tma2d_prefetch(const CUtensorMap* m, int c0, int c1) {
    asm volatile("cp.async.bulk.prefetch.tensor.2d.L2.global [%0, {%1,%2}];" ::"l"(m), "r"(c0), "r"(c1) : "memory");
}
__device__ __forceinline__ void fence_proxy_async_smem() { asm volatile("fence.proxy.async.shared::cta;" ::: "memory"); }
__device__ __forceinline__ void fence_proxy_async_gmem() { asm volatile("fence.proxy.async.global;" ::: "memory"); }
__device__ __forceinline__ void prefetch_l2(const void* p) { asm volatile("prefetch.global.L2 [%0];" ::"l"(p)); }
__device__ __forceinline__ uint32_t ld_relaxed(const void* p) {
    uint32_t v;
    asm volatile("ld.relaxed.gpu.global.u32 %0, [%1];" : "=r"(v) : "l"(p) : "memory");
    return v;
}
__device__ __forceinline__ uint4 ld_relaxed4(const void* p) {
    uint4 v;
    asm volatile("ld.relaxed.gpu.global.v4.u32 {%0,%1,%2,%3}, [%4];" : "=r"(v.x), "=r"(v.y), "=r"(v.z), "=r"(v.w) : "l"(p) : "memory");
    return v;
}
__device__ __forceinline__ uint4 ld_relaxed_b128(const void* p) {
    uint4 v;
    asm volatile("{.reg .b128 t; ld.relaxed.gpu.global.b128 t, [%4]; mov.b128 {%0,%1,%2,%3}, t;}"
                 : "=r"(v.x), "=r"(v.y), "=r"(v.z), "=r"(v.w) : "l"(p) : "memory");
    return v;
}
__device__ __forceinline__ uint4 ld_relaxed_b128_if(const void* p, bool pred) {
    uint4 v = make_uint4(0, 0, 0, 0);
    asm volatile("{.reg .b128 t; .reg .pred p; setp.ne.b32 p, %5, 0; mov.b128 t, {%0,%1,%2,%3};"
                 " @p ld.relaxed.gpu.global.b128 t, [%4]; mov.b128 {%0,%1,%2,%3}, t;}"
                 : "+r"(v.x), "+r"(v.y), "+r"(v.z), "+r"(v.w) : "l"(p), "r"((int)pred) : "memory");
    return v;
}
__device__ __forceinline__ void st_relaxed_b128(void* p, uint32_t x, uint32_t y, uint32_t z, uint32_t w) {
    asm volatile("{.reg .b128 t; .reg .b64 a, b; mov.b64 a, {%1,%2}; mov.b64 b, {%3,%4}; mov.b128 t, {a, b};"
                 " st.relaxed.gpu.global.b128 [%0], t;}" ::"l"(p), "r"(x), "r"(y), "r"(z), "r"(w) : "memory");
}
__device__ __forceinline__ void st_relaxed(unsigned int* p, uint32_t v) {
    asm volatile("st.relaxed.gpu.global.u32 [%0], %1;" ::"l"(p), "r"(v) : "memory");
}
__device__ __forceinline__ void st_key(unsigned int* p, uint32_t v) {
    asm volatile("{.reg .b32 old; atom.relaxed.gpu.global.exch.b32 old, [%0], %1;}" ::"l"(p), "r"(v) : "memory");
}
__device__ __forceinline__ uint32_t tagf(float v, uint32_t par) { return (__float_as_uint(v) & ~1u) | par; }
__device__ __forceinline__ uint4 wait_tags(const unsigned int* p, int bit, uint32_t par) {
    uint32_t n = 0;
    while (true) {
        const uint4 v = ld_relaxed4(p);
        const uint32_t m = par ? (v.x & v.y & v.z & v.w) : ~(v.x | v.y | v.z | v.w);
        if (__all_sync(0xffffffffu, (m >> bit) & 1u)) return v;
        __nanosleep(POLL_NS);
        if (++n > SPIN_LIMIT) return v;
    }
}
template <int SLEEP>
__device__ __forceinline__ void wait_counters(const unsigned int* p, uint32_t want) {
    uint32_t n = 0;
    while (!__all_sync(0xffffffffu, (int)(ld_relaxed(p) - want) >= 0)) {
        if (SLEEP) __nanosleep(SLEEP);
        if (++n > SPIN_LIMIT) break;
    }
    asm volatile("fence.acquire.gpu;" ::: "memory");
}
__device__ __forceinline__ void red_release_add(unsigned int* p, uint32_t v) {
    asm volatile("red.release.gpu.global.add.u32 [%0], %1;" ::"l"(p), "r"(v) : "memory");
}
__device__ __forceinline__ void named_bar(int id, int n) { asm volatile("bar.sync %0, %1;" ::"r"(id), "r"(n) : "memory"); }
template <int OFF>
__device__ __forceinline__ uint4 ldg_nc_off(const void* p) {
    uint4 v;
    asm volatile("ld.global.nc.v4.u32 {%0,%1,%2,%3}, [%4+%5];" : "=r"(v.x), "=r"(v.y), "=r"(v.z), "=r"(v.w) : "l"(p), "n"(OFF));
    return v;
}
template <int OFF>
__device__ __forceinline__ void stg_off_if(void* p, const uint4& v, bool pred) {
    asm volatile("{.reg .pred p; setp.ne.b32 p, %6, 0; @p st.global.v4.u32 [%0+%5], {%1,%2,%3,%4};}"
                 ::"l"(p), "r"(v.x), "r"(v.y), "r"(v.z), "r"(v.w), "n"(OFF), "r"((int)pred) : "memory");
}
template <int OFF>
__device__ __forceinline__ void stg_off(void* p, const uint4& v) {
    asm volatile("st.global.v4.u32 [%0+%5], {%1,%2,%3,%4};" ::"l"(p), "r"(v.x), "r"(v.y), "r"(v.z), "r"(v.w), "n"(OFF) : "memory");
}
__device__ __forceinline__ void sts128(uint32_t a, const uint4& v) {
    asm volatile("st.shared.v4.u32 [%0], {%1,%2,%3,%4};" ::"r"(a), "r"(v.x), "r"(v.y), "r"(v.z), "r"(v.w) : "memory");
}
__device__ __forceinline__ uint4 lds128(uint32_t a) {
    uint4 v;
    asm volatile("ld.shared.v4.u32 {%0,%1,%2,%3}, [%4];" : "=r"(v.x), "=r"(v.y), "=r"(v.z), "=r"(v.w) : "r"(a) : "memory");
    return v;
}
__device__ __forceinline__ float selpf(float a, float b, bool p) {
    float r;
    asm("{.reg .pred q; setp.ne.b32 q, %3, 0; selp.f32 %0, %1, %2, q;}" : "=f"(r) : "f"(a), "f"(b), "r"((int)p));
    return r;
}
template <int N, int MASK, int SZ>
__device__ __forceinline__ void halve(float (&a)[SZ]) {
    const bool up = threadIdx.x & MASK;
#pragma unroll
    for (int j = 0; j < N; j++) a[j] = selpf(a[N + j], a[j], up) + __shfl_xor_sync(0xffffffffu, selpf(a[j], a[N + j], up), MASK);
}
__device__ __forceinline__ float bflo(uint32_t u) { return __uint_as_float(u << 16); }
__device__ __forceinline__ float bfhi(uint32_t u) { return __uint_as_float(u & 0xffff0000u); }
__device__ __forceinline__ uint32_t pack_bf16(float lo, float hi) {
    uint32_t r;
    asm("cvt.rn.bf16x2.f32 %0, %1, %2;" : "=r"(r) : "f"(hi), "f"(lo));
    return r;
}
__device__ __forceinline__ uint32_t hfma2_bf16(uint32_t a, uint32_t b, uint32_t c) {
    uint32_t r;
    asm("fma.rn.bf16x2 %0, %1, %2, %3;" : "=r"(r) : "r"(a), "r"(b), "r"(c));
    return r;
}
__device__ __forceinline__ float sigmoidf_(float v) { return 1.0f / (1.0f + __expf(-v)); }

__device__ __forceinline__ void wg_fence() { asm volatile("wgmma.fence.sync.aligned;" ::: "memory"); }
__device__ __forceinline__ void wg_commit() { asm volatile("wgmma.commit_group.sync.aligned;" ::: "memory"); }
template <int N> __device__ __forceinline__ void wg_wait() { asm volatile("wgmma.wait_group.sync.aligned %0;" ::"n"(N) : "memory"); }
__device__ __forceinline__ uint64_t desc_lo(uint32_t lo) { return (uint64_t)lo | (0x40000040ull << 32); }
template <int LO, int HI, int N>
__device__ __forceinline__ void fence_regs(float (&d)[N]) {
#pragma unroll
    for (int i = LO; i < HI; i++) asm volatile("" : "+f"(d[i])::"memory");
}
template <int TB = 1>
__device__ __forceinline__ void wgmma128(float (&d)[64], uint64_t da, uint64_t db, int scaleD) {
    asm volatile(
        "{ .reg .pred p; setp.ne.b32 p, %66, 0;\n"
        "wgmma.mma_async.sync.aligned.m64n128k16.f32.bf16.bf16 "
        "{%0,%1,%2,%3,%4,%5,%6,%7,%8,%9,%10,%11,%12,%13,%14,%15,%16,%17,%18,%19,%20,%21,%22,%23,%24,%25,%26,%27,%28,%29,%30,%31,"
        "%32,%33,%34,%35,%36,%37,%38,%39,%40,%41,%42,%43,%44,%45,%46,%47,%48,%49,%50,%51,%52,%53,%54,%55,%56,%57,%58,%59,%60,%61,%62,%63}, "
        "%64, %65, p, 1, 1, 0, %67;\n}"
        : "+f"(d[0]), "+f"(d[1]), "+f"(d[2]), "+f"(d[3]), "+f"(d[4]), "+f"(d[5]), "+f"(d[6]), "+f"(d[7]),
          "+f"(d[8]), "+f"(d[9]), "+f"(d[10]), "+f"(d[11]), "+f"(d[12]), "+f"(d[13]), "+f"(d[14]), "+f"(d[15]),
          "+f"(d[16]), "+f"(d[17]), "+f"(d[18]), "+f"(d[19]), "+f"(d[20]), "+f"(d[21]), "+f"(d[22]), "+f"(d[23]),
          "+f"(d[24]), "+f"(d[25]), "+f"(d[26]), "+f"(d[27]), "+f"(d[28]), "+f"(d[29]), "+f"(d[30]), "+f"(d[31]),
          "+f"(d[32]), "+f"(d[33]), "+f"(d[34]), "+f"(d[35]), "+f"(d[36]), "+f"(d[37]), "+f"(d[38]), "+f"(d[39]),
          "+f"(d[40]), "+f"(d[41]), "+f"(d[42]), "+f"(d[43]), "+f"(d[44]), "+f"(d[45]), "+f"(d[46]), "+f"(d[47]),
          "+f"(d[48]), "+f"(d[49]), "+f"(d[50]), "+f"(d[51]), "+f"(d[52]), "+f"(d[53]), "+f"(d[54]), "+f"(d[55]),
          "+f"(d[56]), "+f"(d[57]), "+f"(d[58]), "+f"(d[59]), "+f"(d[60]), "+f"(d[61]), "+f"(d[62]), "+f"(d[63])
        : "l"(da), "l"(db), "r"(scaleD), "n"(TB));
}


__device__ __forceinline__ void wgmma128rs(float (&d)[64], const uint4& a, uint64_t db, int scaleD) {
    asm volatile(
        "{ .reg .pred p; setp.ne.b32 p, %69, 0;\n"
        "wgmma.mma_async.sync.aligned.m64n128k16.f32.bf16.bf16 "
        "{%0,%1,%2,%3,%4,%5,%6,%7,%8,%9,%10,%11,%12,%13,%14,%15,%16,%17,%18,%19,%20,%21,%22,%23,%24,%25,%26,%27,%28,%29,%30,%31,"
        "%32,%33,%34,%35,%36,%37,%38,%39,%40,%41,%42,%43,%44,%45,%46,%47,%48,%49,%50,%51,%52,%53,%54,%55,%56,%57,%58,%59,%60,%61,%62,%63}, "
        "{%64,%65,%66,%67}, %68, p, 1, 1, 0;\n}"
        : "+f"(d[0]), "+f"(d[1]), "+f"(d[2]), "+f"(d[3]), "+f"(d[4]), "+f"(d[5]), "+f"(d[6]), "+f"(d[7]),
          "+f"(d[8]), "+f"(d[9]), "+f"(d[10]), "+f"(d[11]), "+f"(d[12]), "+f"(d[13]), "+f"(d[14]), "+f"(d[15]),
          "+f"(d[16]), "+f"(d[17]), "+f"(d[18]), "+f"(d[19]), "+f"(d[20]), "+f"(d[21]), "+f"(d[22]), "+f"(d[23]),
          "+f"(d[24]), "+f"(d[25]), "+f"(d[26]), "+f"(d[27]), "+f"(d[28]), "+f"(d[29]), "+f"(d[30]), "+f"(d[31]),
          "+f"(d[32]), "+f"(d[33]), "+f"(d[34]), "+f"(d[35]), "+f"(d[36]), "+f"(d[37]), "+f"(d[38]), "+f"(d[39]),
          "+f"(d[40]), "+f"(d[41]), "+f"(d[42]), "+f"(d[43]), "+f"(d[44]), "+f"(d[45]), "+f"(d[46]), "+f"(d[47]),
          "+f"(d[48]), "+f"(d[49]), "+f"(d[50]), "+f"(d[51]), "+f"(d[52]), "+f"(d[53]), "+f"(d[54]), "+f"(d[55]),
          "+f"(d[56]), "+f"(d[57]), "+f"(d[58]), "+f"(d[59]), "+f"(d[60]), "+f"(d[61]), "+f"(d[62]), "+f"(d[63])
        : "r"(a.x), "r"(a.y), "r"(a.z), "r"(a.w), "l"(db), "r"(scaleD));
}
template <int LO, int HI, int N>
__device__ __forceinline__ void keep_regs(uint4 (&f)[N]) {
#pragma unroll
    for (int i = LO; i < HI; i++) asm volatile("" ::"r"(f[i].x), "r"(f[i].y), "r"(f[i].z), "r"(f[i].w) : "memory");
}
__device__ __forceinline__ void tma3d_elect(uint32_t dst, const CUtensorMap* m, int row, int chunk, uint32_t bar) {
    asm volatile("{.reg .pred p; elect.sync _|p, 0xffffffff;"
                 " @p cp.async.bulk.tensor.3d.shared::cluster.global.mbarrier::complete_tx::bytes [%0], [%1, {%3,%4,%5}], [%2];}"
                 ::"r"(dst), "l"(m), "r"(bar), "r"(0), "r"(row), "r"(chunk) : "memory");
}
__device__ __forceinline__ void tma5d(uint32_t dst, const CUtensorMap* m, int c0, int c4, uint32_t bar) {
    asm volatile("cp.async.bulk.tensor.5d.shared::cluster.global.mbarrier::complete_tx::bytes [%0], [%1, {%3,%5,%5,%5,%4}], [%2];"
                 ::"r"(dst), "l"(m), "r"(bar), "r"(c0), "r"(c4), "r"(0) : "memory");
}
__device__ __forceinline__ void tma5d_elect(uint32_t dst, const CUtensorMap* m, int c0, int c4, uint32_t bar) {
    asm volatile("{.reg .pred p; elect.sync _|p, 0xffffffff;"
                 " @p cp.async.bulk.tensor.5d.shared::cluster.global.mbarrier::complete_tx::bytes [%0], [%1, {%3,%5,%5,%5,%4}], [%2];}"
                 ::"r"(dst), "l"(m), "r"(bar), "r"(c0), "r"(c4), "r"(0) : "memory");
}
__device__ __forceinline__ void st_async16(uint32_t dst, uint32_t x, uint32_t y, uint32_t z, uint32_t w, uint32_t bar) {
    asm volatile("st.async.weak.shared::cluster.mbarrier::complete_tx::bytes.v4.b32 [%0], {%1,%2,%3,%4}, [%5];"
                 ::"r"(dst), "r"(x), "r"(y), "r"(z), "r"(w), "r"(bar) : "memory");
}
__device__ __forceinline__ uint32_t hmul2_bf16(uint32_t a, uint32_t b) {
    uint32_t r;
    asm("mul.rn.bf16x2 %0, %1, %2;" : "=r"(r) : "r"(a), "r"(b));
    return r;
}
__device__ __forceinline__ bool mbar_test_cluster(uint32_t bar, uint32_t parity) {
    uint32_t ok;
    asm volatile("{.reg .pred p; mbarrier.test_wait.parity.acquire.cluster.shared::cta.b64 p, [%1], %2; selp.u32 %0,1,0,p;}"
                 : "=r"(ok) : "r"(bar), "r"(parity) : "memory");
    return ok;
}
__device__ __forceinline__ void ldg_nc_if(uint4& v, const void* a, bool pred) {
    asm volatile("{.reg .pred p; setp.ne.b32 p, %5, 0; @p ld.global.nc.v4.u32 {%0,%1,%2,%3}, [%4];}"
                 : "+r"(v.x), "+r"(v.y), "+r"(v.z), "+r"(v.w) : "l"(a), "r"((int)pred) : "memory");
}
__device__ __forceinline__ void lds128_if(uint4& v, uint32_t a, bool pred) {
    asm volatile("{.reg .pred p; setp.ne.b32 p, %5, 0; @p ld.shared.v4.u32 {%0,%1,%2,%3}, [%4];}"
                 : "+r"(v.x), "+r"(v.y), "+r"(v.z), "+r"(v.w) : "r"(a), "r"((int)pred) : "memory");
}
template <int OFF>
__device__ __forceinline__ uint4 ld_b128_off(const void* p) {
    uint4 v;
    asm volatile("{.reg .b128 t; ld.relaxed.gpu.global.b128 t, [%4+%5]; mov.b128 {%0,%1,%2,%3}, t;}"
                 : "=r"(v.x), "=r"(v.y), "=r"(v.z), "=r"(v.w) : "l"(p), "n"(OFF) : "memory");
    return v;
}
template <int OFF>
__device__ __forceinline__ void st_b128_off(void* p, const uint4& v) {
    asm volatile("{.reg .b128 t; .reg .b64 a, b; mov.b64 a, {%1,%2}; mov.b64 b, {%3,%4}; mov.b128 t, {a, b};"
                 " st.relaxed.gpu.global.b128 [%0+%5], t;}" ::"l"(p), "r"(v.x), "r"(v.y), "r"(v.z), "r"(v.w), "n"(OFF) : "memory");
}
__device__ __forceinline__ void st_relaxed_if(unsigned int* p, uint32_t v, bool pred) {
    asm volatile("{.reg .pred p; setp.ne.b32 p, %2, 0; @p st.relaxed.gpu.global.u32 [%0], %1;}" ::"l"(p), "r"(v), "r"((int)pred) : "memory");
}
__device__ __forceinline__ void wait_hint(const unsigned int* p, uint32_t par) {
    uint32_t n = 0;
#pragma unroll 1
    while (__any_sync(0xffffffffu, (ld_relaxed(p) ^ par) & 1u)) { if (++n > SPIN_LIMIT) break; }
}
__device__ __forceinline__ uint32_t clk() { uint64_t c; asm volatile("mov.u64 %0, %%clock64;" : "=l"(c)::"memory"); return (uint32_t)c; }
__device__ __forceinline__ void until(uint32_t t) { while ((int)(clk() - t) < 0) {} }
__device__ __forceinline__ uint32_t lds32(uint32_t a) {
    uint32_t v;
    asm volatile("ld.shared.u32 %0, [%1];" : "=r"(v) : "r"(a) : "memory");
    return v;
}
__device__ __forceinline__ void ld_b128_if(uint4& v, const void* p, bool pred) {
    asm volatile("{.reg .b128 t; .reg .pred p; setp.ne.b32 p, %5, 0; mov.b128 t, {%0,%1,%2,%3};"
                 " @p ld.relaxed.gpu.global.b128 t, [%4]; mov.b128 {%0,%1,%2,%3}, t;}"
                 : "+r"(v.x), "+r"(v.y), "+r"(v.z), "+r"(v.w) : "l"(p), "r"((int)pred) : "memory");
}
template <int OFF>
__device__ __forceinline__ void st32_off(void* p, uint32_t v) {
    asm volatile("st.relaxed.gpu.global.u32 [%0+%2], %1;" ::"l"(p), "r"(v), "n"(OFF) : "memory");
}
template <int N>
__device__ __forceinline__ void mbar_arrive_n_if(uint32_t bar, bool pred) {
    asm volatile("{.reg .pred p; setp.ne.b32 p, %1, 0; @p mbarrier.arrive.shared::cta.b64 _, [%0], %2;}" ::"r"(bar), "r"((int)pred), "n"(N) : "memory");
}
__device__ __forceinline__ void mbar_arrive_cluster2_if(uint32_t bar, bool pred) {
    asm volatile("{.reg .pred p; setp.ne.b32 p, %1, 0; @p mbarrier.arrive.shared::cluster.b64 _, [%0], 2;}"
                 ::"r"(bar), "r"((int)pred) : "memory");
}
__device__ __forceinline__ int sel(int a, int b, bool p) {
    int r;
    asm("{.reg .pred q; setp.ne.b32 q, %3, 0; selp.b32 %0, %1, %2, q;}" : "=r"(r) : "r"(a), "r"(b), "r"((int)p));
    return r;
}
__device__ __forceinline__ void out_piece(void* p, float s, const uint4& w, float a0, float a1, float a2, float a3, float a4, float a5,
                                          float a6, float a7) {
    uint4 z;
    z.x = pack_bf16(fmaf(s, a0, bflo(w.x)), fmaf(s, a1, bfhi(w.x)));
    z.y = pack_bf16(fmaf(s, a2, bflo(w.y)), fmaf(s, a3, bfhi(w.y)));
    z.z = pack_bf16(fmaf(s, a4, bflo(w.z)), fmaf(s, a5, bfhi(w.z)));
    z.w = pack_bf16(fmaf(s, a6, bflo(w.w)), fmaf(s, a7, bfhi(w.w)));
    stg_off<0>(p, z);
    __syncwarp();
}
__device__ __forceinline__ uint32_t watch(const unsigned int* p, uint32_t par) {
    uint32_t n;
    p += threadIdx.x & 3;
    uint32_t a = ld_relaxed(p), b;
#pragma unroll 1
    for (n = 0; n < SPIN_LIMIT; n++) {
        if (!__any_sync(0xffffffffu, (a ^ par) & 1u)) break;
        a = ld_relaxed(p);
    }
    return n;
}
__device__ __forceinline__ uint32_t stamp(const unsigned int* p, uint32_t par) {
    uint32_t a;
#pragma unroll 1
    for (uint32_t n = 0; n < SPIN_LIMIT; n++) {
        a = ld_relaxed(p);
        if (!__any_sync(0xffffffffu, (a ^ par) & 1u)) break;
    }
    const uint32_t now = clk(), age = now - a;
    return now - __reduce_min_sync(0xffffffffu, age > 8192u ? 450u : age);
}
template <int H>
__device__ __forceinline__ void fetch_job(const Params& p, unsigned char* smem, uint32_t sb, int cta, int i, uint32_t par) {
    const int lane = threadIdx.x & 31, tn = (cta >> 1) & 3, comp = cta & 1;
    const int src = (cta & ~6) + 2 * SRC(i, tn);
    const int ua = i == 0 ? a_addr(29) : i == 1 ? a_addr(30) : a_addr(31), ub = i == 0 ? b_addr(29) : i == 1 ? b_addr(30) : b_addr(31);
    const uint32_t land = sb + B_LAND + 8 * (3 * H + i);
    uint32_t ph = 0, th = 0;
#pragma unroll
    for (int c = 0; c < 2; c++) {
        const uint32_t dst = sb + (c ? ub + H * 8192 : ua + (comp ^ H) * 8192);
        const int row = (src * 2 + (comp ^ c)) * 128 + H * 64;
        mbar_expect_tx_elect(land, 8192);
        constexpr int TM[4] = {D_RD0, D_RD1, L_RD0, L_RD1};
        uint32_t np_ = 0;
        if (c == 0) {
            mbar_wait(sb + B_S1, 0);
            th = stamp(g_hint + src * 256 + 128, par) + SG * SRC(i, tn);
        }
        if (c == 0) mbar_wait(sb + B_EA, 0);
        if (c != H) mbar_wait(sb + B_EMPTY + ua / 2048, ((29 + i) / NA) & 1);
        if (TM[2 * c + H]) {
            until(th + TM[2 * c + H]);
        } else {
            if (PDEL && c == 0 && H == 0) until(clk() + PDEL);
            np_ = watch(g_hint + src * 256 + (2 * c + H) * 32, par);
        }
        if (MARG) until(clk() + MARG);
#pragma unroll 1
        for (uint32_t r = 0; r < SPIN_LIMIT; r++) {
            tma2d_elect(dst, &p.mF, 0, row, land);
            mbar_wait(land, ph);
            ph ^= 1;
            const uint32_t a = dst + (lane >> 2) * 132 + (lane & 3) * 32;
            uint32_t v[8], m0 = 0, m1 = ~0u;
#pragma unroll
            for (int k = 0; k < 8; k++) v[k] = lds32(a + k * 1024);
#pragma unroll
            for (int k = 0; k < 8; k++) { m0 |= v[k]; m1 &= v[k]; }
            if (__all_sync(0xffffffffu, (par ? m1 : ~m0) & 1u)) break;
            mbar_expect_tx_elect(land, 8192);
        }
        mbar_arrive_if(sb + B_VAL + 8 * (6 * c + 3 * H + i), lane == 0);
        __syncwarp();
    }
}
__device__ __forceinline__ int dcol(int p, int tn) {
    if (p < 2) return tn * 128 + p * 64;
    const int i = (p - 2) % 3;
    return SRC(i, tn) * 128 + (p >= 5 ? 64 : 0);
}
__host__ __device__ constexpr int dpos_load(int p) { return (p & ~1) == R6POS ? -1 : 32 + ((p & ~1) > R6POS ? p / 2 - 1 : p / 2); }
__host__ __device__ constexpr int dpos_addr(int p) { return dpos_load(p) < 0 ? 6 * REGION + (p & 1) * 16384 : (p & 1) ? b_addr(dpos_load(p) - 6) : a_addr(dpos_load(p) - 6); }
__host__ __device__ constexpr int load_dpos(int l) { return 2 * (l - 32) + (2 * (l - 32) >= R6POS ? 2 : 0); }

__device__ __forceinline__ uint32_t router_key(float score, int row) {
    const float r = score + 0.0f;
    uint32_t u = pack_bf16(r, 0.f) & 0xffffu;
    u = (u & 0x8000u) ? (~u & 0xffffu) : (u | 0x8000u);
    if (r != r) u = 0;
    return (u << 16) | (uint32_t)(0x7fff - row);
}

#define g_fb_h ((float*)g_xch)
#define g_fb_upd (g_fb_h + 2048)
#define g_fb_gate (g_fb_h + 4096)
#define g_fb_keys ((unsigned int*)g_xch + 8192)
__global__ void fb_hidden(const bf16* x, const bf16* dre, const bf16* dim, const bf16* gw, const bf16* wr) {
    __shared__ float xs[D_];
    const int s = blockIdx.x, t = threadIdx.x;
    xs[t] = __bfloat162float(x[s * D_ + t]);
    __syncthreads();
    float a = 0.f, b = 0.f;
    for (int d = 0; d < D_; d++) { a = fmaf(xs[d], __bfloat162float(dre[t * D_ + d]), a); b = fmaf(xs[d], __bfloat162float(dim[t * D_ + d]), b); }
    ((bf16*)g_ab)[s * 1024 + t] = __float2bfloat16(a);
    ((bf16*)g_ab)[s * 1024 + 512 + t] = __float2bfloat16(b);
    if (t == 0) {
        float u = 0.f, v = 0.f;
        for (int d = 0; d < D_; d++) { u = fmaf(xs[d], __bfloat162float(gw[d]), u); v = fmaf(xs[d], __bfloat162float(wr[d]), v); }
        g_fb_gate[s] = sigmoidf_(u);
        g_fb_keys[s] = router_key(v, s);
    }
}
__device__ uint32_t fb_best() {
    uint32_t k = 0;
    for (int i = 0; i < S_; i++) k = max(k, g_fb_keys[i]);
    return k;
}
__global__ void fb_ffn1(const bf16* x, const bf16* wg, const bf16* wu) {
    const int f = blockIdx.x * blockDim.x + threadIdx.x, idx = 0x7fff - (int)(fb_best() & 0x7fffu);
    float a = 0.f, b = 0.f;
    for (int d = 0; d < D_; d++) {
        const float xv = __bfloat162float(x[idx * D_ + d]);
        a = fmaf(xv, __bfloat162float(wg[d * F_ + f]), a); b = fmaf(xv, __bfloat162float(wu[d * F_ + f]), b);
    }
    g_fb_h[f] = a * sigmoidf_(a) * b;
}
__global__ void fb_ffn2(const bf16* wd) {
    const int e = blockIdx.x * blockDim.x + threadIdx.x;
    const uint32_t u = fb_best() >> 16, rb = (u & 0x8000u) ? (u & 0x7fffu) : (~u & 0xffffu);
    float a = 0.f;
    for (int f = 0; f < F_; f++) a = fmaf(g_fb_h[f], __bfloat162float(wd[f * D_ + e]), a);
    g_fb_upd[e] = a * sigmoidf_(__uint_as_float(rb << 16));
}
__global__ void fb_seq(const bf16* x, const bf16* cre, const bf16* cim, bf16* out) {
    __shared__ float c[2][S_];
    __shared__ int idx;
    const int t = blockIdx.x, e = threadIdx.x;
    for (int i = e; i < S_; i += D_) { c[0][i] = __bfloat162float(cre[t * S_ + i]); c[1][i] = __bfloat162float(cim[t * S_ + i]); }
    if (e == 0) idx = 0x7fff - (int)(fb_best() & 0x7fffu);
    __syncthreads();
    float y = 0.f;
    for (int s = 0; s < S_; s++)
        y += c[0][s] * __bfloat162float(((const bf16*)g_ab)[s * 1024 + e]) - c[1][s] * __bfloat162float(((const bf16*)g_ab)[s * 1024 + 512 + e]);
    const float g = g_fb_gate[t];
    out[t * D_ + e] = __float2bfloat16(g * y + (1.f - g) * (__bfloat162float(x[t * D_ + e]) + (t == idx ? g_fb_upd[e] : 0.f)));
}

__device__ __forceinline__ void spare_job(const Params& p, unsigned char* smem, int sp, uint32_t tstart) {
    const int tid = threadIdx.x, warp = tid >> 5, lane = tid & 31;
    const uint32_t e1 = *(volatile unsigned int*)&g_epoch[NCTA + sp] + 1u;
    const uint32_t par = e1 & 1u;
    uint32_t* red = (uint32_t*)smem;
    __syncthreads();
    if (tid == 0) *(volatile unsigned int*)&g_epoch[NCTA + sp] = e1;
    if (tid == 0) {
#pragma unroll 1
        for (int i = 0; i < 28; i++) {
            while ((uint32_t)clock64() - tstart < WD_T0 + i * WD_DT) __nanosleep(20);
            asm volatile("cp.async.bulk.prefetch.L2.global [%0], 16384;" ::"l"((const char*)p.wd + (sp * 28 + i) * 16384) : "memory");
        }
    }
    __syncwarp();
    if (warp >= 8) {
#pragma unroll 1
        for (int i = 0; i < 8; i++) {
            while ((uint32_t)clock64() - tstart < PFD_T0 + i * PFD_DT) __nanosleep(50);
            prefetch_l2((const char*)((sp & 2) ? p.dim : p.dre) + (sp & 1) * 262144 + i * 32768 + (tid - 256) * 128);
        }
    }
    if (warp == 0) {
        const uint4 k4 = wait_tags(g_keys + lane * 4, 15, par);
        const uint32_t k = __reduce_max_sync(0xffffffffu, max(max(k4.x, k4.y), max(k4.z, k4.w)));
        if (lane == 0) red[16] = k;
    }
    __syncthreads();
    while ((uint32_t)clock64() - tstart < SUM_T0) __nanosleep(200);
    float4 s = make_float4(0.f, 0.f, 0.f, 0.f);
    if (warp < 14) {
        uint32_t n = 0;
        while ((int)(ld_relaxed(g_phint + (sp * 16 + warp) * 8) - e1 * 8u) < 0) {
            __nanosleep(40);
            if (++n > SPIN_LIMIT) break;
        }
        const unsigned int* src = g_part + warp * 4 * D_ + sp * 128 + lane * 4;
        uint4 v[4];
        while (true) {
            uint32_t bad = 0;
#pragma unroll
            for (int i = 0; i < 4; i++) v[i] = ld_relaxed4(src + i * D_);
#pragma unroll
            for (int i = 0; i < 4; i++) bad |= (v[i].x ^ par) | (v[i].y ^ par) | (v[i].z ^ par) | (v[i].w ^ par);
            if (!__any_sync(0xffffffffu, bad & 1u)) break;
            if (++n > SPIN_LIMIT) break;
        }
#pragma unroll
        for (int i = 0; i < 4; i++) {
            s.x += __uint_as_float(v[i].x); s.y += __uint_as_float(v[i].y);
            s.z += __uint_as_float(v[i].z); s.w += __uint_as_float(v[i].w);
        }
    }
    float* acc = (float*)(smem + 1024);
    *(float4*)&acc[warp * 128 + lane * 4] = s;
    __syncthreads();
    if (tid < 128) {
        float t = 0.f;
#pragma unroll
        for (int i = 0; i < 16; i++) t += acc[i * 128 + tid];
        const uint32_t u = red[16] >> 16;
        const uint32_t rb = (u & 0x8000u) ? (u & 0x7fffu) : (~u & 0xffffu);
        st_relaxed(&g_upd[sp * 128 + tid], tagf(t * sigmoidf_(__uint_as_float(rb << 16)), par));
    }
}

__global__ void __cluster_dims__(2, 1, 1) __launch_bounds__(NTHREADS, 1)
fused_kernel(const __grid_constant__ Params p) {
    extern __shared__ __align__(1024) unsigned char smem[];
    const uint32_t sb = smem_u32(smem);
    const int tid = threadIdx.x, warp = tid >> 5, lane = tid & 31;
    const int rank = blockIdx.x & 1;
    const uint32_t tstart = (uint32_t)clock64();
    {
        const uint32_t b = blockIdx.x, t = tid - PFW * 32;
        const char* q0 = (const char*)p.cpf[rank] + (uint32_t)((b >> 1) * 32 + t) * (S_ * 2);
        const char* q1 = (const char*)p.x + (uint32_t)(b * 4 + t - 32) * 128;
        asm volatile("{.reg .pred p, q; .reg .b64 a; setp.lt.u32 p, %2, 32; selp.b64 a, %0, %1, p; setp.lt.u32 q, %3, 36; @q prefetch.global.L2 [a];}"
                     ::"l"(q0), "l"(q1), "r"(t), "r"(t | (b & 128)));
    }
    uint32_t smid;
    asm volatile("mov.u32 %0, %%smid;" : "=r"(smid));
    const int u = smid >> 1, v7 = ((u - 32) * 37) >> 8;
    const int tn = sel(u >> 3, sel(v7, u - 62, u < 60), u < 32);
    const int tm = sel(u & 7, sel(u - 23 - 7 * v7, 8, u < 60), u < 32);
    const bool spare = tn < 0;
    const int role = tm * 4 + tn;
    const int comp = rank;
    const CUtensorMap* mC = comp ? &p.mCim : &p.mCre;
#define FIRST(j) do { tma2d(sb + (j) * 16384, mC, (j) * 64, tm * 128, sb + B_FULL + 8 * (j));                      \
                      if ((j) < NB) tma3d(sb + (NA + (j)) * 16384, &p.mX2, (j) * 64, tn * 2, sb + B_FULL + 8 * (j)); } while (0)
#define ARM(j) do { mbar_init(sb + B_FULL + 8 * (j), 1); mbar_expect_tx(sb + B_FULL + 8 * (j), 32768); } while (0)
    if (tid == 384) {
        ARM(0);
        if (!spare) FIRST(0);
        ARM(2); ARM(4); if (NA > 6) ARM(6);
    }
    if (tid == 416) {
        ARM(1);
        if (T_1) until(tstart + T_1);
        if (!spare) FIRST(1);
        ARM(3); ARM(5); if (NA > 7) ARM(7);
    }
    if (PF0 > 1 && ((tid - PFW * 32) | (blockIdx.x & 128)) < 36) {
        const uint32_t b = blockIdx.x, t = tid - PFW * 32;
        const char* q = t < 32 ? (const char*)p.cpf[rank] + (uint32_t)((b >> 1) * 32 + t) * (S_ * 2) : (const char*)p.x + (uint32_t)(b * 4 + t - 32) * 128;
#pragma unroll
        for (int j = 1; j < PF0; j++) {
            until(tstart + P_1 + (j - 1) * P_D);
            prefetch_l2(q + j * (t < 32 ? 128 : 65536));
        }
    }
    __syncwarp();
    if (spare) {
        spare_job(p, smem, smid & 3, tstart);
        return;
    }
    const int cta = role * 2 + rank;
    {
        const int wu = __shfl_sync(0xffffffffu, warp, 0);
        if (lane == 0) {
            if (wu < 12) {
                mbar_init(sb + (wu < 11 ? B_S1 + 8 * wu : B_XF), 1);
                mbar_init(sb + B_EMPTY + 8 * wu, wu < 8 ? 4 : wu == 9 ? 5 : 1);
                if (wu == 6) mbar_expect_tx(sb + B_HX, 256);
                if (wu >= 10) mbar_expect_tx(sb + B_EMPTY + 8 * wu, 8192);
            }
            asm volatile("fence.mbarrier_init.release.cluster;" ::: "memory");
        }
    }
    __syncwarp();
    asm volatile("barrier.cluster.arrive.relaxed.aligned;" ::: "memory");

    if (warp >= 12) {
        asm volatile("setmaxnreg.dec.sync.aligned.u32 " STR(RU) ";");
        const uint32_t sbu = __shfl_sync(0xffffffffu, sb, 0);
    if (tid == 384 || tid == 416) {
        const int jj = 2 + (warp & 1);
        until(tstart + T_2 + (jj - 2) * PACE);
        FIRST(jj);
    }
    __syncwarp();
    asm volatile("barrier.cluster.wait.acquire.aligned;" ::: "memory");

        if (warp == 12) {
#pragma unroll
            for (int step = 4; step < 32; step++) {
                const int slot = step % NSTAGE;
                const uint32_t full = sbu + B_FULL + 8 * slot;
                if (step >= NA) mbar_wait(sbu + B_EMPTY + 8 * slot, (step / NSTAGE - 1) & 1);
                if (step < NPACE) until(tstart + T_2 + (step - 2) * PACE);
                tma2d_elect(sbu + a_addr(step), mC, step * 64, tm * 128, full);
                if (step >= NA) mbar_expect_tx_elect(full, 32768);
            }
        } else if (warp == 13) {
            const CUtensorMap* mD = comp ? &p.mDim : &p.mDre;
#pragma unroll
            for (int step = 4; step < 33; step++) {
                const uint32_t full = sbu + B_FULL + 8 * (step % NA);
                if (step >= NB) mbar_wait(sbu + B_EMPTY + 8 * (b_dep(step) % NA), (b_dep(step) / NA) & 1);
                if (step < NB) {
                    until(tstart + T_2 + (step - 2) * PACE);
                    tma3d_elect(sbu + b_addr(step), &p.mX2, step * 64, tn * 2, full);
                } else if (step < 32) {
                    tma2d_pair_elect(sbu + b_addr(step) + rank * 8192, &p.mX, tn * 128 + rank * 64, step * 64, full);
                } else {
                    tma5d_elect(sbu + a_addr(26), mD, dcol(load_dpos(step), tn), tn * 4, full);
                    tma5d_elect(sbu + b_addr(26), mD, dcol(load_dpos(step) + 1, tn), tn * 4, full);
                    mbar_expect_tx_elect(full, 32768);
                }
            }
            mbar_wait(sbu + B_PRE, 0);
            mbar_wait(sbu + B_R6, 0);
            tma5d_elect(sbu + 6 * REGION, mD, dcol(R6POS, tn), tn * 4, sbu + B_D6);
            tma5d_elect(sbu + 6 * REGION + 16384, mD, dcol(R6POS + 1, tn), tn * 4, sbu + B_D6);
            mbar_expect_tx_elect(sbu + B_D6, 32768);
            __syncwarp();
#pragma unroll
            for (int c = 0; c < 4; c++) mbar_expect_tx_elect(sbu + B_DL + 8 * c, 16384);
            mbar_wait(sbu + B_S1, 0);
            const uint32_t tq = clk();
#pragma unroll
            for (int c = 0; c < 4; c++) {
                constexpr int TD[4] = {T_D4, T_D5, T_D6, T_D7};
                if (!(c & 1)) mbar_wait(sbu + B_EMPTY + 8 * ((27 + c / 2) % NA), ((27 + c / 2) / NA) & 1);
                if (TD[c]) until(tq + TD[c]);
                tma5d_elect(sbu + dpos_addr(4 + c), mD, dcol(4 + c, tn), tn * 4, sbu + B_DL + 8 * c);
            }
        } else if (warp == 14) {
            if (lane == 0) {
                asm volatile("prefetch.tensormap [%0];" ::"l"(&p.mX) : "memory");
                asm volatile("prefetch.tensormap [%0];" ::"l"(&p.mF) : "memory");
                asm volatile("prefetch.tensormap [%0];" ::"l"(comp ? &p.mDim : &p.mDre) : "memory");
            }
            if (lane == 0) {
                asm volatile("st.shared::cluster.u32 [%0], %1;" ::"r"(mapa(sb + M_ROLE, rank ^ 1)), "r"(role) : "memory");
                mbar_wait(sb + B_FULL, 0);
#pragma unroll 1
                for (int i = 0; i < 24; i++) mbar_init(sbu + B_LAND + 8 * i, 1);
                fence_proxy_async_smem();
                mbar_arrive(sbu + B_PRE);
            }
            __syncwarp();
            const uint32_t wo = (uint32_t)((cta >> 6) * 256 + ((cta >> 1) & 31)) * (F_ * 2) + rank * F_ + lane * 128;
            const char* wb = (const char*)p.wg + wo;
            const char* wc = (const char*)p.wu + wo;
#pragma unroll 1
            for (int i = 0; i < 8 * WPF; i++) {
                while ((uint32_t)clock64() - tstart < PF_T0 + i * PF_DT + (cta & 3) * (PF_DT / 4)) __nanosleep(20);
                if (lane < 14) { prefetch_l2(wb + i * (64 * F_)); prefetch_l2(wc + i * (64 * F_)); }
            }
        } else {
            if (lane == 0 && cta < FFN_CTAS) {
#pragma unroll 1
                for (int i = 0; i < 8; i++) {
                    const uint32_t bar = sb + B_FFN + 8 * (i >> 1);
                    if (!(i & 1)) mbar_expect_tx(bar, 8192);
                    while ((uint32_t)clock64() - tstart < FFN_T0 + i * FFN_DT + (rank + 2 * (tm & 1)) * FFN_PH) __nanosleep(20);
                    tma2d(sb + 6 * REGION + (i & 1) * 16384 + (i >> 1) * 4096, (i & 1) ? &p.mWu : &p.mWg, role * 32, rank * 256 + (i >> 1) * 64, bar);
                }
            }
            __syncwarp();
        }
        mbar_wait(sbu + B_EPOCH, 0);
        const uint32_t par = (*(volatile uint32_t*)(smem + M_EPOCH) + 1u) & 1u;
        if (warp != 13) {
            mbar_wait(sbu + B_PRE, 0);
            fetch_job<0>(p, smem, sbu, cta, __shfl_sync(0xffffffffu, warp == 12 ? 0 : warp - 13, 0), par);
        }
    } else if (warp >= 8) {
        asm volatile("setmaxnreg.dec.sync.aligned.u32 " STR(RS_) ";");
        asm volatile("barrier.cluster.wait.acquire.aligned;" ::: "memory");
        const int t = tid - 256, w = warp - 8;
        if (t == 0) {
            const uint32_t e = *(volatile unsigned int*)&g_epoch[cta];
            *(volatile uint32_t*)(smem + M_EPOCH) = e;
            *(volatile unsigned int*)&g_epoch[cta] = e + 1;
            mbar_arrive(sb + B_EPOCH);
        }
        const bool ffn = cta < FFN_CTAS;
        const uint4 gw0 = ldg_nc_off<0>(p.gate_w + lane * 8), gw1 = ldg_nc_off<512>(p.gate_w + lane * 8);
        const uint4 rw0 = ldg_nc_off<0>(p.w_r + lane * 8), rw1 = ldg_nc_off<512>(p.w_r + lane * 8);
        mbar_wait(sb + B_EPOCH, 0);
        const uint32_t par = (*(volatile uint32_t*)(smem + M_EPOCH) + 1u) & 1u;
        while ((uint32_t)clock64() - tstart < ROUTER_T0 + (2 * w + rank) * ROUTER_DT) __nanosleep(20);
        {
            const int row0 = cta * 16 + w * 4;
            const char* xp = (const char*)p.x + (uint32_t)row0 * (D_ * 2) + lane * 16;
            uint4 xa[4], xb[4];
            xa[0] = ldg_nc_off<0>(xp);    xb[0] = ldg_nc_off<512>(xp);  xa[1] = ldg_nc_off<1024>(xp); xb[1] = ldg_nc_off<1536>(xp);
            xa[2] = ldg_nc_off<2048>(xp); xb[2] = ldg_nc_off<2560>(xp); xa[3] = ldg_nc_off<3072>(xp); xb[3] = ldg_nc_off<3584>(xp);
            float a[8];
#pragma unroll
            for (int i = 0; i < 4; i++) {
                const uint32_t xv[8] = {xa[i].x, xa[i].y, xa[i].z, xa[i].w, xb[i].x, xb[i].y, xb[i].z, xb[i].w};
                const uint32_t gv[8] = {gw0.x, gw0.y, gw0.z, gw0.w, gw1.x, gw1.y, gw1.z, gw1.w};
                const uint32_t rv[8] = {rw0.x, rw0.y, rw0.z, rw0.w, rw1.x, rw1.y, rw1.z, rw1.w};
                float uu = 0.f, vv = 0.f;
#pragma unroll
                for (int j = 0; j < 8; j++) {
                    uu = fmaf(bflo(xv[j]), bflo(gv[j]), uu); uu = fmaf(bfhi(xv[j]), bfhi(gv[j]), uu);
                    vv = fmaf(bflo(xv[j]), bflo(rv[j]), vv); vv = fmaf(bfhi(xv[j]), bfhi(rv[j]), vv);
                }
                a[i] = uu; a[4 + i] = vv;
            }
            halve<4, 16>(a); halve<2, 8>(a); halve<1, 4>(a);
            {
                const float b1 = __shfl_xor_sync(0xffffffffu, a[0], 1), b2 = __shfl_xor_sync(0xffffffffu, a[0], 2),
                            b3 = __shfl_xor_sync(0xffffffffu, a[0], 3);
                a[0] = (a[0] + b1) + (b2 + b3);
            }
            const int row = row0 + ((lane >> 2) & 3);
            if (lane < 16 && (lane & 3) == 0) st_relaxed(&g_gate[row], tagf(sigmoidf_(a[0]), par));
            const uint32_t best = __reduce_max_sync(0xffffffffu, lane >= 16 && (lane & 3) == 0 ? router_key(a[0], row) : 0u);
            if (lane == 0) *(volatile uint32_t*)(smem + M_RED + w * 4) = best;
            named_bar(1, 128);
            if (t < 8) {
                const uint4 k = *(const uint4*)(smem + M_RED);
                st_key(&g_keys[t * NCTA + cta], max(max(k.x, k.y), max(k.z, k.w)) | (par << 15));
            }
        }
        {
            const uint32_t np = par ^ 1u;
            if (t < 64) st_relaxed(g_hint + cta * 256 + (t >> 3) * 32 + (t & 7), np);
            if (PREW) {
#pragma unroll 1
                for (int i = 0; i < 16; i++) {
                    st_relaxed_b128(g_frag + cta * 2048 + i * 128 + t, np, np, np, np);
                    __nanosleep(40);
                }
            } else __nanosleep(600);
            mbar_arrive_warp(sb + B_PRE);
        }
        if (w == 0) {
            const uint4 k4 = wait_tags(g_keys + (tm & 7) * NCTA + lane * 4, 15, par);
            const uint32_t k = __reduce_max_sync(0xffffffffu, max(max(k4.x, k4.y), max(k4.z, k4.w)));
            if (lane == 0) *(volatile uint32_t*)(smem + M_KEY) = k;
            sts128(sb + M_UPD + lane * 16, ldg_nc_off<0>(p.x + (0x7fff - (k & 0x7fffu)) * D_ + rank * 256 + lane * 8));
        } else if (w == 1) {
            const uint4 g4 = wait_tags(g_gate + tm * 128 + lane * 4, 0, par);
            *(uint4*)(smem + M_G + lane * 16) = make_uint4(g4.x & ~1u, g4.y & ~1u, g4.z & ~1u, g4.w & ~1u);
            mbar_arrive_warp(sb + B_GATE);
        }
        named_bar(1, 128);
        const int idx = 0x7fff - (int)(*(volatile uint32_t*)(smem + M_KEY) & 0x7fffu);
        if (ffn) {
            mbar_wait(sb + B_PRE, 0);
            float a[16], xs[8];
            uint32_t vd[32];
#pragma unroll
            for (int i = 0; i < 8; i++) {
                a[i] = 0.f; a[8 + i] = 0.f;
                xs[i] = __bfloat162float(((const bf16*)(smem + M_UPD))[32 * i + (t >> 2)]);
            }
#pragma unroll
            for (int i = 0; i < 8; i++) {
                if (i == 4) {
                    named_bar(1, 128);
                    if (t == 0) {
                        mbar_expect_tx(sb + B_FFN, 16384);
                        tma2d(sb + 6 * REGION, &p.mWd, rank * 256, role * 32, sb + B_FFN);
                        tma2d(sb + 6 * REGION + 16384, &p.mWd, rank * 256, role * 32 + 16, sb + B_FFN);
                    }
                    __syncwarp();
                }
                if (i == 6) {
                    mbar_wait(sb + B_FFN, 1);
#pragma unroll
                    for (int j = 0; j < 32; j++) vd[j] = *(const volatile uint32_t*)(smem + 6 * REGION + (j >> 4) * 16384 + (j & 15) * 512 + t * 4);
                }
                if (!(i & 1)) mbar_wait(sb + B_FFN + 4 * i, 0);
                const uint4 vg = lds128(sb + 6 * REGION + i * 2048 + t * 16);
                const uint4 vu = lds128(sb + 6 * REGION + 16384 + i * 2048 + t * 16);
                const uint32_t g4[4] = {vg.x, vg.y, vg.z, vg.w};
                const uint32_t u4[4] = {vu.x, vu.y, vu.z, vu.w};
#pragma unroll
                for (int j = 0; j < 4; j++) {
                    a[2 * j] = fmaf(xs[i], bflo(g4[j]), a[2 * j]);         a[2 * j + 1] = fmaf(xs[i], bfhi(g4[j]), a[2 * j + 1]);
                    a[8 + 2 * j] = fmaf(xs[i], bflo(u4[j]), a[8 + 2 * j]); a[9 + 2 * j] = fmaf(xs[i], bfhi(u4[j]), a[9 + 2 * j]);
                }
            }
            halve<8, 16>(a); halve<4, 8>(a); halve<2, 4>(a);
            float* red = (float*)(smem + M_UPD);
            *(float2*)&red[w * 64 + (lane >> 4) * 32 + (lane & 3) * 8 + ((lane >> 2) & 3) * 2] = make_float2(a[0], a[1]);
            named_bar(1, 128);
            mbar_arrive_if(sb + B_R6, t == 0);
            const float sg = red[lane] + red[64 + lane] + red[128 + lane] + red[192 + lane];
            const float su = red[32 + lane] + red[96 + lane] + red[160 + lane] + red[224 + lane];
            if (w < 2) {
                asm volatile("st.async.weak.shared::cluster.mbarrier::complete_tx::bytes.f32 [%0], %1, [%2];"
                             ::"r"(mapa(sb + M_HX + t * 4, rank ^ 1)), "f"(w ? su : sg), "r"(mapa(sb + B_HX, rank ^ 1)) : "memory");
            }
            named_bar(1, 128);
            mbar_wait_cluster(sb + B_HX, 0);
            const float pg = ((const float*)(smem + M_HX))[lane], pu = ((const float*)(smem + M_HX))[32 + lane];
            const float gs = sg + pg, us = su + pu;
            float* hrow = red + w * 32;
            hrow[lane] = gs * sigmoidf_(gs) * us;
            __syncwarp();
            float o0 = 0.f, o1 = 0.f;
#pragma unroll
            for (int j4 = 0; j4 < 8; j4++) {
                const float4 hv = *(const float4*)&hrow[j4 * 4];
                o0 = fmaf(hv.x, bflo(vd[4 * j4]), o0);     o1 = fmaf(hv.x, bfhi(vd[4 * j4]), o1);
                o0 = fmaf(hv.y, bflo(vd[4 * j4 + 1]), o0); o1 = fmaf(hv.y, bfhi(vd[4 * j4 + 1]), o1);
                o0 = fmaf(hv.z, bflo(vd[4 * j4 + 2]), o0); o1 = fmaf(hv.z, bfhi(vd[4 * j4 + 2]), o1);
                o0 = fmaf(hv.w, bflo(vd[4 * j4 + 3]), o0); o1 = fmaf(hv.w, bfhi(vd[4 * j4 + 3]), o1);
            }
            asm volatile("st.relaxed.gpu.global.v2.u32 [%0], {%1,%2};" ::"l"(&g_part[role * D_ + rank * 256 + t * 2]),
                         "r"(tagf(o0, par)), "r"(tagf(o1, par)) : "memory");
            if (lane == 0) asm volatile("red.relaxed.gpu.global.add.u32 [%0], 1;" ::"l"(g_phint + ((rank * 2 + (w >> 1)) * 16 + (role >> 2)) * 8) : "memory");
        }
        if (!ffn) { mbar_wait(sb + B_PRE, 0); mbar_arrive_if(sb + B_R6, t == 0); }
        if (w < 3) {
            mbar_wait(sb + B_PRE, 0);
            fetch_job<1>(p, smem, __shfl_sync(0xffffffffu, sb, 0), cta, __shfl_sync(0xffffffffu, w, 0), par);
        }
        if (w == 3) {
            if ((idx >> 6) == 2 * tm + 1 - comp) {
                const uint4 u4 = wait_tags(g_upd + tn * 128 + lane * 4, 0, par);
                *(uint2*)(smem + M_RED + 256 + lane * 8) = make_uint2(pack_bf16(__uint_as_float(u4.x), __uint_as_float(u4.y)),
                                                                      pack_bf16(__uint_as_float(u4.z), __uint_as_float(u4.w)));
            }
            if (*(volatile uint32_t*)(smem + M_ROLE) != (uint32_t)role) __trap();
            mbar_arrive_warp(sb + B_SIDE);
        }
    } else {
        asm volatile("setmaxnreg.inc.sync.aligned.u32 " STR(RC) ";");
        const int wg = __shfl_sync(0xffffffffu, warp >> 2, 0);
        const uint32_t sbd = __shfl_sync(0xffffffffu, (sb & 0x3FFFF) >> 4, 0);
        const bool lead = (tid & 127) == 0;
        const bool early = wg == comp;
        const int q = lane & 3;
        const int r0 = (warp & 3) * 16 + (lane >> 2);
        float acc[64];
        const uint32_t da0 = sbd + 0x10000 + wg * 512, db0 = sbd + 0x2000000, dd0 = sbd + 0x10000;
        const uint32_t rE = mapa(sb + B_EMPTY, rank ^ 1);
#define RELEASE(slot) do { mbar_arrive_if(sb + B_EMPTY + 8 * (slot), lead); mbar_arrive_cluster_if(rE + 8 * (slot), lead); } while (0)
#define WAITFULL(s) mbar_wait(sb + B_FULL + 8 * ((s) % NSTAGE), ((s) / NSTAGE) & 1)
#define WAITD(pos) do { if ((pos) >= 4) mbar_wait(sb + B_DL + 8 * ((pos) - 4), 0); else if (dpos_load(pos) < 0) mbar_wait(sb + B_D6, 0); else WAITFULL(dpos_load(pos) < 0 ? 0 : dpos_load(pos)); } while (0)
#define MMA_A(s, kk) wgmma128(acc, desc_lo(da0 + a_addr(s) / 16 + (kk) * 2), desc_lo(db0 + b_addr(s) / 16 + (kk) * 128), 1)
#define MMA_B(f, pos, kk, sc) wgmma128rs(acc, f, desc_lo(dd0 + dpos_addr(pos) / 16 + (kk) * 2), sc)
        asm volatile("barrier.cluster.wait.acquire.aligned;" ::: "memory");
        WAITFULL(0);
        wg_fence();
#pragma unroll
        for (int kk = 0; kk < 4; kk++) wgmma128(acc, desc_lo(da0 + kk * 2), desc_lo(db0 + NA * 1024 + kk * 128), kk != 0);
        wg_commit();
        int slot = 1, ph = 0, pslot = 0, bslot = NA + 1;
        const uint32_t ooff = (uint32_t)((tm * 128 + wg * 64 + r0) * D_ + tn * 128 + q * 8) * 2u;
        uint4 w[8];
#pragma unroll
        for (int i = 0; i < 8; i++) w[i] = make_uint4(0, 0, 0, 0);
#pragma unroll
        for (int part = 0; part <= XN; part++) {
        if (part) {
            const char* xp = (const char*)p.x + ooff;
#pragma unroll
            for (int i = (part - 1) * 8 / XN; i < part * 8 / XN; i++) ldg_nc_if(w[i], xp + (i & 1) * 8192 + (i >> 1) * 64, early);
        }
#pragma unroll 1
        for (int step = part ? XLD + (part - 1) * XD : 1; step < (part < XN ? XLD + part * XD : SP0); step++) {
            mbar_wait(sb + B_FULL + 8 * slot, ph);
            const uint32_t a = da0 + slot * 1024, b = db0 + bslot * 1024;
            wg_fence();
#pragma unroll
            for (int kk = 0; kk < EREL; kk++) wgmma128(acc, desc_lo(a + kk * 2), desc_lo(b + kk * 128), 1);
            wg_commit();
            wg_wait<1>();
            RELEASE(pslot);
            wg_fence();
#pragma unroll
            for (int kk = EREL; kk < 4; kk++) wgmma128(acc, desc_lo(a + kk * 2), desc_lo(b + kk * 128), 1);
            wg_commit();
            pslot = slot;
            if (++slot == NSTAGE) { slot = 0; ph ^= 1; }
            if (++bslot == 12) bslot = NA;
        }
        }
        mbar_wait(sb + B_PRE, 0);
        const uint32_t par = (*(volatile uint32_t*)(smem + M_EPOCH) + 1u) & 1u;
        unsigned int* hint = g_hint + cta * 256 + (early ? 0 : 64) + (warp & 3);
        uint32_t* fout = (uint32_t*)(g_frag + (cta * 2 + wg) * 1024) + (warp & 3) * 128 + lane;
        uint32_t tagm[4];
#pragma unroll
        for (int c = 0; c < 4; c++) tagm[c] = (lane & 7) == (warp & 1) * 4 + c;
        asm volatile("" : "+r"(tagm[0]), "+r"(tagm[1]), "+r"(tagm[2]), "+r"(tagm[3]), "+l"(hint), "+l"(fout));
        uint32_t th;
        if (early) {
            WAITFULL(SP0);
            wg_fence();
            MMA_A(SP0, 0); MMA_A(SP0, 1);
            wg_commit();
            wg_wait<1>();
            mbar_arrive_n_if<2>(sb + B_EMPTY + 8 * ((SP0 - 1) % NSTAGE), lead);
            MMA_A(SP0, 2); MMA_A(SP0, 3);
            wg_commit();
#pragma unroll
            for (int s = SP0 + 1; s < 32; s++) {
                WAITFULL(s);
                wg_fence();
                MMA_A(s, 0); MMA_A(s, 1);
                if (s == 31) { wg_commit(); wg_wait<1>(); mbar_arrive_if(sb + B_S1, lead); th = clk(); st_relaxed_if(hint + 128, (th & ~1u) | par, lead); wg_fence(); }
                MMA_A(s, 2); MMA_A(s, 3);
                wg_commit();
            }
            wg_wait<0>();
            mbar_arrive_if(sb + B_EA, lead);
        } else {
            wg_wait<0>();
            mbar_arrive_n_if<2>(sb + B_EMPTY + 8 * ((SP0 - 1) % NSTAGE), lead);
#pragma unroll
            for (int s = SP0; s < 32; s++) WAITFULL(s);
            mbar_wait(sb + B_S1, 0);
            wg_fence();
#pragma unroll
            for (int s = SP0; s < 32; s++) {
                MMA_A(s, 0); MMA_A(s, 1);
                if (s > SP0) {
                    wg_commit();
                    wg_wait<1>();
                    mbar_arrive_n_if<4>(sb + B_EMPTY + 8 * ((s - 1) % NSTAGE), lead);
                    if (s == 31) { mbar_arrive_if(sb + B_S3, lead); th = 0; }
                    if (s == 30) WAITD(0);
                    wg_fence();
                }
                MMA_A(s, 2); MMA_A(s, 3);
                wg_commit();
            }
            wg_wait<0>();
            mbar_arrive_n_if<4>(sb + B_EMPTY + 8 * (31 % NSTAGE), lead);
        }
        fence_regs<0, 64>(acc);
        uint4 f[8];
#define TAG(v, c) (((v) & ~tagm[c]) | (par & tagm[c]))
#define PACK(k) f[k] = make_uint4(TAG(pack_bf16(acc[8 * (k)], acc[8 * (k) + 1]), 0), TAG(pack_bf16(acc[8 * (k) + 2], acc[8 * (k) + 3]), 2), \
                                  TAG(pack_bf16(acc[8 * (k) + 4], acc[8 * (k) + 5]), 1), TAG(pack_bf16(acc[8 * (k) + 6], acc[8 * (k) + 7]), 3))
#define SEND(k) do { st32_off<2048 * (k)>(fout, f[k].x); st32_off<2048 * (k) + 128>(fout, f[k].z);                          \
                     st32_off<2048 * (k) + 256>(fout, f[k].y); st32_off<2048 * (k) + 384>(fout, f[k].w); } while (0)
#define SENDV(k) do { st_relaxed(fout + 512 * (k), f[k].x); st_relaxed(fout + 512 * (k) + 32, f[k].z);                       \
                      st_relaxed(fout + 512 * (k) + 64, f[k].y); st_relaxed(fout + 512 * (k) + 96, f[k].w);                  \
                      if (((k) & 3) == 3 && !(D_RD0 && D_RD1 && L_RD0 && L_RD1)) st_relaxed_if(hint + 8 * ((k) & 4), par, lane == 0); } while (0)
#define OWN(k) MMA_B(f[k], (k) >> 2, (k) & 3, (k) != 0)
        const uint32_t dfa = sbd + 0x80000 + (early ? comp * 512 : 0), dfb = sbd + 0x80000 + (early ? (1 - comp) * 512 : 512);
#define MMA_F(U, pos, kk) wgmma128<0>(acc, (uint64_t)(((pos) < 5 ? dfa : dfb) + U(29 + ((pos) - 2) % 3) / 16 + (kk) * 128) | (0x10ull << 32), \
                                   desc_lo(dd0 + dpos_addr(pos) / 16 + (kk) * 2), 1)
#define WAITF(pos) mbar_wait(vb + 8 * ((pos) - 2), 0)
        const uint32_t vb = sb + B_VAL + (early ? 0 : 48);
        const uint32_t ts = clk();
        if (early) {
            PACK(0); SENDV(0); PACK(1); SENDV(1); PACK(2); SENDV(2); PACK(3); SENDV(3);
            mbar_wait(sb + B_GATE, 0);
            PACK(4); PACK(5); PACK(6); PACK(7);
            const float g0 = ((const float*)(smem + M_G))[wg * 64 + r0], g1 = ((const float*)(smem + M_G))[wg * 64 + r0 + 8];
            const float s0 = comp ? -g0 : g0, s1 = comp ? -g1 : g1;
            const uint32_t og0 = pack_bf16(1.f - g0, 1.f - g0), og1 = pack_bf16(1.f - g1, 1.f - g1);
#pragma unroll
            for (int k = 4; k < 8; k++) {
                if (k < ESEND) { until(ts + ETIME(k)); SENDV(k); }
#pragma unroll
                for (int i = 2 * k - 8; i < 2 * k - 6; i++) {
                    const uint32_t og = (i & 1) ? og1 : og0;
                    w[i] = make_uint4(hmul2_bf16(og, w[i].x), hmul2_bf16(og, w[i].y), hmul2_bf16(og, w[i].z), hmul2_bf16(og, w[i].w));
                    asm volatile("" : "+r"(w[i].x), "+r"(w[i].y), "+r"(w[i].z), "+r"(w[i].w));
                }
            }
            WAITD(0);
            mbar_wait(sb + B_S3, 0);
            wg_fence();
#pragma unroll
            for (int k = 0; k < 8; k++) {
                OWN(k);
                if (k >= 1 && k + ESEND - 1 < 8) { wg_commit(); until(ts + ETIME(k + ESEND - 1)); SENDV(k + ESEND - 1); wg_fence(); }
            }
            wg_commit();
            WAITD(2);
#pragma unroll
            for (int pos = 2; pos < 8; pos++) {
                if (pos >= 4) WAITD(pos);
                WAITF(pos);
                wg_fence();
                MMA_F(a_addr, pos, 0); MMA_F(a_addr, pos, 1);
                if (pos == 6) { wg_commit(); wg_wait<1>(); mbar_arrive_cluster_if(mapa(sb + B_XF, rank ^ 1), lead); wg_fence(); }
                if (pos == 7) mbar_arrive_if(sb + B_S2, lead);
                MMA_F(a_addr, pos, 2); MMA_F(a_addr, pos, 3);
                wg_commit();
            }
            const uint32_t xd = mapa(sb + a_addr(29) + (tid & 127) * 16, rank ^ 1), xb = mapa(sb + B_X, rank ^ 1);
            mbar_wait(sb + B_XF, 0);
            wg_wait<0>();
            fence_regs<0, 64>(acc);
            keep_regs<0, 8>(f);
#pragma unroll
            for (int i = 0; i < 8; i++) {
                const int o = 16 * (i >> 1) + 2 * (i & 1);
                const float s = (i & 1) ? s1 : s0;
                st_async16(xd + i * 2048, pack_bf16(fmaf(s, acc[o], bflo(w[i].x)), fmaf(s, acc[o + 1], bfhi(w[i].x))),
                           pack_bf16(fmaf(s, acc[o + 4], bflo(w[i].y)), fmaf(s, acc[o + 5], bfhi(w[i].y))),
                           pack_bf16(fmaf(s, acc[o + 8], bflo(w[i].z)), fmaf(s, acc[o + 9], bfhi(w[i].z))),
                           pack_bf16(fmaf(s, acc[o + 12], bflo(w[i].w)), fmaf(s, acc[o + 13], bfhi(w[i].w))), xb + 2 * (i & 4));
                if (i & 1) until(ts);
            }
        } else {
            const uint32_t xs = sb + a_addr(29) + (tid & 127) * 16;
            PACK(0); PACK(1); PACK(2); PACK(3); PACK(4); PACK(5); PACK(6); PACK(7);
            if (!HOLD) {
                wg_fence();
#pragma unroll
                for (int k = 0; k < 8; k++) {
                    OWN(k);
                    if ((k & 1) && k / 2 < LSEND) { wg_commit(); until(ts + LTIME(k / 2)); SENDV(k / 2); wg_fence(); }
                }
                wg_commit();
            }
#pragma unroll
            for (int k = HOLD ? 0 : LSEND; k < 8; k++) { until(ts + LTIME(k)); SENDV(k); }
            WAITD(2);
            mbar_wait(sb + B_GATE, 0);
            const float g0 = ((const float*)(smem + M_G))[wg * 64 + r0], g1 = ((const float*)(smem + M_G))[wg * 64 + r0 + 8];
            const float s0 = comp ? -g0 : g0, s1 = comp ? -g1 : g1;
            const int rr = 0x7fff - (int)(*(volatile uint32_t*)(smem + M_KEY) & 0x7fffu) - (tm * 128 + wg * 64 + r0);
            char* op = (char*)p.out + ooff;
            if (!HOLD) WAITF(2);
            mbar_wait(sb + B_S2, 0);
            if (HOLD) {
                wg_fence();
#pragma unroll
                for (int k = 0; k < 8; k++) OWN(k);
                wg_commit();
            }
            bool there = false;
#pragma unroll
            for (int pos = 2; pos < 8; pos++) {
                if (HOLD || pos > 2) WAITF(pos);
                if (pos == XPOS) {
                    there = mbar_test_cluster(sb + B_X, 0);
#pragma unroll
                    for (int i = 0; i < 4; i++) lds128_if(w[i], xs + i * 2048, there);
                }
                wg_fence();
                MMA_F(b_addr, pos, 0); MMA_F(b_addr, pos, 1); MMA_F(b_addr, pos, 2); MMA_F(b_addr, pos, 3);
                wg_commit();
            }
            if (!there) {
                mbar_wait_cluster(sb + B_X, 0);
#pragma unroll
                for (int i = 0; i < 4; i++) w[i] = lds128(xs + i * 2048);
            }
            const bool there1 = mbar_test_cluster(sb + B_X + 8, 0);
#pragma unroll
            for (int i = 4; i < 8; i++) lds128_if(w[i], xs + i * 2048, there1);
            mbar_wait(sb + B_SIDE, 0);
#pragma unroll
            for (int h = 0; h < 2; h++) {
                if (h == 1 && !there1) {
                    mbar_wait_cluster(sb + B_X + 8, 0);
#pragma unroll
                    for (int i = 4; i < 8; i++) w[i] = lds128(xs + i * 2048);
                }
                if (rr == 0 || rr == 8) {
                    const uint32_t og = rr ? pack_bf16(1.f - g1, 1.f - g1) : pack_bf16(1.f - g0, 1.f - g0);
#pragma unroll
                    for (int i = 4 * h; i < 4 * h + 4; i++) {
                        const uint4 z = lds128(sb + M_RED + 256 + (i >> 1) * 64 + q * 16);
                        if (((i & 1) != 0) == (rr == 8))
                            w[i] = make_uint4(hfma2_bf16(og, z.x, w[i].x), hfma2_bf16(og, z.y, w[i].y), hfma2_bf16(og, z.z, w[i].z), hfma2_bf16(og, z.w, w[i].w));
                    }
                }
                __syncwarp();
                if (h == 0) {
                    wg_wait<0>();
                    fence_regs<0, 64>(acc);
                    keep_regs<0, 8>(f);
                }
#pragma unroll
                for (int i = 4 * h; i < 4 * h + 4; i++) {
                    const int o = 16 * (i >> 1) + 2 * (i & 1);
                    out_piece(op + (i & 1) * 8192 + (i >> 1) * 64, (i & 1) ? s1 : s0, w[i], acc[o], acc[o + 1], acc[o + 4], acc[o + 5],
                              acc[o + 8], acc[o + 9], acc[o + 12], acc[o + 13]);
                }
            }
        }
    }
}

typedef CUresult (*EncodeTiledFn)(CUtensorMap*, CUtensorMapDataType, cuuint32_t, void*, const cuuint64_t*, const cuuint64_t*,
                                  const cuuint32_t*, const cuuint32_t*, CUtensorMapInterleave, CUtensorMapSwizzle,
                                  CUtensorMapL2promotion, CUtensorMapFloatOOBfill);

static void make_map(EncodeTiledFn enc, CUtensorMap* m, const void* base, uint64_t cols, uint64_t rows, uint32_t box_rows,
                     CUtensorMapSwizzle sw = CU_TENSOR_MAP_SWIZZLE_128B, uint32_t box_cols = 64,
                     CUtensorMapL2promotion promo = CU_TENSOR_MAP_L2_PROMOTION_L2_128B) {
    cuuint64_t dims[2] = {cols, rows};
    cuuint64_t str[1] = {cols * 2};
    cuuint32_t box[2] = {box_cols, box_rows};
    cuuint32_t es[2] = {1, 1};
    enc(m, CU_TENSOR_MAP_DATA_TYPE_BFLOAT16, 2, (void*)base, dims, str, box, es, CU_TENSOR_MAP_INTERLEAVE_NONE,
        sw, promo, CU_TENSOR_MAP_FLOAT_OOB_FILL_NONE);
}

static void make_map_chunks(EncodeTiledFn enc, CUtensorMap* m, const void* base, uint64_t rows) {
    cuuint64_t dims[3] = {64, rows, D_ / 64};
    cuuint64_t str[2] = {D_ * 2, 128};
    cuuint32_t box[3] = {64, 64, 2};
    cuuint32_t es[3] = {1, 1, 1};
    enc(m, CU_TENSOR_MAP_DATA_TYPE_BFLOAT16, 3, (void*)base, dims, str, box, es, CU_TENSOR_MAP_INTERLEAVE_NONE,
        CU_TENSOR_MAP_SWIZZLE_128B, CU_TENSOR_MAP_L2_PROMOTION_L2_128B, CU_TENSOR_MAP_FLOAT_OOB_FILL_NONE);
}

static void make_map_perm(EncodeTiledFn enc, CUtensorMap* m, const void* base) {
    cuuint64_t dims[5] = {D_, 2, 4, 4, D_ / 32};
    cuuint64_t str[4] = {D_ * 2, 8 * D_ * 2, 2 * D_ * 2, 32 * D_ * 2};
    cuuint32_t box[5] = {64, 2, 4, 4, 4};
    cuuint32_t es[5] = {1, 1, 1, 1, 1};
    enc(m, CU_TENSOR_MAP_DATA_TYPE_BFLOAT16, 5, (void*)base, dims, str, box, es, CU_TENSOR_MAP_INTERLEAVE_NONE,
        CU_TENSOR_MAP_SWIZZLE_128B, CU_TENSOR_MAP_L2_PROMOTION_L2_128B, CU_TENSOR_MAP_FLOAT_OOB_FILL_NONE);
}

extern "C" void kernel_launch(void* const* d_in, const int* in_sizes, int n_in, void* d_out, int out_size) {
    (void)in_sizes; (void)n_in; (void)out_size;
    static EncodeTiledFn enc = nullptr;
    static bool fused_ok = false;
    static void* frag_ptr = nullptr;
    if (!enc) {
        void* fn = nullptr;
        cudaDriverEntryPointQueryResult q;
        cudaGetDriverEntryPoint("cuTensorMapEncodeTiled", &fn, cudaEnableDefault, &q);
        enc = (EncodeTiledFn)fn;
        cudaGetSymbolAddress(&frag_ptr, g_frag);
        cudaFuncSetAttribute(fused_kernel, cudaFuncAttributeMaxDynamicSharedMemorySize, SMEM_BYTES);
        int dev = 0, nsm = 0, ncl = 0;
        cudaGetDevice(&dev);
        cudaDeviceGetAttribute(&nsm, cudaDevAttrMultiProcessorCount, dev);
        cudaLaunchConfig_t cfg = {};
        cfg.gridDim = dim3(132); cfg.blockDim = dim3(NTHREADS); cfg.dynamicSmemBytes = SMEM_BYTES;
        cudaLaunchAttribute at;
        at.id = cudaLaunchAttributeClusterDimension;
        at.val.clusterDim.x = 2; at.val.clusterDim.y = 1; at.val.clusterDim.z = 1;
        cfg.attrs = &at; cfg.numAttrs = 1;
        fused_ok = cudaOccupancyMaxActiveClusters(&ncl, fused_kernel, &cfg) == cudaSuccess && nsm == 132 && ncl == 66;
        (void)cudaGetLastError();
    }
    if (!fused_ok) {
        const bf16* const* in = (const bf16* const*)d_in;
        fb_hidden<<<S_, D_, 0, cudaStreamPerThread>>>(in[0], in[3], in[4], in[10], in[6]);
        fb_ffn1<<<F_ / 128, 128, 0, cudaStreamPerThread>>>(in[0], in[7], in[8]);
        fb_ffn2<<<D_ / 64, 64, 0, cudaStreamPerThread>>>(in[9]);
        fb_seq<<<S_, D_, 0, cudaStreamPerThread>>>(in[0], in[1], in[2], (bf16*)d_out);
        return;
    }
    Params p;
    p.x = (const bf16*)d_in[0];
    p.cpf[0] = (const bf16*)d_in[1];
    p.cpf[1] = (const bf16*)d_in[2];
    p.dre = (const bf16*)d_in[3];
    p.dim = (const bf16*)d_in[4];
    p.w_r = (const bf16*)d_in[6];
    p.wg = (const bf16*)d_in[7];
    p.wu = (const bf16*)d_in[8];
    p.wd = (const bf16*)d_in[9];
    p.gate_w = (const bf16*)d_in[10];
    p.out = (bf16*)d_out;
    make_map_chunks(enc, &p.mX2, d_in[0], S_);
    make_map(enc, &p.mX, d_in[0], D_, S_, 64);
    make_map(enc, &p.mCre, d_in[1], S_, S_, 128, CU_TENSOR_MAP_SWIZZLE_128B, 64, PROMOC);
    make_map(enc, &p.mCim, d_in[2], S_, S_, 128, CU_TENSOR_MAP_SWIZZLE_128B, 64, PROMOC);
    make_map_perm(enc, &p.mDre, d_in[3]);
    make_map_perm(enc, &p.mDim, d_in[4]);
    make_map(enc, &p.mF, frag_ptr, 64, NCTA * 256, 64, CU_TENSOR_MAP_SWIZZLE_NONE);
    make_map(enc, &p.mWg, d_in[7], F_, D_, 64, CU_TENSOR_MAP_SWIZZLE_NONE, 32, CU_TENSOR_MAP_L2_PROMOTION_NONE);
    make_map(enc, &p.mWu, d_in[8], F_, D_, 64, CU_TENSOR_MAP_SWIZZLE_NONE, 32, CU_TENSOR_MAP_L2_PROMOTION_NONE);
    make_map(enc, &p.mWd, d_in[9], D_, F_, 16, CU_TENSOR_MAP_SWIZZLE_NONE, 256);
    fused_kernel<<<132, NTHREADS, SMEM_BYTES, cudaStreamPerThread>>>(p);
}
```

```cpp
#include <cuda_runtime.h>
#include <cuda.h>
#include <cuda_bf16.h>
#include <stdint.h>

typedef __nv_bfloat16 bf16;

constexpr int S_ = 2048, D_ = 512, F_ = 1792;
constexpr int NCTA = 128;
constexpr int NTHREADS = 512;
#define NA 6
constexpr int NSTAGE = NA;
constexpr int NB = 12 - NA;
__host__ __device__ constexpr int a_addr(int s) { return s % NA * 16384; }
__host__ __device__ constexpr int b_dep(int s) { return s > 37 - NA ? s - 6 : s - NB; }
__host__ __device__ constexpr int b_addr(int s) { return s > 37 - NA ? a_addr(s - 6) : (NA + s % NB) * 16384; }
constexpr int REGION = 32768;
constexpr int FFN_CTAS = F_ / 16;
constexpr uint32_t SPIN_LIMIT = 1u << 16;

#define SPRINT 5
#define R6POS 2
#define HOLD 0
#define EREL 1
#define D_RD0 1330
#define D_RD1 2180
#define STP 170
#define PREW 0
#define XLD 14
#define L_RD0 3300
#define L_RD1 3930
#define SRC(i, tn) ((i) + ((i) >= (tn)))
#define LTP STP
#define ESEND 6
#define LSEND 3
#define LT0 450
#define XPOS 7
#define MARG 0
#define STP0 60
#define ET1 600
#define ETIME(k) ((k) < 4 ? (k) * STP0 : ET1 + ((k) - 4) * STP)
#define PDEL 500
#define T_D4 0
#define T_D5 1500
#define T_D6 1700
#define T_D7 2400
#define LTP0 LTP
#define LT1 (LT0 + 4 * LTP0)
#define LTIME(k) ((k) < 4 ? LT0 + (k) * LTP0 : LT1 + ((k) - 4) * LTP)
#define SG 130
#define NPACE (NA + 3)
#define XN 4
#define XD 2
#define PRET 1
#define GMARG 0
#define SDEL 200
#define PACE 400
#define PFW 14
#define P_1 500
#define P_D 430
#define PF0 2
#define T_1 550
#define T_2 1000
#define POLL_NS 100
#define ROUTER_T0 3000
#define ROUTER_DT 350
#define WPF 0
#define FFN_PH (FFN_DT / 4)
#define PF_T0 5500
#define PF_DT 900
#define FFN_T0 5500
#define FFN_DT 640
#define SUM_T0 14000
#define PFD_T0 12500
#define PFD_DT 250
#define RC 168
#define RS_ 112
#define RU 64
#define PROMOC CU_TENSOR_MAP_L2_PROMOTION_L2_128B
#define STR2(x) #x
#define STR(x) STR2(x)

static_assert(SPRINT == 5, "release pattern");
constexpr int SP0 = 32 - SPRINT;

constexpr int OFF_MISC = 7 * REGION;
constexpr int B_FULL = OFF_MISC;
constexpr int B_S1 = B_FULL + 64;
constexpr int B_S2 = B_S1 + 8;
constexpr int B_D6 = B_S2 + 8;
constexpr int B_EPOCH = B_D6 + 8;
constexpr int B_GATE = B_EPOCH + 8;
constexpr int B_SIDE = B_GATE + 8;
constexpr int B_HX = B_SIDE + 8;
constexpr int B_FFN = B_HX + 8;
constexpr int B_EMPTY = B_FFN + 32;
constexpr int B_EA = B_EMPTY + 64;
constexpr int B_PRE = B_EA + 8;
constexpr int B_X = B_PRE + 8;
constexpr int B_XF = B_X + 16;
constexpr int B_LAND = B_XF + 8;
constexpr int B_VAL = B_LAND + 48;
constexpr int B_DL = B_VAL + 96;
constexpr int B_S3 = B_DL + 32;
constexpr int B_R6 = B_S3 + 8;
constexpr int B_S0 = B_R6 + 8;
constexpr int B_VD = B_S0 + 8;
constexpr int B_TH = B_VD + 8;
constexpr int M_TH = B_TH + 24;
constexpr int M_EPOCH = M_TH + 12;
constexpr int M_KEY = M_EPOCH + 4;
constexpr int M_ROLE = M_KEY + 4;
constexpr int M_HX = OFF_MISC + 528;
constexpr int M_G = OFF_MISC + 784;
constexpr int M_UPD = M_G + 512;
constexpr int M_RED = M_UPD + 512;
constexpr int M_PROF = M_RED + 512;
constexpr int SMEM_BYTES = 232448;
static_assert(M_PROF + 512 <= SMEM_BYTES && M_ROLE + 4 <= M_HX, "smem");

struct Params {
    const bf16 *x, *gate_w, *w_r, *wg, *wu, *wd, *dre, *dim;
    bf16* out;
    CUtensorMap mCre, mCim, mX2, mX, mDre, mDim, mF, mWg, mWu, mWd;
};

__device__ __align__(1024) uint4 g_frag[NCTA * 2 * 8 * 128];
__device__ __align__(128) uint4 g_xch[NCTA * 8 * 128];
__device__ __align__(128) unsigned int g_hint[NCTA * 256];
__device__ __align__(128) unsigned int g_gate[S_];
__device__ __align__(128) unsigned int g_part[FFN_CTAS / 2 * D_];
__device__ __align__(128) unsigned int g_phint[4 * 16 * 8];
__device__ __align__(128) unsigned int g_upd[D_];
__device__ __align__(128) unsigned int g_keys[8 * NCTA];
__device__ __align__(128) unsigned int g_epoch[NCTA + 4];
#define g_ab g_frag

__device__ __forceinline__ uint32_t smem_u32(const void* p) { return (uint32_t)__cvta_generic_to_shared(p); }
__device__ __forceinline__ void mbar_init(uint32_t bar, uint32_t cnt) {
    asm volatile("mbarrier.init.shared::cta.b64 [%0], %1;" ::"r"(bar), "r"(cnt) : "memory");
}
__device__ __forceinline__ void mbar_expect_tx(uint32_t bar, uint32_t bytes) {
    asm volatile("mbarrier.arrive.expect_tx.shared::cta.b64 _, [%0], %1;" ::"r"(bar), "r"(bytes) : "memory");
}
__device__ __forceinline__ void mbar_arrive(uint32_t bar) {
    asm volatile("mbarrier.arrive.shared::cta.b64 _, [%0];" ::"r"(bar) : "memory");
}
__device__ __forceinline__ void mbar_arrive_if(uint32_t bar, bool pred) {
    asm volatile("{.reg .pred p; setp.ne.b32 p, %1, 0; @p mbarrier.arrive.shared::cta.b64 _, [%0];}" ::"r"(bar), "r"((int)pred) : "memory");
}
__device__ __forceinline__ void mbar_arrive_warp(uint32_t bar) {
    __syncwarp();
    mbar_arrive_if(bar, (threadIdx.x & 31) == 0);
}
__device__ __forceinline__ void mbar_arrive_cluster_if(uint32_t bar, bool pred) {
    asm volatile("{.reg .pred p; setp.ne.b32 p, %1, 0; @p mbarrier.arrive.shared::cluster.b64 _, [%0], 1;}"
                 ::"r"(bar), "r"((int)pred) : "memory");
}
__device__ __forceinline__ uint32_t mapa(uint32_t a, uint32_t cta) {
    uint32_t r;
    asm volatile("mapa.shared::cluster.u32 %0, %1, %2;" : "=r"(r) : "r"(a), "r"(cta));
    return r;
}
__device__ __forceinline__ bool mbar_try(uint32_t bar, uint32_t parity) {
    uint32_t ok;
    asm volatile("{.reg .pred p; mbarrier.try_wait.parity.shared::cta.b64 p, [%1], %2; selp.u32 %0,1,0,p;}"
                 : "=r"(ok) : "r"(bar), "r"(parity) : "memory");
    return ok;
}
__device__ __forceinline__ bool mbar_test(uint32_t bar, uint32_t parity) {
    uint32_t ok;
    asm volatile("{.reg .pred p; mbarrier.test_wait.parity.shared::cta.b64 p, [%1], %2; selp.u32 %0,1,0,p;}"
                 : "=r"(ok) : "r"(bar), "r"(parity) : "memory");
    return ok;
}
__device__ __forceinline__ void mbar_wait(uint32_t bar, uint32_t parity) {
    uint32_t n = 0;
#pragma unroll 1
    while (!mbar_try(bar, parity)) { if (++n > SPIN_LIMIT) break; }
}
__device__ __forceinline__ void mbar_wait_cluster(uint32_t bar, uint32_t parity) {
    uint32_t n = 0, ok;
#pragma unroll 1
    do {
        asm volatile("{.reg .pred p; mbarrier.try_wait.parity.acquire.cluster.shared::cta.b64 p, [%1], %2; selp.u32 %0,1,0,p;}"
                     : "=r"(ok) : "r"(bar), "r"(parity) : "memory");
        if (++n > SPIN_LIMIT) break;
    } while (!ok);
}
__device__ __forceinline__ void tma2d(uint32_t dst, const CUtensorMap* m, int c0, int c1, uint32_t bar) {
    asm volatile("cp.async.bulk.tensor.2d.shared::cluster.global.mbarrier::complete_tx::bytes [%0], [%1, {%3,%4}], [%2];"
                 ::"r"(dst), "l"(m), "r"(bar), "r"(c0), "r"(c1) : "memory");
}
__device__ __forceinline__ void tma2d_elect(uint32_t dst, const CUtensorMap* m, int c0, int c1, uint32_t bar) {
    asm volatile("{.reg .pred p; elect.sync _|p, 0xffffffff;"
                 " @p cp.async.bulk.tensor.2d.shared::cluster.global.mbarrier::complete_tx::bytes [%0], [%1, {%3,%4}], [%2];}"
                 ::"r"(dst), "l"(m), "r"(bar), "r"(c0), "r"(c1) : "memory");
}
__device__ __forceinline__ void tma2d_pair_elect(uint32_t dst, const CUtensorMap* m, int c0, int c1, uint32_t bar) {
    asm volatile("{.reg .pred p; elect.sync _|p, 0xffffffff;"
                 " @p cp.async.bulk.tensor.2d.shared::cluster.global.mbarrier::complete_tx::bytes.multicast::cluster"
                 " [%0], [%1, {%3,%4}], [%2], %5;}" ::"r"(dst), "l"(m), "r"(bar), "r"(c0), "r"(c1), "h"((uint16_t)3) : "memory");
}
__device__ __forceinline__ void mbar_expect_tx_elect(uint32_t bar, uint32_t bytes) {
    asm volatile("{.reg .pred p; elect.sync _|p, 0xffffffff; @p mbarrier.arrive.expect_tx.shared::cta.b64 _, [%0], %1;}"
                 ::"r"(bar), "r"(bytes) : "memory");
}
__device__ __forceinline__ void tma3d(uint32_t dst, const CUtensorMap* m, int row, int chunk, uint32_t bar) {
    asm volatile("cp.async.bulk.tensor.3d.shared::cluster.global.mbarrier::complete_tx::bytes [%0], [%1, {%3,%4,%5}], [%2];"
                 ::"r"(dst), "l"(m), "r"(bar), "r"(0), "r"(row), "r"(chunk) : "memory");
}
__device__ __forceinline__ void tma2d_prefetch(const CUtensorMap* m, int c0, int c1) {
    asm volatile("cp.async.bulk.prefetch.tensor.2d.L2.global [%0, {%1,%2}];" ::"l"(m), "r"(c0), "r"(c1) : "memory");
}
__device__ __forceinline__ void fence_proxy_async_smem() { asm volatile("fence.proxy.async.shared::cta;" ::: "memory"); }
__device__ __forceinline__ void fence_proxy_async_gmem() { asm volatile("fence.proxy.async.global;" ::: "memory"); }
__device__ __forceinline__ void prefetch_l2(const void* p) { asm volatile("prefetch.global.L2 [%0];" ::"l"(p)); }
__device__ __forceinline__ uint32_t ld_relaxed(const void* p) {
    uint32_t v;
    asm volatile("ld.relaxed.gpu.global.u32 %0, [%1];" : "=r"(v) : "l"(p) : "memory");
    return v;
}
__device__ __forceinline__ uint4 ld_relaxed4(const void* p) {
    uint4 v;
    asm volatile("ld.relaxed.gpu.global.v4.u32 {%0,%1,%2,%3}, [%4];" : "=r"(v.x), "=r"(v.y), "=r"(v.z), "=r"(v.w) : "l"(p) : "memory");
    return v;
}
__device__ __forceinline__ uint4 ld_relaxed_b128(const void* p) {
    uint4 v;
    asm volatile("{.reg .b128 t; ld.relaxed.gpu.global.b128 t, [%4]; mov.b128 {%0,%1,%2,%3}, t;}"
                 : "=r"(v.x), "=r"(v.y), "=r"(v.z), "=r"(v.w) : "l"(p) : "memory");
    return v;
}
__device__ __forceinline__ uint4 ld_relaxed_b128_if(const void* p, bool pred) {
    uint4 v = make_uint4(0, 0, 0, 0);
    asm volatile("{.reg .b128 t; .reg .pred p; setp.ne.b32 p, %5, 0; mov.b128 t, {%0,%1,%2,%3};"
                 " @p ld.relaxed.gpu.global.b128 t, [%4]; mov.b128 {%0,%1,%2,%3}, t;}"
                 : "+r"(v.x), "+r"(v.y), "+r"(v.z), "+r"(v.w) : "l"(p), "r"((int)pred) : "memory");
    return v;
}
__device__ __forceinline__ void st_relaxed_b128(void* p, uint32_t x, uint32_t y, uint32_t z, uint32_t w) {
    asm volatile("{.reg .b128 t; .reg .b64 a, b; mov.b64 a, {%1,%2}; mov.b64 b, {%3,%4}; mov.b128 t, {a, b};"
                 " st.relaxed.gpu.global.b128 [%0], t;}" ::"l"(p), "r"(x), "r"(y), "r"(z), "r"(w) : "memory");
}
__device__ __forceinline__ void st_relaxed(unsigned int* p, uint32_t v) {
    asm volatile("st.relaxed.gpu.global.u32 [%0], %1;" ::"l"(p), "r"(v) : "memory");
}
__device__ __forceinline__ void st_key(unsigned int* p, uint32_t v) {
    asm volatile("{.reg .b32 old; atom.relaxed.gpu.global.exch.b32 old, [%0], %1;}" ::"l"(p), "r"(v) : "memory");
}
__device__ __forceinline__ uint32_t tagf(float v, uint32_t par) { return (__float_as_uint(v) & ~1u) | par; }
__device__ __forceinline__ uint4 wait_tags(const unsigned int* p, int bit, uint32_t par) {
    uint32_t n = 0;
    while (true) {
        const uint4 v = ld_relaxed4(p);
        const uint32_t m = par ? (v.x & v.y & v.z & v.w) : ~(v.x | v.y | v.z | v.w);
        if (__all_sync(0xffffffffu, (m >> bit) & 1u)) return v;
        __nanosleep(POLL_NS);
        if (++n > SPIN_LIMIT) return v;
    }
}
template <int SLEEP>
__device__ __forceinline__ void wait_counters(const unsigned int* p, uint32_t want) {
    uint32_t n = 0;
    while (!__all_sync(0xffffffffu, (int)(ld_relaxed(p) - want) >= 0)) {
        if (SLEEP) __nanosleep(SLEEP);
        if (++n > SPIN_LIMIT) break;
    }
    asm volatile("fence.acquire.gpu;" ::: "memory");
}
__device__ __forceinline__ void red_release_add(unsigned int* p, uint32_t v) {
    asm volatile("red.release.gpu.global.add.u32 [%0], %1;" ::"l"(p), "r"(v) : "memory");
}
__device__ __forceinline__ void named_bar(int id, int n) { asm volatile("bar.sync %0, %1;" ::"r"(id), "r"(n) : "memory"); }
template <int OFF>
__device__ __forceinline__ uint4 ldg_nc_off(const void* p) {
    uint4 v;
    asm volatile("ld.global.nc.v4.u32 {%0,%1,%2,%3}, [%4+%5];" : "=r"(v.x), "=r"(v.y), "=r"(v.z), "=r"(v.w) : "l"(p), "n"(OFF));
    return v;
}
template <int OFF>
__device__ __forceinline__ void stg_off_if(void* p, const uint4& v, bool pred) {
    asm volatile("{.reg .pred p; setp.ne.b32 p, %6, 0; @p st.global.v4.u32 [%0+%5], {%1,%2,%3,%4};}"
                 ::"l"(p), "r"(v.x), "r"(v.y), "r"(v.z), "r"(v.w), "n"(OFF), "r"((int)pred) : "memory");
}
template <int OFF>
__device__ __forceinline__ void stg_off(void* p, const uint4& v) {
    asm volatile("st.global.v4.u32 [%0+%5], {%1,%2,%3,%4};" ::"l"(p), "r"(v.x), "r"(v.y), "r"(v.z), "r"(v.w), "n"(OFF) : "memory");
}
__device__ __forceinline__ void sts128(uint32_t a, const uint4& v) {
    asm volatile("st.shared.v4.u32 [%0], {%1,%2,%3,%4};" ::"r"(a), "r"(v.x), "r"(v.y), "r"(v.z), "r"(v.w) : "memory");
}
__device__ __forceinline__ uint4 lds128(uint32_t a) {
    uint4 v;
    asm volatile("ld.shared.v4.u32 {%0,%1,%2,%3}, [%4];" : "=r"(v.x), "=r"(v.y), "=r"(v.z), "=r"(v.w) : "r"(a) : "memory");
    return v;
}
__device__ __forceinline__ float selpf(float a, float b, bool p) {
    float r;
    asm("{.reg .pred q; setp.ne.b32 q, %3, 0; selp.f32 %0, %1, %2, q;}" : "=f"(r) : "f"(a), "f"(b), "r"((int)p));
    return r;
}
template <int N, int MASK, int SZ>
__device__ __forceinline__ void halve(float (&a)[SZ]) {
    const bool up = threadIdx.x & MASK;
#pragma unroll
    for (int j = 0; j < N; j++) a[j] = selpf(a[N + j], a[j], up) + __shfl_xor_sync(0xffffffffu, selpf(a[j], a[N + j], up), MASK);
}
__device__ __forceinline__ float bflo(uint32_t u) { return __uint_as_float(u << 16); }
__device__ __forceinline__ float bfhi(uint32_t u) { return __uint_as_float(u & 0xffff0000u); }
__device__ __forceinline__ uint32_t pack_bf16(float lo, float hi) {
    uint32_t r;
    asm("cvt.rn.bf16x2.f32 %0, %1, %2;" : "=r"(r) : "f"(hi), "f"(lo));
    return r;
}
__device__ __forceinline__ uint32_t hfma2_bf16(uint32_t a, uint32_t b, uint32_t c) {
    uint32_t r;
    asm("fma.rn.bf16x2 %0, %1, %2, %3;" : "=r"(r) : "r"(a), "r"(b), "r"(c));
    return r;
}
__device__ __forceinline__ float sigmoidf_(float v) { return 1.0f / (1.0f + __expf(-v)); }

__device__ __forceinline__ void wg_fence() { asm volatile("wgmma.fence.sync.aligned;" ::: "memory"); }
__device__ __forceinline__ void wg_commit() { asm volatile("wgmma.commit_group.sync.aligned;" ::: "memory"); }
template <int N> __device__ __forceinline__ void wg_wait() { asm volatile("wgmma.wait_group.sync.aligned %0;" ::"n"(N) : "memory"); }
__device__ __forceinline__ uint64_t desc_lo(uint32_t lo) { return (uint64_t)lo | (0x40000040ull << 32); }
template <int LO, int HI, int N>
__device__ __forceinline__ void fence_regs(float (&d)[N]) {
#pragma unroll
    for (int i = LO; i < HI; i++) asm volatile("" : "+f"(d[i])::"memory");
}
template <int TB = 1>
__device__ __forceinline__ void wgmma128(float (&d)[64], uint64_t da, uint64_t db, int scaleD) {
    asm volatile(
        "{ .reg .pred p; setp.ne.b32 p, %66, 0;\n"
        "wgmma.mma_async.sync.aligned.m64n128k16.f32.bf16.bf16 "
        "{%0,%1,%2,%3,%4,%5,%6,%7,%8,%9,%10,%11,%12,%13,%14,%15,%16,%17,%18,%19,%20,%21,%22,%23,%24,%25,%26,%27,%28,%29,%30,%31,"
        "%32,%33,%34,%35,%36,%37,%38,%39,%40,%41,%42,%43,%44,%45,%46,%47,%48,%49,%50,%51,%52,%53,%54,%55,%56,%57,%58,%59,%60,%61,%62,%63}, "
        "%64, %65, p, 1, 1, 0, %67;\n}"
        : "+f"(d[0]), "+f"(d[1]), "+f"(d[2]), "+f"(d[3]), "+f"(d[4]), "+f"(d[5]), "+f"(d[6]), "+f"(d[7]),
          "+f"(d[8]), "+f"(d[9]), "+f"(d[10]), "+f"(d[11]), "+f"(d[12]), "+f"(d[13]), "+f"(d[14]), "+f"(d[15]),
          "+f"(d[16]), "+f"(d[17]), "+f"(d[18]), "+f"(d[19]), "+f"(d[20]), "+f"(d[21]), "+f"(d[22]), "+f"(d[23]),
          "+f"(d[24]), "+f"(d[25]), "+f"(d[26]), "+f"(d[27]), "+f"(d[28]), "+f"(d[29]), "+f"(d[30]), "+f"(d[31]),
          "+f"(d[32]), "+f"(d[33]), "+f"(d[34]), "+f"(d[35]), "+f"(d[36]), "+f"(d[37]), "+f"(d[38]), "+f"(d[39]),
          "+f"(d[40]), "+f"(d[41]), "+f"(d[42]), "+f"(d[43]), "+f"(d[44]), "+f"(d[45]), "+f"(d[46]), "+f"(d[47]),
          "+f"(d[48]), "+f"(d[49]), "+f"(d[50]), "+f"(d[51]), "+f"(d[52]), "+f"(d[53]), "+f"(d[54]), "+f"(d[55]),
          "+f"(d[56]), "+f"(d[57]), "+f"(d[58]), "+f"(d[59]), "+f"(d[60]), "+f"(d[61]), "+f"(d[62]), "+f"(d[63])
        : "l"(da), "l"(db), "r"(scaleD), "n"(TB));
}


__device__ __forceinline__ void wgmma128rs(float (&d)[64], const uint4& a, uint64_t db, int scaleD) {
    asm volatile(
        "{ .reg .pred p; setp.ne.b32 p, %69, 0;\n"
        "wgmma.mma_async.sync.aligned.m64n128k16.f32.bf16.bf16 "
        "{%0,%1,%2,%3,%4,%5,%6,%7,%8,%9,%10,%11,%12,%13,%14,%15,%16,%17,%18,%19,%20,%21,%22,%23,%24,%25,%26,%27,%28,%29,%30,%31,"
        "%32,%33,%34,%35,%36,%37,%38,%39,%40,%41,%42,%43,%44,%45,%46,%47,%48,%49,%50,%51,%52,%53,%54,%55,%56,%57,%58,%59,%60,%61,%62,%63}, "
        "{%64,%65,%66,%67}, %68, p, 1, 1, 0;\n}"
        : "+f"(d[0]), "+f"(d[1]), "+f"(d[2]), "+f"(d[3]), "+f"(d[4]), "+f"(d[5]), "+f"(d[6]), "+f"(d[7]),
          "+f"(d[8]), "+f"(d[9]), "+f"(d[10]), "+f"(d[11]), "+f"(d[12]), "+f"(d[13]), "+f"(d[14]), "+f"(d[15]),
          "+f"(d[16]), "+f"(d[17]), "+f"(d[18]), "+f"(d[19]), "+f"(d[20]), "+f"(d[21]), "+f"(d[22]), "+f"(d[23]),
          "+f"(d[24]), "+f"(d[25]), "+f"(d[26]), "+f"(d[27]), "+f"(d[28]), "+f"(d[29]), "+f"(d[30]), "+f"(d[31]),
          "+f"(d[32]), "+f"(d[33]), "+f"(d[34]), "+f"(d[35]), "+f"(d[36]), "+f"(d[37]), "+f"(d[38]), "+f"(d[39]),
          "+f"(d[40]), "+f"(d[41]), "+f"(d[42]), "+f"(d[43]), "+f"(d[44]), "+f"(d[45]), "+f"(d[46]), "+f"(d[47]),
          "+f"(d[48]), "+f"(d[49]), "+f"(d[50]), "+f"(d[51]), "+f"(d[52]), "+f"(d[53]), "+f"(d[54]), "+f"(d[55]),
          "+f"(d[56]), "+f"(d[57]), "+f"(d[58]), "+f"(d[59]), "+f"(d[60]), "+f"(d[61]), "+f"(d[62]), "+f"(d[63])
        : "r"(a.x), "r"(a.y), "r"(a.z), "r"(a.w), "l"(db), "r"(scaleD));
}
template <int LO, int HI, int N>
__device__ __forceinline__ void keep_regs(uint4 (&f)[N]) {
#pragma unroll
    for (int i = LO; i < HI; i++) asm volatile("" ::"r"(f[i].x), "r"(f[i].y), "r"(f[i].z), "r"(f[i].w) : "memory");
}
__device__ __forceinline__ void tma3d_elect(uint32_t dst, const CUtensorMap* m, int row, int chunk, uint32_t bar) {
    asm volatile("{.reg .pred p; elect.sync _|p, 0xffffffff;"
                 " @p cp.async.bulk.tensor.3d.shared::cluster.global.mbarrier::complete_tx::bytes [%0], [%1, {%3,%4,%5}], [%2];}"
                 ::"r"(dst), "l"(m), "r"(bar), "r"(0), "r"(row), "r"(chunk) : "memory");
}
__device__ __forceinline__ void tma5d(uint32_t dst, const CUtensorMap* m, int c0, int c4, uint32_t bar) {
    asm volatile("cp.async.bulk.tensor.5d.shared::cluster.global.mbarrier::complete_tx::bytes [%0], [%1, {%3,%5,%5,%5,%4}], [%2];"
                 ::"r"(dst), "l"(m), "r"(bar), "r"(c0), "r"(c4), "r"(0) : "memory");
}
__device__ __forceinline__ void tma5d_elect(uint32_t dst, const CUtensorMap* m, int c0, int c4, uint32_t bar) {
    asm volatile("{.reg .pred p; elect.sync _|p, 0xffffffff;"
                 " @p cp.async.bulk.tensor.5d.shared::cluster.global.mbarrier::complete_tx::bytes [%0], [%1, {%3,%5,%5,%5,%4}], [%2];}"
                 ::"r"(dst), "l"(m), "r"(bar), "r"(c0), "r"(c4), "r"(0) : "memory");
}
__device__ __forceinline__ void st_async16(uint32_t dst, uint32_t x, uint32_t y, uint32_t z, uint32_t w, uint32_t bar) {
    asm volatile("st.async.weak.shared::cluster.mbarrier::complete_tx::bytes.v4.b32 [%0], {%1,%2,%3,%4}, [%5];"
                 ::"r"(dst), "r"(x), "r"(y), "r"(z), "r"(w), "r"(bar) : "memory");
}
__device__ __forceinline__ uint32_t hmul2_bf16(uint32_t a, uint32_t b) {
    uint32_t r;
    asm("mul.rn.bf16x2 %0, %1, %2;" : "=r"(r) : "r"(a), "r"(b));
    return r;
}
__device__ __forceinline__ bool mbar_test_cluster(uint32_t bar, uint32_t parity) {
    uint32_t ok;
    asm volatile("{.reg .pred p; mbarrier.test_wait.parity.acquire.cluster.shared::cta.b64 p, [%1], %2; selp.u32 %0,1,0,p;}"
                 : "=r"(ok) : "r"(bar), "r"(parity) : "memory");
    return ok;
}
__device__ __forceinline__ void ldg_nc_if(uint4& v, const void* a, bool pred) {
    asm volatile("{.reg .pred p; setp.ne.b32 p, %5, 0; @p ld.global.nc.v4.u32 {%0,%1,%2,%3}, [%4];}"
                 : "+r"(v.x), "+r"(v.y), "+r"(v.z), "+r"(v.w) : "l"(a), "r"((int)pred) : "memory");
}
__device__ __forceinline__ void lds128_if(uint4& v, uint32_t a, bool pred) {
    asm volatile("{.reg .pred p; setp.ne.b32 p, %5, 0; @p ld.shared.v4.u32 {%0,%1,%2,%3}, [%4];}"
                 : "+r"(v.x), "+r"(v.y), "+r"(v.z), "+r"(v.w) : "r"(a), "r"((int)pred) : "memory");
}
template <int OFF>
__device__ __forceinline__ uint4 ld_b128_off(const void* p) {
    uint4 v;
    asm volatile("{.reg .b128 t; ld.relaxed.gpu.global.b128 t, [%4+%5]; mov.b128 {%0,%1,%2,%3}, t;}"
                 : "=r"(v.x), "=r"(v.y), "=r"(v.z), "=r"(v.w) : "l"(p), "n"(OFF) : "memory");
    return v;
}
template <int OFF>
__device__ __forceinline__ void st_b128_off(void* p, const uint4& v) {
    asm volatile("{.reg .b128 t; .reg .b64 a, b; mov.b64 a, {%1,%2}; mov.b64 b, {%3,%4}; mov.b128 t, {a, b};"
                 " st.relaxed.gpu.global.b128 [%0+%5], t;}" ::"l"(p), "r"(v.x), "r"(v.y), "r"(v.z), "r"(v.w), "n"(OFF) : "memory");
}
__device__ __forceinline__ void st_relaxed_if(unsigned int* p, uint32_t v, bool pred) {
    asm volatile("{.reg .pred p; setp.ne.b32 p, %2, 0; @p st.relaxed.gpu.global.u32 [%0], %1;}" ::"l"(p), "r"(v), "r"((int)pred) : "memory");
}
__device__ __forceinline__ void wait_hint(const unsigned int* p, uint32_t par) {
    uint32_t n = 0;
#pragma unroll 1
    while (__any_sync(0xffffffffu, (ld_relaxed(p) ^ par) & 1u)) { if (++n > SPIN_LIMIT) break; }
}
__device__ __forceinline__ uint32_t clk() { uint64_t c; asm volatile("mov.u64 %0, %%clock64;" : "=l"(c)::"memory"); return (uint32_t)c; }
__device__ __forceinline__ void until(uint32_t t) { while ((int)(clk() - t) < 0) {} }
__device__ __forceinline__ uint32_t lds32(uint32_t a) {
    uint32_t v;
    asm volatile("ld.shared.u32 %0, [%1];" : "=r"(v) : "r"(a) : "memory");
    return v;
}
__device__ __forceinline__ void ld_b128_if(uint4& v, const void* p, bool pred) {
    asm volatile("{.reg .b128 t; .reg .pred p; setp.ne.b32 p, %5, 0; mov.b128 t, {%0,%1,%2,%3};"
                 " @p ld.relaxed.gpu.global.b128 t, [%4]; mov.b128 {%0,%1,%2,%3}, t;}"
                 : "+r"(v.x), "+r"(v.y), "+r"(v.z), "+r"(v.w) : "l"(p), "r"((int)pred) : "memory");
}
template <int OFF>
__device__ __forceinline__ void st32_off(void* p, uint32_t v) {
    asm volatile("st.relaxed.gpu.global.u32 [%0+%2], %1;" ::"l"(p), "r"(v), "n"(OFF) : "memory");
}
template <int N>
__device__ __forceinline__ void mbar_arrive_n_if(uint32_t bar, bool pred) {
    asm volatile("{.reg .pred p; setp.ne.b32 p, %1, 0; @p mbarrier.arrive.shared::cta.b64 _, [%0], %2;}" ::"r"(bar), "r"((int)pred), "n"(N) : "memory");
}
__device__ __forceinline__ void mbar_arrive_cluster2_if(uint32_t bar, bool pred) {
    asm volatile("{.reg .pred p; setp.ne.b32 p, %1, 0; @p mbarrier.arrive.shared::cluster.b64 _, [%0], 2;}"
                 ::"r"(bar), "r"((int)pred) : "memory");
}
__device__ __forceinline__ int sel(int a, int b, bool p) {
    int r;
    asm("{.reg .pred q; setp.ne.b32 q, %3, 0; selp.b32 %0, %1, %2, q;}" : "=r"(r) : "r"(a), "r"(b), "r"((int)p));
    return r;
}
__device__ __forceinline__ void out_piece(void* p, float s, const uint4& w, float a0, float a1, float a2, float a3, float a4, float a5,
                                          float a6, float a7) {
    uint4 z;
    z.x = pack_bf16(fmaf(s, a0, bflo(w.x)), fmaf(s, a1, bfhi(w.x)));
    z.y = pack_bf16(fmaf(s, a2, bflo(w.y)), fmaf(s, a3, bfhi(w.y)));
    z.z = pack_bf16(fmaf(s, a4, bflo(w.z)), fmaf(s, a5, bfhi(w.z)));
    z.w = pack_bf16(fmaf(s, a6, bflo(w.w)), fmaf(s, a7, bfhi(w.w)));
    stg_off<0>(p, z);
    __syncwarp();
}
__device__ __forceinline__ uint32_t watch(const unsigned int* p, uint32_t par) {
    uint32_t n;
    p += threadIdx.x & 3;
    uint32_t a = ld_relaxed(p), b;
#pragma unroll 1
    for (n = 0; n < SPIN_LIMIT; n++) {
        if (!__any_sync(0xffffffffu, (a ^ par) & 1u)) break;
        a = ld_relaxed(p);
    }
    return n;
}
__device__ __forceinline__ uint32_t gtime() { uint64_t t; asm volatile("mov.u64 %0, %%globaltimer;" : "=l"(t)::"memory"); return (uint32_t)t; }
__device__ __forceinline__ uint32_t stamp(const unsigned int* p, uint32_t par) {
    uint32_t a, g;
#pragma unroll 1
    for (uint32_t n = 0; n < SPIN_LIMIT; n++) {
        asm volatile("{.reg .b64 t; ld.relaxed.gpu.global.b64 t, [%2]; mov.b64 {%0,%1}, t;}" : "=r"(a), "=r"(g) : "l"(p) : "memory");
        if (!__any_sync(0xffffffffu, (a ^ par) & 1u)) break;
    }
    const uint32_t ns = min(gtime() - g, 4096u), now = clk();
    return now - a < 8192u ? a : now - (ns + (ns >> 1) + (ns >> 4)) + GMARG;
}
__device__ __forceinline__ void put_stamp_if(unsigned int* p, uint32_t t, bool pred) {
    asm volatile("{.reg .pred p; .reg .b64 t; setp.ne.b32 p, %2, 0; mov.b64 t, {%1, %3}; @p st.relaxed.gpu.global.b64 [%0], t;}"
                 ::"l"(p), "r"(t), "r"((int)pred), "r"(gtime()) : "memory");
}
template <int H>
__device__ __forceinline__ void fetch_job(const Params& p, unsigned char* smem, uint32_t sb, int cta, int i, uint32_t par) {
    const int lane = threadIdx.x & 31, tn = (cta >> 1) & 3, comp = cta & 1;
    const int src = (cta & ~6) + 2 * SRC(i, tn);
    const int ua = i == 0 ? a_addr(29) : i == 1 ? a_addr(30) : a_addr(31), ub = i == 0 ? b_addr(29) : i == 1 ? b_addr(30) : b_addr(31);
    const uint32_t land = sb + B_LAND + 8 * (3 * H + i);
    uint32_t ph = 0, th = 0;
#pragma unroll
    for (int c = 0; c < 2; c++) {
        const uint32_t dst = sb + (c ? ub + H * 8192 : ua + (comp ^ H) * 8192);
        const int row = (src * 2 + (comp ^ c)) * 128 + H * 64;
        mbar_expect_tx_elect(land, 8192);
        constexpr int TM[4] = {D_RD0, D_RD1, L_RD0, L_RD1};
        uint32_t np_ = 0;
        if (c == 0 && H == 1) {
            mbar_wait(sb + B_TH + 8 * i, 0);
            th = lds32(sb + M_TH + 4 * i);
        }
        if (c == 0 && H == 0) {
            mbar_wait(sb + B_S0, 0);
            const uint32_t t0 = clk();
            if (H == 0 && i == 0) {
                mbar_wait(sb + B_FULL + 8 * (31 % NA), (31 / NA) & 1);
                const uint32_t d = max(clk() - t0, 180u) - 180u;
                put_stamp_if(g_hint + cta * 256 + 128, ((t0 + d) & ~1u) | par, lane == 0);
            }
            until(t0 + SDEL);
            th = stamp(g_hint + src * 256 + 128, par) + SG * SRC(i, tn);
            if (lane == 0) { *(volatile uint32_t*)(smem + M_TH + 4 * i) = th; mbar_arrive(sb + B_TH + 8 * i); }
            __syncwarp();
        }
        if (c == 0) mbar_wait(sb + B_EA, 0);
        if (c != H) mbar_wait(sb + B_EMPTY + ua / 2048, ((29 + i) / NA) & 1);
        if (TM[2 * c + H]) {
            until(th + TM[2 * c + H]);
        } else {
            if (PDEL && c == 0 && H == 0) until(clk() + PDEL);
            np_ = watch(g_hint + src * 256 + (2 * c + H) * 32, par);
        }
        if (MARG) until(clk() + MARG);
#pragma unroll 1
        for (uint32_t r = 0; r < SPIN_LIMIT; r++) {
            tma2d_elect(dst, &p.mF, 0, row, land);
            mbar_wait(land, ph);
            ph ^= 1;
            const uint32_t a = dst + (lane >> 2) * 132 + (lane & 3) * 32;
            uint32_t v[8], m0 = 0, m1 = ~0u;
#pragma unroll
            for (int k = 0; k < 8; k++) v[k] = lds32(a + k * 1024);
#pragma unroll
            for (int k = 0; k < 8; k++) { m0 |= v[k]; m1 &= v[k]; }
            if (__all_sync(0xffffffffu, (par ? m1 : ~m0) & 1u)) break;
            mbar_expect_tx_elect(land, 8192);
        }
        mbar_arrive_if(sb + B_VAL + 8 * (6 * c + 3 * H + i), lane == 0);
        __syncwarp();
    }
}
__device__ __forceinline__ int dcol(int p, int tn) {
    if (p < 2) return tn * 128 + p * 64;
    const int i = (p - 2) % 3;
    return SRC(i, tn) * 128 + (p >= 5 ? 64 : 0);
}
__host__ __device__ constexpr int dpos_load(int p) { return (p & ~1) == R6POS ? -1 : 32 + ((p & ~1) > R6POS ? p / 2 - 1 : p / 2); }
__host__ __device__ constexpr int dpos_addr(int p) { return dpos_load(p) < 0 ? 6 * REGION + (p & 1) * 16384 : (p & 1) ? b_addr(dpos_load(p) - 6) : a_addr(dpos_load(p) - 6); }
__host__ __device__ constexpr int load_dpos(int l) { return 2 * (l - 32) + (2 * (l - 32) >= R6POS ? 2 : 0); }

__device__ __forceinline__ uint32_t router_key(float score, int row) {
    const float r = score + 0.0f;
    uint32_t u = pack_bf16(r, 0.f) & 0xffffu;
    u = (u & 0x8000u) ? (~u & 0xffffu) : (u | 0x8000u);
    if (r != r) u = 0;
    return (u << 16) | (uint32_t)(0x7fff - row);
}

#define g_fb_h ((float*)g_xch)
#define g_fb_upd (g_fb_h + 2048)
#define g_fb_gate (g_fb_h + 4096)
#define g_fb_keys ((unsigned int*)g_xch + 8192)
__global__ void fb_hidden(const bf16* x, const bf16* dre, const bf16* dim, const bf16* gw, const bf16* wr) {
    __shared__ float xs[D_];
    const int s = blockIdx.x, t = threadIdx.x;
    xs[t] = __bfloat162float(x[s * D_ + t]);
    __syncthreads();
    float a = 0.f, b = 0.f;
    for (int d = 0; d < D_; d++) { a = fmaf(xs[d], __bfloat162float(dre[t * D_ + d]), a); b = fmaf(xs[d], __bfloat162float(dim[t * D_ + d]), b); }
    ((bf16*)g_ab)[s * 1024 + t] = __float2bfloat16(a);
    ((bf16*)g_ab)[s * 1024 + 512 + t] = __float2bfloat16(b);
    if (t == 0) {
        float u = 0.f, v = 0.f;
        for (int d = 0; d < D_; d++) { u = fmaf(xs[d], __bfloat162float(gw[d]), u); v = fmaf(xs[d], __bfloat162float(wr[d]), v); }
        g_fb_gate[s] = sigmoidf_(u);
        g_fb_keys[s] = router_key(v, s);
    }
}
__device__ uint32_t fb_best() {
    uint32_t k = 0;
    for (int i = 0; i < S_; i++) k = max(k, g_fb_keys[i]);
    return k;
}
__global__ void fb_ffn1(const bf16* x, const bf16* wg, const bf16* wu) {
    const int f = blockIdx.x * blockDim.x + threadIdx.x, idx = 0x7fff - (int)(fb_best() & 0x7fffu);
    float a = 0.f, b = 0.f;
    for (int d = 0; d < D_; d++) {
        const float xv = __bfloat162float(x[idx * D_ + d]);
        a = fmaf(xv, __bfloat162float(wg[d * F_ + f]), a); b = fmaf(xv, __bfloat162float(wu[d * F_ + f]), b);
    }
    g_fb_h[f] = a * sigmoidf_(a) * b;
}
__global__ void fb_ffn2(const bf16* wd) {
    const int e = blockIdx.x * blockDim.x + threadIdx.x;
    const uint32_t u = fb_best() >> 16, rb = (u & 0x8000u) ? (u & 0x7fffu) : (~u & 0xffffu);
    float a = 0.f;
    for (int f = 0; f < F_; f++) a = fmaf(g_fb_h[f], __bfloat162float(wd[f * D_ + e]), a);
    g_fb_upd[e] = a * sigmoidf_(__uint_as_float(rb << 16));
}
__global__ void fb_seq(const bf16* x, const bf16* cre, const bf16* cim, bf16* out) {
    __shared__ float c[2][S_];
    __shared__ int idx;
    const int t = blockIdx.x, e = threadIdx.x;
    for (int i = e; i < S_; i += D_) { c[0][i] = __bfloat162float(cre[t * S_ + i]); c[1][i] = __bfloat162float(cim[t * S_ + i]); }
    if (e == 0) idx = 0x7fff - (int)(fb_best() & 0x7fffu);
    __syncthreads();
    float y = 0.f;
    for (int s = 0; s < S_; s++)
        y += c[0][s] * __bfloat162float(((const bf16*)g_ab)[s * 1024 + e]) - c[1][s] * __bfloat162float(((const bf16*)g_ab)[s * 1024 + 512 + e]);
    const float g = g_fb_gate[t];
    out[t * D_ + e] = __float2bfloat16(g * y + (1.f - g) * (__bfloat162float(x[t * D_ + e]) + (t == idx ? g_fb_upd[e] : 0.f)));
}

__device__ __forceinline__ void spare_job(const Params& p, unsigned char* smem, int sp, uint32_t tstart) {
    const int tid = threadIdx.x, warp = tid >> 5, lane = tid & 31;
    const uint32_t e1 = *(volatile unsigned int*)&g_epoch[NCTA + sp] + 1u;
    const uint32_t par = e1 & 1u;
    uint32_t* red = (uint32_t*)smem;
    __syncthreads();
    if (tid == 0) *(volatile unsigned int*)&g_epoch[NCTA + sp] = e1;
    if (warp >= 8) {
#pragma unroll 1
        for (int i = 0; i < 8; i++) {
            while ((uint32_t)clock64() - tstart < PFD_T0 + i * PFD_DT) __nanosleep(50);
            prefetch_l2((const char*)((sp & 2) ? p.dim : p.dre) + (sp & 1) * 262144 + i * 32768 + (tid - 256) * 128);
        }
    }
    if (warp == 0) {
        const uint4 k4 = wait_tags(g_keys + lane * 4, 15, par);
        const uint32_t k = __reduce_max_sync(0xffffffffu, max(max(k4.x, k4.y), max(k4.z, k4.w)));
        if (lane == 0) red[16] = k;
    }
    __syncthreads();
    while ((uint32_t)clock64() - tstart < SUM_T0) __nanosleep(200);
    float4 s = make_float4(0.f, 0.f, 0.f, 0.f);
    if (warp < 14) {
        uint32_t n = 0;
        while ((int)(ld_relaxed(g_phint + (sp * 16 + warp) * 8) - e1 * 8u) < 0) {
            __nanosleep(40);
            if (++n > SPIN_LIMIT) break;
        }
        const unsigned int* src = g_part + warp * 4 * D_ + sp * 128 + lane * 4;
        uint4 v[4];
        while (true) {
            uint32_t bad = 0;
#pragma unroll
            for (int i = 0; i < 4; i++) v[i] = ld_relaxed4(src + i * D_);
#pragma unroll
            for (int i = 0; i < 4; i++) bad |= (v[i].x ^ par) | (v[i].y ^ par) | (v[i].z ^ par) | (v[i].w ^ par);
            if (!__any_sync(0xffffffffu, bad & 1u)) break;
            if (++n > SPIN_LIMIT) break;
        }
#pragma unroll
        for (int i = 0; i < 4; i++) {
            s.x += __uint_as_float(v[i].x); s.y += __uint_as_float(v[i].y);
            s.z += __uint_as_float(v[i].z); s.w += __uint_as_float(v[i].w);
        }
    }
    float* acc = (float*)(smem + 1024);
    *(float4*)&acc[warp * 128 + lane * 4] = s;
    __syncthreads();
    if (tid < 128) {
        float t = 0.f;
#pragma unroll
        for (int i = 0; i < 16; i++) t += acc[i * 128 + tid];
        const uint32_t u = red[16] >> 16;
        const uint32_t rb = (u & 0x8000u) ? (u & 0x7fffu) : (~u & 0xffffu);
        st_relaxed(&g_upd[sp * 128 + tid], tagf(t * sigmoidf_(__uint_as_float(rb << 16)), par));
    }
}

__global__ void __cluster_dims__(2, 1, 1) __launch_bounds__(NTHREADS, 1)
fused_kernel(const char* pc0, const char* pc1, const char* px, const __grid_constant__ Params p) {
    extern __shared__ __align__(1024) unsigned char smem[];
    const uint32_t sb = smem_u32(smem);
    const int tid = threadIdx.x, warp = tid >> 5, lane = tid & 31;
    const int rank = blockIdx.x & 1;
    {
        const uint32_t b = blockIdx.x;
        const char* q0 = (rank ? pc1 : pc0) + (uint32_t)((b >> 1) * 32 + tid) * (S_ * 2);
        const char* q1 = px + (uint32_t)(b * 4 + tid - 32) * 128;
        asm volatile("{.reg .pred p, q; setp.lt.u32 p, %2, 32; @p prefetch.global.L2 [%0]; setp.lt.u32 q, %3, 4; @q prefetch.global.L2 [%1];}"
                     ::"l"(q0), "l"(q1), "r"(tid | (b & 128)), "r"((tid | (b & 128)) - 32));
    }
    const uint32_t tstart = clk();
    uint32_t smid;
    asm volatile("mov.u32 %0, %%smid;" : "=r"(smid));
    const int u = smid >> 1, v7 = ((u - 32) * 37) >> 8;
    const int tn = sel(u >> 3, sel(v7, u - 62, u < 60), u < 32);
    const int tm = sel(u & 7, sel(u - 23 - 7 * v7, 8, u < 60), u < 32);
    const bool spare = tn < 0;
    const int role = tm * 4 + tn;
    const int comp = rank;
    const CUtensorMap* mC = comp ? &p.mCim : &p.mCre;
#define FIRST(j) do { tma2d(sb + (j) * 16384, mC, (j) * 64, tm * 128, sb + B_FULL + 8 * (j));                      \
                      if ((j) < NB) tma3d(sb + (NA + (j)) * 16384, &p.mX2, (j) * 64, tn * 2, sb + B_FULL + 8 * (j)); } while (0)
#define ARM(j) do { mbar_init(sb + B_FULL + 8 * (j), 1); mbar_expect_tx(sb + B_FULL + 8 * (j), 32768); } while (0)
    if (tid == 384) {
        ARM(0);
        if (!spare) FIRST(0);
        ARM(2); ARM(4); if (NA > 6) ARM(6);
    }
    if (tid == 416) {
        ARM(1);
        if (T_1) until(tstart + T_1);
        if (!spare) FIRST(1);
        ARM(3); ARM(5); if (NA > 7) ARM(7);
    }
    if (PF0 > 1 && ((tid - PFW * 32) | (blockIdx.x & 128)) < 36) {
        const uint32_t b = blockIdx.x, t = tid - PFW * 32;
        const char* q = t < 32 ? (rank ? pc1 : pc0) + (uint32_t)((b >> 1) * 32 + t) * (S_ * 2) : px + (uint32_t)(b * 4 + t - 32) * 128;
#pragma unroll
        for (int j = 1; j < PF0; j++) {
            until(tstart + P_1 + (j - 1) * P_D);
            prefetch_l2(q + j * (t < 32 ? 128 : 65536));
        }
    }
    __syncwarp();
    if (spare) {
        spare_job(p, smem, smid & 3, tstart);
        return;
    }
    const int cta = role * 2 + rank;
    const int wu = __shfl_sync(0xffffffffu, warp, 0);
    {
        if (lane == 0) {
            if (wu < 12) {
                mbar_init(sb + (wu < 11 ? B_S1 + 8 * wu : B_XF), 1);
                mbar_init(sb + B_EMPTY + 8 * wu, wu < 8 ? 4 : wu == 9 ? 5 : 1);
                if (wu == 6) mbar_expect_tx(sb + B_HX, 256);
                if (wu >= 10) mbar_expect_tx(sb + B_EMPTY + 8 * wu, 8192);
            }
            asm volatile("fence.mbarrier_init.release.cluster;" ::: "memory");
        }
    }
    __syncwarp();
    asm volatile("barrier.cluster.arrive.relaxed.aligned;" ::: "memory");

    if (wu >= 12) {
        asm volatile("setmaxnreg.dec.sync.aligned.u32 " STR(RU) ";");
        const uint32_t sbu = sb;
    if (wu < 14) {
        const int jj = wu - 10;
        until(tstart + T_2 + (jj - 2) * PACE);
        tma2d_elect(sb + jj * 16384, mC, jj * 64, tm * 128, sb + B_FULL + 8 * jj);
        tma3d_elect(sb + (NA + jj) * 16384, &p.mX2, jj * 64, tn * 2, sb + B_FULL + 8 * jj);
    }
    __syncwarp();
    asm volatile("barrier.cluster.wait.acquire.aligned;" ::: "memory");

        if (wu == 12) {
#pragma unroll
            for (int step = 4; step < 32; step++) {
                const int slot = step % NSTAGE;
                const uint32_t full = sbu + B_FULL + 8 * slot;
                if (step >= NA) mbar_wait(sbu + B_EMPTY + 8 * slot, (step / NSTAGE - 1) & 1);
                if (step < NPACE) until(tstart + T_2 + (step - 2) * PACE);
                tma2d_elect(sbu + a_addr(step), mC, step * 64, tm * 128, full);
                if (step >= NA) mbar_expect_tx_elect(full, 32768);
            }
        } else if (wu == 13) {
            const CUtensorMap* mD = comp ? &p.mDim : &p.mDre;
#pragma unroll
            for (int step = 4; step < 33; step++) {
                const uint32_t full = sbu + B_FULL + 8 * (step % NA);
                if (step >= NB) mbar_wait(sbu + B_EMPTY + 8 * (b_dep(step) % NA), (b_dep(step) / NA) & 1);
                if (step < NB) {
                    until(tstart + T_2 + (step - 2) * PACE);
                    tma3d_elect(sbu + b_addr(step), &p.mX2, step * 64, tn * 2, full);
                } else if (step < 32) {
                    tma2d_pair_elect(sbu + b_addr(step) + rank * 8192, &p.mX, tn * 128 + rank * 64, step * 64, full);
                } else {
                    tma5d_elect(sbu + a_addr(26), mD, dcol(load_dpos(step), tn), tn * 4, full);
                    tma5d_elect(sbu + b_addr(26), mD, dcol(load_dpos(step) + 1, tn), tn * 4, full);
                    mbar_expect_tx_elect(full, 32768);
                }
            }
            mbar_wait(sbu + B_PRE, 0);
            mbar_wait(sbu + B_R6, 0);
            tma5d_elect(sbu + 6 * REGION, mD, dcol(R6POS, tn), tn * 4, sbu + B_D6);
            tma5d_elect(sbu + 6 * REGION + 16384, mD, dcol(R6POS + 1, tn), tn * 4, sbu + B_D6);
            mbar_expect_tx_elect(sbu + B_D6, 32768);
            __syncwarp();
#pragma unroll
            for (int c = 0; c < 4; c++) mbar_expect_tx_elect(sbu + B_DL + 8 * c, 16384);
            mbar_wait(sbu + B_S1, 0);
            const uint32_t tq = clk();
#pragma unroll
            for (int c = 0; c < 4; c++) {
                constexpr int TD[4] = {T_D4, T_D5, T_D6, T_D7};
                if (!(c & 1)) mbar_wait(sbu + B_EMPTY + 8 * ((27 + c / 2) % NA), ((27 + c / 2) / NA) & 1);
                if (TD[c]) until(tq + TD[c]);
                tma5d_elect(sbu + dpos_addr(4 + c), mD, dcol(4 + c, tn), tn * 4, sbu + B_DL + 8 * c);
            }
        } else if (wu == 14) {
            if (lane == 0) {
                asm volatile("prefetch.tensormap [%0];" ::"l"(&p.mX) : "memory");
                asm volatile("prefetch.tensormap [%0];" ::"l"(&p.mF) : "memory");
                asm volatile("prefetch.tensormap [%0];" ::"l"(comp ? &p.mDim : &p.mDre) : "memory");
            }
            if (lane == 0) {
                asm volatile("st.shared::cluster.u32 [%0], %1;" ::"r"(mapa(sb + M_ROLE, rank ^ 1)), "r"(role) : "memory");
                mbar_wait(sb + B_FULL, 0);
#pragma unroll 1
                for (int i = 0; i < 29; i++) mbar_init(sbu + B_LAND + 8 * i, i == 25 ? 4 : 1);
                fence_proxy_async_smem();
                mbar_arrive(sbu + B_PRE);
            }
            __syncwarp();
            const uint32_t wo = (uint32_t)((cta >> 6) * 256 + ((cta >> 1) & 31)) * (F_ * 2) + rank * F_ + lane * 128;
            const char* wb = (const char*)p.wg + wo;
            const char* wc = (const char*)p.wu + wo;
#pragma unroll 1
            for (int i = 0; i < 8 * WPF; i++) {
                while ((uint32_t)clock64() - tstart < PF_T0 + i * PF_DT + (cta & 3) * (PF_DT / 4)) __nanosleep(20);
                if (lane < 14) { prefetch_l2(wb + i * (64 * F_)); prefetch_l2(wc + i * (64 * F_)); }
            }
        } else {
            if (cta < FFN_CTAS) {
                const uint32_t t1 = tstart + FFN_T0 + (rank + 2 * (tm & 1)) * FFN_PH;
#pragma unroll
                for (int i = 0; i < 12; i++) {
                    const int qu = i < 4 ? 2 + (i >> 1) : (i - 4) >> 1;
                    const uint32_t bar = sb + B_FFN + 8 * (i < 4 ? 3 : qu), dst = sb + 6 * REGION + (i & 1) * 16384 + qu * 4096;
                    if (i == 8) { mbar_wait(sb + B_PRE, 0); mbar_wait(sb + B_VD, 0); }
                    if (i == 0 || (i >= 4 && !(i & 1))) mbar_expect_tx_elect(bar, i ? 8192 : 16384);
                    while ((int)(clk() - t1 - i * FFN_DT) < 0) __nanosleep(20);
                    if (i < 4) tma2d_elect(dst, &p.mWd, rank * 256, role * 32 + i * 8, bar);
                    else tma2d_elect(dst, (i & 1) ? &p.mWu : &p.mWg, role * 32, rank * 256 + qu * 64, bar);
                }
            }
            __syncwarp();
        }
        mbar_wait(sbu + B_EPOCH, 0);
        const uint32_t par = (*(volatile uint32_t*)(smem + M_EPOCH) + 1u) & 1u;
        if (wu != 13) {
            mbar_wait(sbu + B_PRE, 0);
            fetch_job<0>(p, smem, sbu, cta, wu == 12 ? 0 : wu - 13, par);
        }
    } else if (wu >= 8) {
        asm volatile("setmaxnreg.dec.sync.aligned.u32 " STR(RS_) ";");
        asm volatile("barrier.cluster.wait.acquire.aligned;" ::: "memory");
        const int t = tid - 256, w = wu - 8;
        if (t == 0) {
            const uint32_t e = *(volatile unsigned int*)&g_epoch[cta];
            *(volatile uint32_t*)(smem + M_EPOCH) = e;
            *(volatile unsigned int*)&g_epoch[cta] = e + 1;
            mbar_arrive(sb + B_EPOCH);
        }
        const bool ffn = cta < FFN_CTAS;
        const uint4 gw0 = ldg_nc_off<0>(p.gate_w + lane * 8), gw1 = ldg_nc_off<512>(p.gate_w + lane * 8);
        const uint4 rw0 = ldg_nc_off<0>(p.w_r + lane * 8), rw1 = ldg_nc_off<512>(p.w_r + lane * 8);
        mbar_wait(sb + B_EPOCH, 0);
        const uint32_t par = (*(volatile uint32_t*)(smem + M_EPOCH) + 1u) & 1u;
        while ((uint32_t)clock64() - tstart < ROUTER_T0 + (2 * w + rank) * ROUTER_DT) __nanosleep(20);
        {
            const int row0 = cta * 16 + w * 4;
            const char* xp = (const char*)p.x + (uint32_t)row0 * (D_ * 2) + lane * 16;
            uint4 xa[4], xb[4];
            xa[0] = ldg_nc_off<0>(xp);    xb[0] = ldg_nc_off<512>(xp);  xa[1] = ldg_nc_off<1024>(xp); xb[1] = ldg_nc_off<1536>(xp);
            xa[2] = ldg_nc_off<2048>(xp); xb[2] = ldg_nc_off<2560>(xp); xa[3] = ldg_nc_off<3072>(xp); xb[3] = ldg_nc_off<3584>(xp);
            float a[8];
#pragma unroll
            for (int i = 0; i < 4; i++) {
                const uint32_t xv[8] = {xa[i].x, xa[i].y, xa[i].z, xa[i].w, xb[i].x, xb[i].y, xb[i].z, xb[i].w};
                const uint32_t gv[8] = {gw0.x, gw0.y, gw0.z, gw0.w, gw1.x, gw1.y, gw1.z, gw1.w};
                const uint32_t rv[8] = {rw0.x, rw0.y, rw0.z, rw0.w, rw1.x, rw1.y, rw1.z, rw1.w};
                float uu = 0.f, vv = 0.f;
#pragma unroll
                for (int j = 0; j < 8; j++) {
                    uu = fmaf(bflo(xv[j]), bflo(gv[j]), uu); uu = fmaf(bfhi(xv[j]), bfhi(gv[j]), uu);
                    vv = fmaf(bflo(xv[j]), bflo(rv[j]), vv); vv = fmaf(bfhi(xv[j]), bfhi(rv[j]), vv);
                }
                a[i] = uu; a[4 + i] = vv;
            }
            halve<4, 16>(a); halve<2, 8>(a); halve<1, 4>(a);
            {
                const float b1 = __shfl_xor_sync(0xffffffffu, a[0], 1), b2 = __shfl_xor_sync(0xffffffffu, a[0], 2),
                            b3 = __shfl_xor_sync(0xffffffffu, a[0], 3);
                a[0] = (a[0] + b1) + (b2 + b3);
            }
            const int row = row0 + ((lane >> 2) & 3);
            if (lane < 16 && (lane & 3) == 0) st_relaxed(&g_gate[row], tagf(sigmoidf_(a[0]), par));
            const uint32_t best = __reduce_max_sync(0xffffffffu, lane >= 16 && (lane & 3) == 0 ? router_key(a[0], row) : 0u);
            if (lane == 0) *(volatile uint32_t*)(smem + M_RED + w * 4) = best;
            named_bar(1, 128);
            if (t < 8) {
                const uint4 k = *(const uint4*)(smem + M_RED);
                st_key(&g_keys[t * NCTA + cta], max(max(k.x, k.y), max(k.z, k.w)) | (par << 15));
            }
        }
        {
            const uint32_t np = par ^ 1u;
            if (t < 64) st_relaxed(g_hint + cta * 256 + (t >> 3) * 32 + (t & 7), np);
            if (PREW) {
#pragma unroll 1
                for (int i = 0; i < 16; i++) {
                    st_relaxed_b128(g_frag + cta * 2048 + i * 128 + t, np, np, np, np);
                    __nanosleep(40);
                }
            }
            mbar_arrive_warp(sb + B_PRE);
        }
        uint32_t vd[32];
        if (ffn) {
            mbar_wait(sb + B_FFN + 24, 0);
#pragma unroll
            for (int j = 0; j < 32; j++) vd[j] = lds32(sb + 6 * REGION + ((j >> 3) & 1) * 16384 + (2 + (j >> 4)) * 4096 + (j & 7) * 512 + t * 4);
            mbar_wait(sb + B_PRE, 0);
            mbar_arrive_warp(sb + B_VD);
        }
        if (w == 0) {
            const uint4 k4 = wait_tags(g_keys + (tm & 7) * NCTA + lane * 4, 15, par);
            const uint32_t k = __reduce_max_sync(0xffffffffu, max(max(k4.x, k4.y), max(k4.z, k4.w)));
            if (lane == 0) *(volatile uint32_t*)(smem + M_KEY) = k;
            sts128(sb + M_UPD + lane * 16, ldg_nc_off<0>(p.x + (0x7fff - (k & 0x7fffu)) * D_ + rank * 256 + lane * 8));
        } else if (w == 1) {
            const uint4 g4 = wait_tags(g_gate + tm * 128 + lane * 4, 0, par);
            *(uint4*)(smem + M_G + lane * 16) = make_uint4(g4.x & ~1u, g4.y & ~1u, g4.z & ~1u, g4.w & ~1u);
            mbar_arrive_warp(sb + B_GATE);
        }
        named_bar(1, 128);
        const int idx = 0x7fff - (int)(*(volatile uint32_t*)(smem + M_KEY) & 0x7fffu);
        if (ffn) {
            float a[16], xs[8];
#pragma unroll
            for (int i = 0; i < 8; i++) {
                a[i] = 0.f; a[8 + i] = 0.f;
                xs[i] = __bfloat162float(((const bf16*)(smem + M_UPD))[32 * i + (t >> 2)]);
            }
#pragma unroll
            for (int i = 0; i < 8; i++) {
                if (!(i & 1)) mbar_wait(sb + B_FFN + 4 * i, i == 6);
                const uint4 vg = lds128(sb + 6 * REGION + i * 2048 + t * 16);
                const uint4 vu = lds128(sb + 6 * REGION + 16384 + i * 2048 + t * 16);
                const uint32_t g4[4] = {vg.x, vg.y, vg.z, vg.w};
                const uint32_t u4[4] = {vu.x, vu.y, vu.z, vu.w};
#pragma unroll
                for (int j = 0; j < 4; j++) {
                    a[2 * j] = fmaf(xs[i], bflo(g4[j]), a[2 * j]);         a[2 * j + 1] = fmaf(xs[i], bfhi(g4[j]), a[2 * j + 1]);
                    a[8 + 2 * j] = fmaf(xs[i], bflo(u4[j]), a[8 + 2 * j]); a[9 + 2 * j] = fmaf(xs[i], bfhi(u4[j]), a[9 + 2 * j]);
                }
            }
            halve<8, 16>(a); halve<4, 8>(a); halve<2, 4>(a);
            float* red = (float*)(smem + M_UPD);
            *(float2*)&red[w * 64 + (lane >> 4) * 32 + (lane & 3) * 8 + ((lane >> 2) & 3) * 2] = make_float2(a[0], a[1]);
            named_bar(1, 128);
            mbar_arrive_if(sb + B_R6, t == 0);
            const float sg = red[lane] + red[64 + lane] + red[128 + lane] + red[192 + lane];
            const float su = red[32 + lane] + red[96 + lane] + red[160 + lane] + red[224 + lane];
            if (w < 2) {
                asm volatile("st.async.weak.shared::cluster.mbarrier::complete_tx::bytes.f32 [%0], %1, [%2];"
                             ::"r"(mapa(sb + M_HX + t * 4, rank ^ 1)), "f"(w ? su : sg), "r"(mapa(sb + B_HX, rank ^ 1)) : "memory");
            }
            named_bar(1, 128);
            mbar_wait_cluster(sb + B_HX, 0);
            const float pg = ((const float*)(smem + M_HX))[lane], pu = ((const float*)(smem + M_HX))[32 + lane];
            const float gs = sg + pg, us = su + pu;
            float* hrow = red + w * 32;
            hrow[lane] = gs * sigmoidf_(gs) * us;
            __syncwarp();
            float o0 = 0.f, o1 = 0.f;
#pragma unroll
            for (int j4 = 0; j4 < 8; j4++) {
                const float4 hv = *(const float4*)&hrow[j4 * 4];
                o0 = fmaf(hv.x, bflo(vd[4 * j4]), o0);     o1 = fmaf(hv.x, bfhi(vd[4 * j4]), o1);
                o0 = fmaf(hv.y, bflo(vd[4 * j4 + 1]), o0); o1 = fmaf(hv.y, bfhi(vd[4 * j4 + 1]), o1);
                o0 = fmaf(hv.z, bflo(vd[4 * j4 + 2]), o0); o1 = fmaf(hv.z, bfhi(vd[4 * j4 + 2]), o1);
                o0 = fmaf(hv.w, bflo(vd[4 * j4 + 3]), o0); o1 = fmaf(hv.w, bfhi(vd[4 * j4 + 3]), o1);
            }
            asm volatile("st.relaxed.gpu.global.v2.u32 [%0], {%1,%2};" ::"l"(&g_part[role * D_ + rank * 256 + t * 2]),
                         "r"(tagf(o0, par)), "r"(tagf(o1, par)) : "memory");
            if (lane == 0) asm volatile("red.relaxed.gpu.global.add.u32 [%0], 1;" ::"l"(g_phint + ((rank * 2 + (w >> 1)) * 16 + (role >> 2)) * 8) : "memory");
        }
        if (!ffn) { mbar_wait(sb + B_PRE, 0); mbar_arrive_if(sb + B_R6, t == 0); }
        if (w < 3) {
            mbar_wait(sb + B_PRE, 0);
            fetch_job<1>(p, smem, sb, cta, w, par);
        }
        if (w == 3) {
            if ((idx >> 6) == 2 * tm + 1 - comp) {
                const uint4 u4 = wait_tags(g_upd + tn * 128 + lane * 4, 0, par);
                *(uint4*)(smem + M_RED + lane * 16) = u4;
            }
            if (*(volatile uint32_t*)(smem + M_ROLE) != (uint32_t)role) __trap();
            mbar_arrive_warp(sb + B_SIDE);
        }
    } else {
        asm volatile("setmaxnreg.inc.sync.aligned.u32 " STR(RC) ";");
        const int wg = wu >> 2;
        const uint32_t sbd = (sb & 0x3FFFF) >> 4;
        const bool lead = (tid & 127) == 0;
        const bool early = wg == comp;
        const int q = lane & 3;
        const int r0 = (warp & 3) * 16 + (lane >> 2);
        float acc[64];
        const uint32_t da0 = sbd + 0x10000 + wg * 512, db0 = sbd + 0x2000000, dd0 = sbd + 0x10000;
        const uint32_t rE = mapa(sb + B_EMPTY, rank ^ 1);
#define RELEASE(slot) do { mbar_arrive_if(sb + B_EMPTY + 8 * (slot), lead); mbar_arrive_cluster_if(rE + 8 * (slot), lead); } while (0)
#define WAITFULL(s) mbar_wait(sb + B_FULL + 8 * ((s) % NSTAGE), ((s) / NSTAGE) & 1)
#define TESTFULL(s) (PRET && mbar_test(sb + B_FULL + 8 * ((s) % NSTAGE), ((s) / NSTAGE) & 1))
#define WAITD(pos) do { if ((pos) >= 4) mbar_wait(sb + B_DL + 8 * ((pos) - 4), 0); else if (dpos_load(pos) < 0) mbar_wait(sb + B_D6, 0); else WAITFULL(dpos_load(pos) < 0 ? 0 : dpos_load(pos)); } while (0)
#define MMA_A(s, kk) wgmma128(acc, desc_lo(da0 + a_addr(s) / 16 + (kk) * 2), desc_lo(db0 + b_addr(s) / 16 + (kk) * 128), 1)
#define MMA_B(f, pos, kk, sc) wgmma128rs(acc, f, desc_lo(dd0 + dpos_addr(pos) / 16 + (kk) * 2), sc)
        asm volatile("barrier.cluster.wait.acquire.aligned;" ::: "memory");
        WAITFULL(0);
        wg_fence();
#pragma unroll
        for (int kk = 0; kk < 4; kk++) wgmma128(acc, desc_lo(da0 + kk * 2), desc_lo(db0 + NA * 1024 + kk * 128), kk != 0);
        wg_commit();
        int slot = 1, ph = 0, pslot = 0, bslot = NA + 1;
        const uint32_t ooff = (uint32_t)((tm * 128 + wg * 64 + r0) * D_ + tn * 128 + q * 8) * 2u;
        uint4 w[8];
#pragma unroll
        for (int i = 0; i < 8; i++) w[i] = make_uint4(0, 0, 0, 0);
#pragma unroll
        for (int part = 0; part <= XN; part++) {
        if (part) {
            const char* xp = (const char*)p.x + ooff;
#pragma unroll
            for (int i = (part - 1) * 8 / XN; i < part * 8 / XN; i++) ldg_nc_if(w[i], xp + (i & 1) * 8192 + (i >> 1) * 64, early);
        }
#pragma unroll 1
        for (int step = part ? XLD + (part - 1) * XD : 1; step < (part < XN ? XLD + part * XD : SP0); step++) {
            mbar_wait(sb + B_FULL + 8 * slot, ph);
            const uint32_t a = da0 + slot * 1024, b = db0 + bslot * 1024;
            wg_fence();
#pragma unroll
            for (int kk = 0; kk < EREL; kk++) wgmma128(acc, desc_lo(a + kk * 2), desc_lo(b + kk * 128), 1);
            wg_commit();
            wg_wait<1>();
            RELEASE(pslot);
            wg_fence();
#pragma unroll
            for (int kk = EREL; kk < 4; kk++) wgmma128(acc, desc_lo(a + kk * 2), desc_lo(b + kk * 128), 1);
            wg_commit();
            pslot = slot;
            if (++slot == NSTAGE) { slot = 0; ph ^= 1; }
            if (++bslot == 12) bslot = NA;
        }
        }
        mbar_wait(sb + B_PRE, 0);
        const uint32_t par = (*(volatile uint32_t*)(smem + M_EPOCH) + 1u) & 1u;
        unsigned int* hint = g_hint + cta * 256 + (early ? 0 : 64) + (warp & 3);
        uint32_t* fout = (uint32_t*)(g_frag + (cta * 2 + wg) * 1024) + (warp & 3) * 128 + lane;
        uint32_t tagm[4];
#pragma unroll
        for (int c = 0; c < 4; c++) tagm[c] = (lane & 7) == (warp & 1) * 4 + c;
        asm volatile("" : "+r"(tagm[0]), "+r"(tagm[1]), "+r"(tagm[2]), "+r"(tagm[3]), "+l"(hint), "+l"(fout));
        uint32_t th;
        if (early) {
            WAITFULL(SP0);
            wg_fence();
            MMA_A(SP0, 0); MMA_A(SP0, 1);
            wg_commit();
            wg_wait<1>();
            mbar_arrive_n_if<2>(sb + B_EMPTY + 8 * ((SP0 - 1) % NSTAGE), lead);
            bool ok = TESTFULL(SP0 + 1);
            MMA_A(SP0, 2); MMA_A(SP0, 3);
            wg_commit();
#pragma unroll
            for (int s = SP0 + 1; s < 32; s++) {
                if (!ok) WAITFULL(s);
                wg_fence();
                MMA_A(s, 0); MMA_A(s, 1);
                if (s == 30) { wg_commit(); wg_wait<1>(); mbar_arrive_if(sb + B_S0, lead); wg_fence(); }
                if (s < 31) ok = TESTFULL(s + 1);
                if (s == 31) { wg_commit(); wg_wait<1>(); mbar_arrive_if(sb + B_S1, lead); wg_fence(); }
                MMA_A(s, 2); MMA_A(s, 3);
                wg_commit();
            }
            wg_wait<0>();
            mbar_arrive_if(sb + B_EA, lead);
        } else {
            wg_wait<0>();
            mbar_arrive_n_if<2>(sb + B_EMPTY + 8 * ((SP0 - 1) % NSTAGE), lead);
#pragma unroll
            for (int s = SP0; s < 32; s++) WAITFULL(s);
            mbar_wait(sb + B_S1, 0);
            wg_fence();
#pragma unroll
            for (int s = SP0; s < 32; s++) {
                MMA_A(s, 0); MMA_A(s, 1);
                if (s > SP0) {
                    wg_commit();
                    wg_wait<1>();
                    mbar_arrive_n_if<4>(sb + B_EMPTY + 8 * ((s - 1) % NSTAGE), lead);
                    if (s == 31) { mbar_arrive_if(sb + B_S3, lead); th = 0; }
                    if (s == 30) WAITD(0);
                    wg_fence();
                }
                MMA_A(s, 2); MMA_A(s, 3);
                wg_commit();
            }
            wg_wait<0>();
            mbar_arrive_n_if<4>(sb + B_EMPTY + 8 * (31 % NSTAGE), lead);
        }
        fence_regs<0, 64>(acc);
        uint4 f[8];
#define TAG(v, c) (((v) & ~tagm[c]) | (par & tagm[c]))
#define PACK(k) f[k] = make_uint4(TAG(pack_bf16(acc[8 * (k)], acc[8 * (k) + 1]), 0), TAG(pack_bf16(acc[8 * (k) + 2], acc[8 * (k) + 3]), 2), \
                                  TAG(pack_bf16(acc[8 * (k) + 4], acc[8 * (k) + 5]), 1), TAG(pack_bf16(acc[8 * (k) + 6], acc[8 * (k) + 7]), 3))
#define SEND(k) do { st32_off<2048 * (k)>(fout, f[k].x); st32_off<2048 * (k) + 128>(fout, f[k].z);                          \
                     st32_off<2048 * (k) + 256>(fout, f[k].y); st32_off<2048 * (k) + 384>(fout, f[k].w); } while (0)
#define SENDV(k) do { st_relaxed(fout + 512 * (k), f[k].x); st_relaxed(fout + 512 * (k) + 32, f[k].z);                       \
                      st_relaxed(fout + 512 * (k) + 64, f[k].y); st_relaxed(fout + 512 * (k) + 96, f[k].w);                  \
                      if (((k) & 3) == 3 && !(D_RD0 && D_RD1 && L_RD0 && L_RD1)) st_relaxed_if(hint + 8 * ((k) & 4), par, lane == 0); } while (0)
#define OWN(k) MMA_B(f[k], (k) >> 2, (k) & 3, (k) != 0)
        const uint32_t dfa = sbd + 0x80000 + (early ? comp * 512 : 0), dfb = sbd + 0x80000 + (early ? (1 - comp) * 512 : 512);
#define MMA_F(U, pos, kk) wgmma128<0>(acc, (uint64_t)(((pos) < 5 ? dfa : dfb) + U(29 + ((pos) - 2) % 3) / 16 + (kk) * 128) | (0x10ull << 32), \
                                   desc_lo(dd0 + dpos_addr(pos) / 16 + (kk) * 2), 1)
#define WAITF(pos) mbar_wait(vb + 8 * ((pos) - 2), 0)
        const uint32_t vb = sb + B_VAL + (early ? 0 : 48);
        const uint32_t ts = clk();
        if (early) {
            PACK(0); SENDV(0); PACK(1); SENDV(1); PACK(2); SENDV(2); PACK(3); SENDV(3);
            mbar_wait(sb + B_GATE, 0);
            PACK(4); PACK(5); PACK(6); PACK(7);
            const float g0 = ((const float*)(smem + M_G))[wg * 64 + r0], g1 = ((const float*)(smem + M_G))[wg * 64 + r0 + 8];
            const float s0 = comp ? -g0 : g0, s1 = comp ? -g1 : g1;
            const uint32_t og0 = pack_bf16(1.f - g0, 1.f - g0), og1 = pack_bf16(1.f - g1, 1.f - g1);
#pragma unroll
            for (int k = 4; k < 8; k++) {
                if (k < ESEND) { until(ts + ETIME(k)); SENDV(k); }
#pragma unroll
                for (int i = 2 * k - 8; i < 2 * k - 6; i++) {
                    const uint32_t og = (i & 1) ? og1 : og0;
                    w[i] = make_uint4(hmul2_bf16(og, w[i].x), hmul2_bf16(og, w[i].y), hmul2_bf16(og, w[i].z), hmul2_bf16(og, w[i].w));
                    asm volatile("" : "+r"(w[i].x), "+r"(w[i].y), "+r"(w[i].z), "+r"(w[i].w));
                }
            }
            WAITD(0);
            mbar_wait(sb + B_S3, 0);
            wg_fence();
#pragma unroll
            for (int k = 0; k < 8; k++) {
                OWN(k);
                if (k >= 1 && k + ESEND - 1 < 8) { wg_commit(); until(ts + ETIME(k + ESEND - 1)); SENDV(k + ESEND - 1); wg_fence(); }
            }
            wg_commit();
            WAITD(2);
            bool ok = false;
#pragma unroll
            for (int pos = 2; pos < 8; pos++) {
                if (!ok) {
                    if (pos >= 4) WAITD(pos);
                    WAITF(pos);
                }
                wg_fence();
                MMA_F(a_addr, pos, 0); MMA_F(a_addr, pos, 1);
                if (pos == 6) { wg_commit(); wg_wait<1>(); mbar_arrive_cluster_if(mapa(sb + B_XF, rank ^ 1), lead); wg_fence(); }
                if (pos == 7) mbar_arrive_if(sb + B_S2, lead);
                if (pos < 7) ok = PRET && (mbar_test(vb + 8 * (pos - 1), 0) & (pos < 3 || mbar_test(sb + B_DL + 8 * (pos - 3), 0)));
                MMA_F(a_addr, pos, 2); MMA_F(a_addr, pos, 3);
                wg_commit();
            }
            const uint32_t xd = mapa(sb + a_addr(29) + (tid & 127) * 16, rank ^ 1), xb = mapa(sb + B_X, rank ^ 1);
            mbar_wait(sb + B_XF, 0);
            wg_wait<0>();
            fence_regs<0, 64>(acc);
            keep_regs<0, 8>(f);
#pragma unroll
            for (int i = 0; i < 8; i++) {
                const int o = 16 * (i >> 1) + 2 * (i & 1);
                const float s = (i & 1) ? s1 : s0;
                st_async16(xd + i * 2048, pack_bf16(fmaf(s, acc[o], bflo(w[i].x)), fmaf(s, acc[o + 1], bfhi(w[i].x))),
                           pack_bf16(fmaf(s, acc[o + 4], bflo(w[i].y)), fmaf(s, acc[o + 5], bfhi(w[i].y))),
                           pack_bf16(fmaf(s, acc[o + 8], bflo(w[i].z)), fmaf(s, acc[o + 9], bfhi(w[i].z))),
                           pack_bf16(fmaf(s, acc[o + 12], bflo(w[i].w)), fmaf(s, acc[o + 13], bfhi(w[i].w))), xb + 2 * (i & 4));
                if (i & 1) until(ts);
            }
        } else {
            uint32_t xs = sb + a_addr(29) + (tid & 127) * 16;
            PACK(0); PACK(1); PACK(2); PACK(3); PACK(4); PACK(5); PACK(6); PACK(7);
            if (!HOLD) {
                wg_fence();
#pragma unroll
                for (int k = 0; k < 8; k++) {
                    OWN(k);
                    if ((k & 1) && k / 2 < LSEND) { wg_commit(); until(ts + LTIME(k / 2)); SENDV(k / 2); wg_fence(); }
                }
                wg_commit();
            }
#pragma unroll
            for (int k = HOLD ? 0 : LSEND; k < 8; k++) { until(ts + LTIME(k)); SENDV(k); }
            WAITD(2);
            mbar_wait(sb + B_GATE, 0);
            const float g0 = ((const float*)(smem + M_G))[wg * 64 + r0], g1 = ((const float*)(smem + M_G))[wg * 64 + r0 + 8];
            float s0 = comp ? -g0 : g0, s1 = comp ? -g1 : g1;
            const int rr = 0x7fff - (int)(*(volatile uint32_t*)(smem + M_KEY) & 0x7fffu) - (tm * 128 + wg * 64 + r0);
            char* op = (char*)p.out + ooff;
            asm volatile("" : "+f"(s0), "+f"(s1), "+r"(xs), "+l"(op));
            if (!HOLD) WAITF(2);
            mbar_wait(sb + B_S2, 0);
            if (HOLD) {
                wg_fence();
#pragma unroll
                for (int k = 0; k < 8; k++) OWN(k);
                wg_commit();
            }
            bool there = false, there1 = false, ok = !HOLD;
#pragma unroll
            for (int pos = 2; pos < 8; pos++) {
                if (!ok) WAITF(pos);
                wg_fence();
                MMA_F(b_addr, pos, 0);
                if (pos == XPOS) there = mbar_test(sb + B_X, 0);
                MMA_F(b_addr, pos, 1);
                if (pos == XPOS) {
#pragma unroll
                    for (int i = 0; i < 4; i++) lds128_if(w[i], xs + i * 2048, there);
                }
                if (pos < 7) ok = PRET && mbar_test(vb + 8 * (pos - 1), 0);
                MMA_F(b_addr, pos, 2);
                if (pos == 7) there1 = mbar_test(sb + B_X + 8, 0);
                MMA_F(b_addr, pos, 3);
                wg_commit();
            }
#pragma unroll
            for (int i = 4; i < 8; i++) lds128_if(w[i], xs + i * 2048, there1);
            if (!there) {
                mbar_wait(sb + B_X, 0);
#pragma unroll
                for (int i = 0; i < 4; i++) w[i] = lds128(xs + i * 2048);
            }
#pragma unroll
            for (int h = 0; h < 2; h++) {
                if (h == 1 && !there1) {
                    mbar_wait(sb + B_X + 8, 0);
#pragma unroll
                    for (int i = 4; i < 8; i++) w[i] = lds128(xs + i * 2048);
                }
                if (h == 0) {
                    wg_wait<0>();
                    fence_regs<0, 64>(acc);
                    keep_regs<0, 8>(f);
                }
#pragma unroll
                for (int i = 4 * h; i < 4 * h + 4; i++) {
                    const int o = 16 * (i >> 1) + 2 * (i & 1);
                    out_piece(op + (i & 1) * 8192 + (i >> 1) * 64, (i & 1) ? s1 : s0, w[i], acc[o], acc[o + 1], acc[o + 4], acc[o + 5],
                              acc[o + 8], acc[o + 9], acc[o + 12], acc[o + 13]);
                }
            }
            if (rr == 0 || rr == 8) {
                const bool hi = rr == 8;
                const float og = 1.f - (hi ? g1 : g0), s = hi ? s1 : s0;
                mbar_wait(sb + B_SIDE, 0);
#pragma unroll
                for (int j = 0; j < 4; j++) {
                    const float4 ua = *(const float4*)(smem + M_RED + j * 128 + q * 32), ub = *(const float4*)(smem + M_RED + j * 128 + q * 32 + 16);
                    const uint4 v = hi ? w[2 * j + 1] : w[2 * j];
                    float a[8];
#pragma unroll
                    for (int k = 0; k < 8; k++) a[k] = selpf(acc[16 * j + 4 * (k >> 1) + (k & 1) + 2], acc[16 * j + 4 * (k >> 1) + (k & 1)], hi);
                    stg_off<0>(op + rr * 1024 + j * 64,
                               make_uint4(pack_bf16(fmaf(og, ua.x, fmaf(s, a[0], bflo(v.x))), fmaf(og, ua.y, fmaf(s, a[1], bfhi(v.x)))),
                                          pack_bf16(fmaf(og, ua.z, fmaf(s, a[2], bflo(v.y))), fmaf(og, ua.w, fmaf(s, a[3], bfhi(v.y)))),
                                          pack_bf16(fmaf(og, ub.x, fmaf(s, a[4], bflo(v.z))), fmaf(og, ub.y, fmaf(s, a[5], bfhi(v.z)))),
                                          pack_bf16(fmaf(og, ub.z, fmaf(s, a[6], bflo(v.w))), fmaf(og, ub.w, fmaf(s, a[7], bfhi(v.w))))));
                }
            }
        }
    }
}

typedef CUresult (*EncodeTiledFn)(CUtensorMap*, CUtensorMapDataType, cuuint32_t, void*, const cuuint64_t*, const cuuint64_t*,
                                  const cuuint32_t*, const cuuint32_t*, CUtensorMapInterleave, CUtensorMapSwizzle,
                                  CUtensorMapL2promotion, CUtensorMapFloatOOBfill);

static void make_map(EncodeTiledFn enc, CUtensorMap* m, const void* base, uint64_t cols, uint64_t rows, uint32_t box_rows,
                     CUtensorMapSwizzle sw = CU_TENSOR_MAP_SWIZZLE_128B, uint32_t box_cols = 64,
                     CUtensorMapL2promotion promo = CU_TENSOR_MAP_L2_PROMOTION_L2_128B) {
    cuuint64_t dims[2] = {cols, rows};
    cuuint64_t str[1] = {cols * 2};
    cuuint32_t box[2] = {box_cols, box_rows};
    cuuint32_t es[2] = {1, 1};
    enc(m, CU_TENSOR_MAP_DATA_TYPE_BFLOAT16, 2, (void*)base, dims, str, box, es, CU_TENSOR_MAP_INTERLEAVE_NONE,
        sw, promo, CU_TENSOR_MAP_FLOAT_OOB_FILL_NONE);
}

static void make_map_chunks(EncodeTiledFn enc, CUtensorMap* m, const void* base, uint64_t rows) {
    cuuint64_t dims[3] = {64, rows, D_ / 64};
    cuuint64_t str[2] = {D_ * 2, 128};
    cuuint32_t box[3] = {64, 64, 2};
    cuuint32_t es[3] = {1, 1, 1};
    enc(m, CU_TENSOR_MAP_DATA_TYPE_BFLOAT16, 3, (void*)base, dims, str, box, es, CU_TENSOR_MAP_INTERLEAVE_NONE,
        CU_TENSOR_MAP_SWIZZLE_128B, CU_TENSOR_MAP_L2_PROMOTION_L2_128B, CU_TENSOR_MAP_FLOAT_OOB_FILL_NONE);
}

static void make_map_perm(EncodeTiledFn enc, CUtensorMap* m, const void* base) {
    cuuint64_t dims[5] = {D_, 2, 4, 4, D_ / 32};
    cuuint64_t str[4] = {D_ * 2, 8 * D_ * 2, 2 * D_ * 2, 32 * D_ * 2};
    cuuint32_t box[5] = {64, 2, 4, 4, 4};
    cuuint32_t es[5] = {1, 1, 1, 1, 1};
    enc(m, CU_TENSOR_MAP_DATA_TYPE_BFLOAT16, 5, (void*)base, dims, str, box, es, CU_TENSOR_MAP_INTERLEAVE_NONE,
        CU_TENSOR_MAP_SWIZZLE_128B, CU_TENSOR_MAP_L2_PROMOTION_L2_128B, CU_TENSOR_MAP_FLOAT_OOB_FILL_NONE);
}

extern "C" void kernel_launch(void* const* d_in, const int* in_sizes, int n_in, void* d_out, int out_size) {
    (void)in_sizes; (void)n_in; (void)out_size;
    static EncodeTiledFn enc = nullptr;
    static bool fused_ok = false;
    static void* frag_ptr = nullptr;
    if (!enc) {
        void* fn = nullptr;
        cudaDriverEntryPointQueryResult q;
        cudaGetDriverEntryPoint("cuTensorMapEncodeTiled", &fn, cudaEnableDefault, &q);
        enc = (EncodeTiledFn)fn;
        cudaGetSymbolAddress(&frag_ptr, g_frag);
        cudaFuncSetAttribute(fused_kernel, cudaFuncAttributeMaxDynamicSharedMemorySize, SMEM_BYTES);
        int dev = 0, nsm = 0, ncl = 0;
        cudaGetDevice(&dev);
        cudaDeviceGetAttribute(&nsm, cudaDevAttrMultiProcessorCount, dev);
        cudaLaunchConfig_t cfg = {};
        cfg.gridDim = dim3(132); cfg.blockDim = dim3(NTHREADS); cfg.dynamicSmemBytes = SMEM_BYTES;
        cudaLaunchAttribute at;
        at.id = cudaLaunchAttributeClusterDimension;
        at.val.clusterDim.x = 2; at.val.clusterDim.y = 1; at.val.clusterDim.z = 1;
        cfg.attrs = &at; cfg.numAttrs = 1;
        fused_ok = cudaOccupancyMaxActiveClusters(&ncl, fused_kernel, &cfg) == cudaSuccess && nsm == 132 && ncl == 66;
        (void)cudaGetLastError();
    }
    if (!fused_ok) {
        const bf16* const* in = (const bf16* const*)d_in;
        fb_hidden<<<S_, D_, 0, cudaStreamPerThread>>>(in[0], in[3], in[4], in[10], in[6]);
        fb_ffn1<<<F_ / 128, 128, 0, cudaStreamPerThread>>>(in[0], in[7], in[8]);
        fb_ffn2<<<D_ / 64, 64, 0, cudaStreamPerThread>>>(in[9]);
        fb_seq<<<S_, D_, 0, cudaStreamPerThread>>>(in[0], in[1], in[2], (bf16*)d_out);
        return;
    }
    Params p;
    p.x = (const bf16*)d_in[0];
    p.dre = (const bf16*)d_in[3];
    p.dim = (const bf16*)d_in[4];
    p.w_r = (const bf16*)d_in[6];
    p.wg = (const bf16*)d_in[7];
    p.wu = (const bf16*)d_in[8];
    p.wd = (const bf16*)d_in[9];
    p.gate_w = (const bf16*)d_in[10];
    p.out = (bf16*)d_out;
    make_map_chunks(enc, &p.mX2, d_in[0], S_);
    make_map(enc, &p.mX, d_in[0], D_, S_, 64);
    make_map(enc, &p.mCre, d_in[1], S_, S_, 128, CU_TENSOR_MAP_SWIZZLE_128B, 64, PROMOC);
    make_map(enc, &p.mCim, d_in[2], S_, S_, 128, CU_TENSOR_MAP_SWIZZLE_128B, 64, PROMOC);
    make_map_perm(enc, &p.mDre, d_in[3]);
    make_map_perm(enc, &p.mDim, d_in[4]);
    make_map(enc, &p.mF, frag_ptr, 64, NCTA * 256, 64, CU_TENSOR_MAP_SWIZZLE_NONE);
    make_map(enc, &p.mWg, d_in[7], F_, D_, 64, CU_TENSOR_MAP_SWIZZLE_NONE, 32, CU_TENSOR_MAP_L2_PROMOTION_NONE);
    make_map(enc, &p.mWu, d_in[8], F_, D_, 64, CU_TENSOR_MAP_SWIZZLE_NONE, 32, CU_TENSOR_MAP_L2_PROMOTION_NONE);
    make_map(enc, &p.mWd, d_in[9], D_, F_, 8, CU_TENSOR_MAP_SWIZZLE_NONE, 256);
    fused_kernel<<<132, NTHREADS, SMEM_BYTES, cudaStreamPerThread>>>((const char*)d_in[1], (const char*)d_in[2], (const char*)d_in[0], p);
}
```

```cpp
#include <cuda_runtime.h>
#include <cuda.h>
#include <cuda_bf16.h>
#include <stdint.h>

typedef __nv_bfloat16 bf16;

constexpr int S_ = 2048, D_ = 512, F_ = 1792;
constexpr int NCTA = 128;
constexpr int NTHREADS = 512;
constexpr int NST = 6;
constexpr int SP0 = 27;
constexpr int FFN_CTAS = F_ / 16;
constexpr uint32_t SPIN_LIMIT = 1u << 16;

#define P_1 500
#define T_1 550
#define T_2 1050
#define PACE 400
#define ROUTER_T0 3000
#define ROUTER_DT 280
#define FFN_T0 5200
#define FFN_DT 640
#define XLD 10
#define XN 8
#define XD 1
#define PFD_T0 12200
#define PFD_DT 250
#define SUM_T0 14000
#define ET1 600
#define STP 170
#define ESEND 6
#define LT0 450
#define LTP 170
#define LSEND 3
#define SDEL 280
#define E_RD0 1330
#define E_RD1 2180
#define L_RD0 3300
#define L_RD1 3930
#define SG 130
#define T_D5 1500
#define T_D6 1700
#define T_D7 2400
#define XPOS 7
#define RC 168
#define RS_ 112
#define RU 64
#define SIDE_T0 2800
#define STR2(x) #x
#define STR(x) STR2(x)

__host__ __device__ constexpr int a_addr(int s) { return s % NST * 16384; }
__host__ __device__ constexpr int b_addr(int s) { return (NST + s % NST) * 16384; }
constexpr int R6 = 2 * NST * 16384;
__host__ __device__ constexpr int d_addr(int p) { return p / 2 == 1 ? R6 + (p & 1) * 16384 : (p & 1) ? b_addr(26 + p / 3) : a_addr(26 + p / 3); }
static_assert(d_addr(0) == a_addr(26) && d_addr(4) == a_addr(27) && d_addr(6) == a_addr(28), "");
constexpr int OFF_MISC = R6 + 32768;
constexpr int B_FULL = OFF_MISC;
constexpr int B_EMPTY = B_FULL + 48;
constexpr int B_VD = B_EMPTY + 48;
constexpr int B_X = B_VD + 8;
constexpr int B_HX = B_X + 16;
constexpr int B_XF = B_HX + 8;
constexpr int B_S0 = B_XF + 8;
constexpr int B_S1 = B_S0 + 8;
constexpr int B_EA = B_S1 + 8;
constexpr int B_S2 = B_EA + 8;
constexpr int B_S3 = B_S2 + 8;
constexpr int B_D6 = B_S3 + 8;
constexpr int B_DL = B_D6 + 8;
constexpr int B_GATE = B_DL + 32;
constexpr int B_SIDE = B_GATE + 8;
constexpr int B_FFN = B_SIDE + 8;
constexpr int B_R6 = B_FFN + 32;
constexpr int B_LAND = B_R6 + 8;
constexpr int B_VAL = B_LAND + 48;
constexpr int B_TH = B_VAL + 96;
constexpr int M_TH = B_TH + 24;
constexpr int NBAR = (M_TH - B_EMPTY) / 8;
constexpr int M_KEY = M_TH + 12;
constexpr int M_PAR = M_KEY + 4;
constexpr int M_ROLE = M_PAR + 4;
constexpr int M_HX = OFF_MISC + 512;
constexpr int M_G = M_HX + 256;
constexpr int M_UPD = M_G + 512;
constexpr int M_RED = M_UPD + 512;
constexpr int SMEM_BYTES = 232448;
static_assert(M_RED + 512 <= SMEM_BYTES && M_ROLE + 4 <= M_HX, "smem");

struct Params {
    const bf16 *gate_w, *w_r, *dre, *dim;
    CUtensorMap mCre, mCim, mX2, mX, mDre, mDim, mF, mWg, mWu, mWd;
};

struct Scratch {
    uint32_t frag[NCTA * 2 * 4096];
    uint32_t stamp[NCTA * 32];
    uint32_t gate[S_];
    uint32_t part[FFN_CTAS / 2 * D_];
    uint32_t phint[4 * 8 * 8];
    uint32_t upd[D_];
    uint32_t keys[8 * NCTA];
    uint32_t epoch[NCTA + 4];
};
__device__ __align__(1024) Scratch g_scr;

__device__ __forceinline__ uint32_t smem_u32(const void* p) { return (uint32_t)__cvta_generic_to_shared(p); }
__device__ __forceinline__ void mbar_init(uint32_t bar, uint32_t cnt) {
    asm volatile("mbarrier.init.shared::cta.b64 [%0], %1;" ::"r"(bar), "r"(cnt) : "memory");
}
__device__ __forceinline__ void mbar_expect_tx(uint32_t bar, uint32_t bytes) {
    asm volatile("mbarrier.arrive.expect_tx.shared::cta.b64 _, [%0], %1;" ::"r"(bar), "r"(bytes) : "memory");
}
__device__ __forceinline__ void mbar_arrive(uint32_t bar) {
    asm volatile("mbarrier.arrive.shared::cta.b64 _, [%0];" ::"r"(bar) : "memory");
}
template <int N>
__device__ __forceinline__ void mbar_arrive_n_if(uint32_t bar, bool pred) {
    asm volatile("{.reg .pred p; setp.ne.b32 p, %1, 0; @p mbarrier.arrive.shared::cta.b64 _, [%0], %2;}" ::"r"(bar), "r"((int)pred), "n"(N) : "memory");
}
__device__ __forceinline__ void mbar_arrive_if(uint32_t bar, bool pred) {
    asm volatile("{.reg .pred p; setp.ne.b32 p, %1, 0; @p mbarrier.arrive.shared::cta.b64 _, [%0];}" ::"r"(bar), "r"((int)pred) : "memory");
}
__device__ __forceinline__ void mbar_arrive_warp(uint32_t bar) {
    __syncwarp();
    mbar_arrive_if(bar, (threadIdx.x & 31) == 0);
}
__device__ __forceinline__ void mbar_arrive_cluster_if(uint32_t bar, bool pred) {
    asm volatile("{.reg .pred p; setp.ne.b32 p, %1, 0; @p mbarrier.arrive.shared::cluster.b64 _, [%0], 1;}"
                 ::"r"(bar), "r"((int)pred) : "memory");
}
__device__ __forceinline__ uint32_t mapa(uint32_t a, uint32_t cta) {
    uint32_t r;
    asm volatile("mapa.shared::cluster.u32 %0, %1, %2;" : "=r"(r) : "r"(a), "r"(cta));
    return r;
}
__device__ __forceinline__ bool mbar_try(uint32_t bar, uint32_t parity) {
    uint32_t ok;
    asm volatile("{.reg .pred p; mbarrier.try_wait.parity.shared::cta.b64 p, [%1], %2; selp.u32 %0,1,0,p;}"
                 : "=r"(ok) : "r"(bar), "r"(parity) : "memory");
    return ok;
}
__device__ __forceinline__ bool mbar_test(uint32_t bar, uint32_t parity) {
    uint32_t ok;
    asm volatile("{.reg .pred p; mbarrier.test_wait.parity.shared::cta.b64 p, [%1], %2; selp.u32 %0,1,0,p;}"
                 : "=r"(ok) : "r"(bar), "r"(parity) : "memory");
    return ok;
}
__device__ __forceinline__ void mbar_wait(uint32_t bar, uint32_t parity) {
    uint32_t n = 0;
#pragma unroll 1
    while (!mbar_try(bar, parity)) { if (++n > SPIN_LIMIT) break; }
}
__device__ __forceinline__ void tma2d(uint32_t dst, const CUtensorMap* m, int c0, int c1, uint32_t bar) {
    asm volatile("cp.async.bulk.tensor.2d.shared::cluster.global.mbarrier::complete_tx::bytes [%0], [%1, {%3,%4}], [%2];"
                 ::"r"(dst), "l"(m), "r"(bar), "r"(c0), "r"(c1) : "memory");
}
__device__ __forceinline__ void tma3d(uint32_t dst, const CUtensorMap* m, int row, int chunk, uint32_t bar) {
    asm volatile("cp.async.bulk.tensor.3d.shared::cluster.global.mbarrier::complete_tx::bytes [%0], [%1, {%3,%4,%5}], [%2];"
                 ::"r"(dst), "l"(m), "r"(bar), "r"(0), "r"(row), "r"(chunk) : "memory");
}
__device__ __forceinline__ void tma2d_elect(uint32_t dst, const CUtensorMap* m, int c0, int c1, uint32_t bar) {
    asm volatile("{.reg .pred p; elect.sync _|p, 0xffffffff;"
                 " @p cp.async.bulk.tensor.2d.shared::cluster.global.mbarrier::complete_tx::bytes [%0], [%1, {%3,%4}], [%2];}"
                 ::"r"(dst), "l"(m), "r"(bar), "r"(c0), "r"(c1) : "memory");
}
__device__ __forceinline__ void tma2d_pair_elect(uint32_t dst, const CUtensorMap* m, int c0, int c1, uint32_t bar) {
    asm volatile("{.reg .pred p; elect.sync _|p, 0xffffffff;"
                 " @p cp.async.bulk.tensor.2d.shared::cluster.global.mbarrier::complete_tx::bytes.multicast::cluster"
                 " [%0], [%1, {%3,%4}], [%2], %5;}" ::"r"(dst), "l"(m), "r"(bar), "r"(c0), "r"(c1), "h"((uint16_t)3) : "memory");
}
__device__ __forceinline__ void tma3d_elect(uint32_t dst, const CUtensorMap* m, int row, int chunk, uint32_t bar) {
    asm volatile("{.reg .pred p; elect.sync _|p, 0xffffffff;"
                 " @p cp.async.bulk.tensor.3d.shared::cluster.global.mbarrier::complete_tx::bytes [%0], [%1, {%3,%4,%5}], [%2];}"
                 ::"r"(dst), "l"(m), "r"(bar), "r"(0), "r"(row), "r"(chunk) : "memory");
}
__device__ __forceinline__ void tma5d_elect(uint32_t dst, const CUtensorMap* m, int c0, int c4, uint32_t bar) {
    asm volatile("{.reg .pred p; elect.sync _|p, 0xffffffff;"
                 " @p cp.async.bulk.tensor.5d.shared::cluster.global.mbarrier::complete_tx::bytes [%0], [%1, {%3,%5,%5,%5,%4}], [%2];}"
                 ::"r"(dst), "l"(m), "r"(bar), "r"(c0), "r"(c4), "r"(0) : "memory");
}
__device__ __forceinline__ void mbar_expect_tx_elect(uint32_t bar, uint32_t bytes) {
    asm volatile("{.reg .pred p; elect.sync _|p, 0xffffffff; @p mbarrier.arrive.expect_tx.shared::cta.b64 _, [%0], %1;}"
                 ::"r"(bar), "r"(bytes) : "memory");
}
__device__ __forceinline__ void fence_proxy_async_smem() { asm volatile("fence.proxy.async.shared::cta;" ::: "memory"); }
__device__ __forceinline__ void prefetch_l2(const void* p) { asm volatile("prefetch.global.L2 [%0];" ::"l"(p)); }
__device__ __forceinline__ uint32_t ld_relaxed(const void* p) {
    uint32_t v;
    asm volatile("ld.relaxed.gpu.global.u32 %0, [%1];" : "=r"(v) : "l"(p) : "memory");
    return v;
}
__device__ __forceinline__ uint4 ld_relaxed4(const void* p) {
    uint4 v;
    asm volatile("ld.relaxed.gpu.global.v4.u32 {%0,%1,%2,%3}, [%4];" : "=r"(v.x), "=r"(v.y), "=r"(v.z), "=r"(v.w) : "l"(p) : "memory");
    return v;
}
__device__ __forceinline__ void st_relaxed(unsigned int* p, uint32_t v) {
    asm volatile("st.relaxed.gpu.global.u32 [%0], %1;" ::"l"(p), "r"(v) : "memory");
}
__device__ __forceinline__ void st_key(unsigned int* p, uint32_t v) {
    asm volatile("{.reg .b32 old; atom.relaxed.gpu.global.exch.b32 old, [%0], %1;}" ::"l"(p), "r"(v) : "memory");
}
__device__ __forceinline__ uint32_t tagf(float v, uint32_t par) { return (__float_as_uint(v) & ~1u) | par; }
__device__ __forceinline__ uint4 wait_tags(const unsigned int* p, int bit, uint32_t par) {
    uint32_t n = 0;
#pragma unroll 1
    while (true) {
        const uint4 v = ld_relaxed4(p);
        const uint32_t m = par ? (v.x & v.y & v.z & v.w) : ~(v.x | v.y | v.z | v.w);
        if (__all_sync(0xffffffffu, (m >> bit) & 1u)) return v;
        __nanosleep(100);
        if (++n > SPIN_LIMIT) return v;
    }
}
__device__ __forceinline__ void named_bar(int id, int n) { asm volatile("bar.sync %0, %1;" ::"r"(id), "r"(n) : "memory"); }
template <int OFF>
__device__ __forceinline__ uint4 ldg_nc_off(const void* p) {
    uint4 v;
    asm volatile("ld.global.nc.v4.u32 {%0,%1,%2,%3}, [%4+%5];" : "=r"(v.x), "=r"(v.y), "=r"(v.z), "=r"(v.w) : "l"(p), "n"(OFF));
    return v;
}
__device__ __forceinline__ void ldg_nc_if(uint4& v, const void* a, bool pred) {
    asm volatile("{.reg .pred p; setp.ne.b32 p, %5, 0; @p ld.global.nc.v4.u32 {%0,%1,%2,%3}, [%4];}"
                 : "+r"(v.x), "+r"(v.y), "+r"(v.z), "+r"(v.w) : "l"(a), "r"((int)pred) : "memory");
}
template <int OFF>
__device__ __forceinline__ void stg_off(void* p, const uint4& v) {
    asm volatile("st.global.v4.u32 [%0+%5], {%1,%2,%3,%4};" ::"l"(p), "r"(v.x), "r"(v.y), "r"(v.z), "r"(v.w), "n"(OFF) : "memory");
}
__device__ __forceinline__ void sts128(uint32_t a, const uint4& v) {
    asm volatile("st.shared.v4.u32 [%0], {%1,%2,%3,%4};" ::"r"(a), "r"(v.x), "r"(v.y), "r"(v.z), "r"(v.w) : "memory");
}
__device__ __forceinline__ uint4 lds128(uint32_t a) {
    uint4 v;
    asm volatile("ld.shared.v4.u32 {%0,%1,%2,%3}, [%4];" : "=r"(v.x), "=r"(v.y), "=r"(v.z), "=r"(v.w) : "r"(a) : "memory");
    return v;
}
__device__ __forceinline__ void lds128_if(uint4& v, uint32_t a, bool pred) {
    asm volatile("{.reg .pred p; setp.ne.b32 p, %5, 0; @p ld.shared.v4.u32 {%0,%1,%2,%3}, [%4];}"
                 : "+r"(v.x), "+r"(v.y), "+r"(v.z), "+r"(v.w) : "r"(a), "r"((int)pred) : "memory");
}
__device__ __forceinline__ uint32_t lds32(uint32_t a) {
    uint32_t v;
    asm volatile("ld.shared.u32 %0, [%1];" : "=r"(v) : "r"(a) : "memory");
    return v;
}
__device__ __forceinline__ void st_async16(uint32_t dst, uint32_t x, uint32_t y, uint32_t z, uint32_t w, uint32_t bar) {
    asm volatile("st.async.weak.shared::cluster.mbarrier::complete_tx::bytes.v4.b32 [%0], {%1,%2,%3,%4}, [%5];"
                 ::"r"(dst), "r"(x), "r"(y), "r"(z), "r"(w), "r"(bar) : "memory");
}
__device__ __forceinline__ int sel(int a, int b, bool p) {
    int r;
    asm("{.reg .pred q; setp.ne.b32 q, %3, 0; selp.b32 %0, %1, %2, q;}" : "=r"(r) : "r"(a), "r"(b), "r"((int)p));
    return r;
}
__device__ __forceinline__ float selpf(float a, float b, bool p) {
    float r;
    asm("{.reg .pred q; setp.ne.b32 q, %3, 0; selp.f32 %0, %1, %2, q;}" : "=f"(r) : "f"(a), "f"(b), "r"((int)p));
    return r;
}
template <int N, int MASK, int SZ>
__device__ __forceinline__ void halve(float (&a)[SZ]) {
    const bool up = threadIdx.x & MASK;
#pragma unroll
    for (int j = 0; j < N; j++) a[j] = selpf(a[N + j], a[j], up) + __shfl_xor_sync(0xffffffffu, selpf(a[j], a[N + j], up), MASK);
}
__device__ __forceinline__ float bflo(uint32_t u) { return __uint_as_float(u << 16); }
__device__ __forceinline__ float bfhi(uint32_t u) { return __uint_as_float(u & 0xffff0000u); }
__device__ __forceinline__ uint32_t pack_bf16(float lo, float hi) {
    uint32_t r;
    asm("cvt.rn.bf16x2.f32 %0, %1, %2;" : "=r"(r) : "f"(hi), "f"(lo));
    return r;
}
__device__ __forceinline__ uint32_t hmul2_bf16(uint32_t a, uint32_t b) {
    uint32_t r;
    asm("mul.rn.bf16x2 %0, %1, %2;" : "=r"(r) : "r"(a), "r"(b));
    return r;
}
__device__ __forceinline__ float sigmoidf_(float v) { return 1.0f / (1.0f + __expf(-v)); }
__device__ __forceinline__ void wg_fence() { asm volatile("wgmma.fence.sync.aligned;" ::: "memory"); }
__device__ __forceinline__ void wg_commit() { asm volatile("wgmma.commit_group.sync.aligned;" ::: "memory"); }
template <int N> __device__ __forceinline__ void wg_wait() { asm volatile("wgmma.wait_group.sync.aligned %0;" ::"n"(N) : "memory"); }
__device__ __forceinline__ uint64_t desc_lo(uint32_t lo) { return (uint64_t)lo | (0x40000040ull << 32); }
template <int LO, int HI, int N>
__device__ __forceinline__ void fence_regs(float (&d)[N]) {
#pragma unroll
    for (int i = LO; i < HI; i++) asm volatile("" : "+f"(d[i])::"memory");
}
template <int LO, int HI, int N>
__device__ __forceinline__ void keep_regs(uint4 (&f)[N]) {
#pragma unroll
    for (int i = LO; i < HI; i++) asm volatile("" ::"r"(f[i].x), "r"(f[i].y), "r"(f[i].z), "r"(f[i].w) : "memory");
}
template <int TB = 1>
__device__ __forceinline__ void wgmma128(float (&d)[64], uint64_t da, uint64_t db, int scaleD) {
    asm volatile(
        "{ .reg .pred p; setp.ne.b32 p, %66, 0;\n"
        "wgmma.mma_async.sync.aligned.m64n128k16.f32.bf16.bf16 "
        "{%0,%1,%2,%3,%4,%5,%6,%7,%8,%9,%10,%11,%12,%13,%14,%15,%16,%17,%18,%19,%20,%21,%22,%23,%24,%25,%26,%27,%28,%29,%30,%31,"
        "%32,%33,%34,%35,%36,%37,%38,%39,%40,%41,%42,%43,%44,%45,%46,%47,%48,%49,%50,%51,%52,%53,%54,%55,%56,%57,%58,%59,%60,%61,%62,%63}, "
        "%64, %65, p, 1, 1, 0, %67;\n}"
        : "+f"(d[0]), "+f"(d[1]), "+f"(d[2]), "+f"(d[3]), "+f"(d[4]), "+f"(d[5]), "+f"(d[6]), "+f"(d[7]),
          "+f"(d[8]), "+f"(d[9]), "+f"(d[10]), "+f"(d[11]), "+f"(d[12]), "+f"(d[13]), "+f"(d[14]), "+f"(d[15]),
          "+f"(d[16]), "+f"(d[17]), "+f"(d[18]), "+f"(d[19]), "+f"(d[20]), "+f"(d[21]), "+f"(d[22]), "+f"(d[23]),
          "+f"(d[24]), "+f"(d[25]), "+f"(d[26]), "+f"(d[27]), "+f"(d[28]), "+f"(d[29]), "+f"(d[30]), "+f"(d[31]),
          "+f"(d[32]), "+f"(d[33]), "+f"(d[34]), "+f"(d[35]), "+f"(d[36]), "+f"(d[37]), "+f"(d[38]), "+f"(d[39]),
          "+f"(d[40]), "+f"(d[41]), "+f"(d[42]), "+f"(d[43]), "+f"(d[44]), "+f"(d[45]), "+f"(d[46]), "+f"(d[47]),
          "+f"(d[48]), "+f"(d[49]), "+f"(d[50]), "+f"(d[51]), "+f"(d[52]), "+f"(d[53]), "+f"(d[54]), "+f"(d[55]),
          "+f"(d[56]), "+f"(d[57]), "+f"(d[58]), "+f"(d[59]), "+f"(d[60]), "+f"(d[61]), "+f"(d[62]), "+f"(d[63])
        : "l"(da), "l"(db), "r"(scaleD), "n"(TB));
}
__device__ __forceinline__ void wgmma128rs(float (&d)[64], const uint4& a, uint64_t db, int scaleD) {
    asm volatile(
        "{ .reg .pred p; setp.ne.b32 p, %69, 0;\n"
        "wgmma.mma_async.sync.aligned.m64n128k16.f32.bf16.bf16 "
        "{%0,%1,%2,%3,%4,%5,%6,%7,%8,%9,%10,%11,%12,%13,%14,%15,%16,%17,%18,%19,%20,%21,%22,%23,%24,%25,%26,%27,%28,%29,%30,%31,"
        "%32,%33,%34,%35,%36,%37,%38,%39,%40,%41,%42,%43,%44,%45,%46,%47,%48,%49,%50,%51,%52,%53,%54,%55,%56,%57,%58,%59,%60,%61,%62,%63}, "
        "{%64,%65,%66,%67}, %68, p, 1, 1, 0;\n}"
        : "+f"(d[0]), "+f"(d[1]), "+f"(d[2]), "+f"(d[3]), "+f"(d[4]), "+f"(d[5]), "+f"(d[6]), "+f"(d[7]),
          "+f"(d[8]), "+f"(d[9]), "+f"(d[10]), "+f"(d[11]), "+f"(d[12]), "+f"(d[13]), "+f"(d[14]), "+f"(d[15]),
          "+f"(d[16]), "+f"(d[17]), "+f"(d[18]), "+f"(d[19]), "+f"(d[20]), "+f"(d[21]), "+f"(d[22]), "+f"(d[23]),
          "+f"(d[24]), "+f"(d[25]), "+f"(d[26]), "+f"(d[27]), "+f"(d[28]), "+f"(d[29]), "+f"(d[30]), "+f"(d[31]),
          "+f"(d[32]), "+f"(d[33]), "+f"(d[34]), "+f"(d[35]), "+f"(d[36]), "+f"(d[37]), "+f"(d[38]), "+f"(d[39]),
          "+f"(d[40]), "+f"(d[41]), "+f"(d[42]), "+f"(d[43]), "+f"(d[44]), "+f"(d[45]), "+f"(d[46]), "+f"(d[47]),
          "+f"(d[48]), "+f"(d[49]), "+f"(d[50]), "+f"(d[51]), "+f"(d[52]), "+f"(d[53]), "+f"(d[54]), "+f"(d[55]),
          "+f"(d[56]), "+f"(d[57]), "+f"(d[58]), "+f"(d[59]), "+f"(d[60]), "+f"(d[61]), "+f"(d[62]), "+f"(d[63])
        : "r"(a.x), "r"(a.y), "r"(a.z), "r"(a.w), "l"(db), "r"(scaleD));
}
__device__ __forceinline__ uint32_t clk() { uint64_t c; asm volatile("mov.u64 %0, %%clock64;" : "=l"(c)::"memory"); return (uint32_t)c; }
__device__ __forceinline__ uint32_t gtime() { uint64_t t; asm volatile("mov.u64 %0, %%globaltimer;" : "=l"(t)::"memory"); return (uint32_t)t; }
__device__ __forceinline__ void until(uint32_t t) { while (t - clk() < 0x8000u) {} }
__device__ __forceinline__ void nap_until(uint32_t t) { while (t - clk() < 0x8000u) __nanosleep(20); }
__device__ __forceinline__ uint4 scale_add(float s, const float (&a)[64], int o, const uint4& w) {
    return make_uint4(pack_bf16(fmaf(s, a[o], bflo(w.x)), fmaf(s, a[o + 1], bfhi(w.x))), pack_bf16(fmaf(s, a[o + 4], bflo(w.y)), fmaf(s, a[o + 5], bfhi(w.y))),
                      pack_bf16(fmaf(s, a[o + 8], bflo(w.z)), fmaf(s, a[o + 9], bfhi(w.z))), pack_bf16(fmaf(s, a[o + 12], bflo(w.w)), fmaf(s, a[o + 13], bfhi(w.w))));
}

__device__ __forceinline__ uint32_t router_key(float score, int row) {
    const float r = score + 0.0f;
    uint32_t u = pack_bf16(r, 0.f) & 0xffffu;
    u = (u & 0x8000u) ? (~u & 0xffffu) : (u | 0x8000u);
    if (r != r) u = 0;
    return (u << 16) | (uint32_t)(0x7fff - row);
}

#define g_ab g_scr.frag
#define g_fb_h ((float*)g_scr.part)
#define g_fb_upd (g_fb_h + 2048)
#define g_fb_gate (g_fb_h + 4096)
#define g_fb_keys (g_scr.part + 8192)
__global__ void fb_hidden(const bf16* x, const bf16* dre, const bf16* dim, const bf16* gw, const bf16* wr) {
    __shared__ float xs[D_];
    const int s = blockIdx.x, t = threadIdx.x;
    xs[t] = __bfloat162float(x[s * D_ + t]);
    __syncthreads();
    float a = 0.f, b = 0.f;
    for (int d = 0; d < D_; d++) { a = fmaf(xs[d], __bfloat162float(dre[t * D_ + d]), a); b = fmaf(xs[d], __bfloat162float(dim[t * D_ + d]), b); }
    ((bf16*)g_ab)[s * 1024 + t] = __float2bfloat16(a);
    ((bf16*)g_ab)[s * 1024 + 512 + t] = __float2bfloat16(b);
    if (t == 0) {
        float u = 0.f, v = 0.f;
        for (int d = 0; d < D_; d++) { u = fmaf(xs[d], __bfloat162float(gw[d]), u); v = fmaf(xs[d], __bfloat162float(wr[d]), v); }
        g_fb_gate[s] = sigmoidf_(u);
        g_fb_keys[s] = router_key(v, s);
    }
}
__device__ uint32_t fb_best() {
    uint32_t k = 0;
    for (int i = 0; i < S_; i++) k = max(k, g_fb_keys[i]);
    return k;
}
__global__ void fb_ffn1(const bf16* x, const bf16* wg, const bf16* wu) {
    const int f = blockIdx.x * blockDim.x + threadIdx.x, idx = 0x7fff - (int)(fb_best() & 0x7fffu);
    float a = 0.f, b = 0.f;
    for (int d = 0; d < D_; d++) {
        const float xv = __bfloat162float(x[idx * D_ + d]);
        a = fmaf(xv, __bfloat162float(wg[d * F_ + f]), a); b = fmaf(xv, __bfloat162float(wu[d * F_ + f]), b);
    }
    g_fb_h[f] = a * sigmoidf_(a) * b;
}
__global__ void fb_ffn2(const bf16* wd) {
    const int e = blockIdx.x * blockDim.x + threadIdx.x;
    const uint32_t u = fb_best() >> 16, rb = (u & 0x8000u) ? (u & 0x7fffu) : (~u & 0xffffu);
    float a = 0.f;
    for (int f = 0; f < F_; f++) a = fmaf(g_fb_h[f], __bfloat162float(wd[f * D_ + e]), a);
    g_fb_upd[e] = a * sigmoidf_(__uint_as_float(rb << 16));
}
__global__ void fb_seq(const bf16* x, const bf16* cre, const bf16* cim, bf16* out) {
    __shared__ float c[2][S_];
    __shared__ int idx;
    const int t = blockIdx.x, e = threadIdx.x;
    for (int i = e; i < S_; i += D_) { c[0][i] = __bfloat162float(cre[t * S_ + i]); c[1][i] = __bfloat162float(cim[t * S_ + i]); }
    if (e == 0) idx = 0x7fff - (int)(fb_best() & 0x7fffu);
    __syncthreads();
    float y = 0.f;
    for (int s = 0; s < S_; s++)
        y += c[0][s] * __bfloat162float(((const bf16*)g_ab)[s * 1024 + e]) - c[1][s] * __bfloat162float(((const bf16*)g_ab)[s * 1024 + 512 + e]);
    const float g = g_fb_gate[t];
    out[t * D_ + e] = __float2bfloat16(g * y + (1.f - g) * (__bfloat162float(x[t * D_ + e]) + (t == idx ? g_fb_upd[e] : 0.f)));
}

__device__ __forceinline__ void spare_job(const Params& p, Scratch* g, unsigned char* smem, int sp, uint32_t tstart) {
    const int tid = threadIdx.x, warp = tid >> 5, lane = tid & 31;
    if (warp >= 8) {
#pragma unroll 1
        for (int i = 0; i < 16; i++) {
            nap_until(tstart + PFD_T0 + i * (PFD_DT / 2));
            prefetch_l2((const char*)((sp & 2) ? p.dim : p.dre) + (sp & 1) * 262144 + i * 16384 + (tid - 256) * 128);
        }
        return;
    }
    nap_until(tstart + SUM_T0 - 2000);
    const uint32_t e1 = ld_relaxed(g->epoch + NCTA + sp) + 1u, par = e1 & 1u;
    const uint4 k4 = wait_tags(g->keys + warp * NCTA + lane * 4, 15, par);
    const uint32_t u = __reduce_max_sync(0xffffffffu, max(max(k4.x, k4.y), max(k4.z, k4.w))) >> 16;
    const float rs = sigmoidf_(__uint_as_float(((u & 0x8000u) ? (u & 0x7fffu) : (~u & 0xffffu)) << 16));
    nap_until(tstart + SUM_T0);
    uint32_t n = 0;
#pragma unroll 1
    while ((int)(ld_relaxed(g->phint + (sp * 8 + warp) * 8) - e1 * 14u) < 0) {
        __nanosleep(40);
        if (++n > SPIN_LIMIT) break;
    }
    const unsigned int* src = g->part + warp * 7 * D_ + sp * 128 + lane * 4;
    uint4 v[7];
#pragma unroll 1
    while (true) {
        uint32_t bad = 0;
#pragma unroll
        for (int i = 0; i < 7; i++) v[i] = ld_relaxed4(src + i * D_);
#pragma unroll
        for (int i = 0; i < 7; i++) bad |= (v[i].x ^ par) | (v[i].y ^ par) | (v[i].z ^ par) | (v[i].w ^ par);
        if (!__any_sync(0xffffffffu, bad & 1u)) break;
        if (++n > SPIN_LIMIT) break;
    }
    float4 s = make_float4(0.f, 0.f, 0.f, 0.f);
#pragma unroll
    for (int i = 0; i < 7; i++) {
        s.x += __uint_as_float(v[i].x); s.y += __uint_as_float(v[i].y);
        s.z += __uint_as_float(v[i].z); s.w += __uint_as_float(v[i].w);
    }
    float* acc = (float*)smem;
    *(float4*)&acc[warp * 128 + lane * 4] = s;
    named_bar(1, 256);
    if (tid < 128) {
        float t = 0.f;
#pragma unroll
        for (int i = 0; i < 8; i++) t += acc[i * 128 + tid];
        st_relaxed(&g->upd[sp * 128 + tid], tagf(t * rs, par));
        if (tid == 0) st_relaxed(g->epoch + NCTA + sp, e1);
    }
}

__device__ __forceinline__ int other(int i, int tn) { return i + (i >= tn); }
__device__ __forceinline__ int dcol(int p, int tn) { return p < 2 ? tn * 128 + p * 64 : other((p - 2) % 3, tn) * 128 + (p >= 5 ? 64 : 0); }

template <int H>
__device__ __forceinline__ void fetch_job(const Params& p, Scratch* g, unsigned char* smem, uint32_t sb, int cta, int i, uint32_t par) {
    const int lane = threadIdx.x & 31, comp = cta & 1;
    const int j = other(i, (cta >> 1) & 3), src = (cta & ~6) + 2 * j;
    const int slot = i == 0 ? 29 % NST : i - 1;
    const uint32_t land = sb + B_LAND + 8 * (3 * H + i);
    uint32_t ph = 0, th;
    mbar_expect_tx_elect(land, 8192);
    if (H == 0) {
        mbar_wait(sb + B_S0, 0);
        const uint32_t t0 = clk();
        if (i == 0) {
            mbar_wait(sb + B_FULL + 8 * (31 % NST), (31 / NST) & 1);
            const uint32_t t1 = t0 + max(clk() - t0, 180u) - 180u;
            asm volatile("{.reg .pred p; .reg .b64 t; setp.eq.b32 p, %3, 0; mov.b64 t, {%1, %2}; @p st.relaxed.gpu.global.b64 [%0], t;}"
                         ::"l"(g->stamp + cta * 32), "r"((t1 & ~1u) | par), "r"(gtime()), "r"(lane) : "memory");
        }
        until(t0 + SDEL);
        uint32_t gt;
#pragma unroll 1
        for (uint32_t n = 0; n < SPIN_LIMIT; n++) {
            asm volatile("{.reg .b64 t; ld.relaxed.gpu.global.b64 t, [%2]; mov.b64 {%0,%1}, t;}" : "=r"(th), "=r"(gt) : "l"(g->stamp + src * 32) : "memory");
            if (!__any_sync(0xffffffffu, (th ^ par) & 1u)) break;
        }
        const uint32_t ns = min(gtime() - gt, 4096u), now = clk();
        if (now - th >= 8192u) th = now - (ns + (ns >> 1) + (ns >> 4));
        th += SG * j;
        if (lane == 0) { *(volatile uint32_t*)(smem + M_TH + 4 * i) = th; mbar_arrive(sb + B_TH + 8 * i); }
        __syncwarp();
    } else {
        mbar_wait(sb + B_TH + 8 * i, 0);
        th = lds32(sb + M_TH + 4 * i);
    }
    mbar_wait(sb + B_EA, 0);
#pragma unroll
    for (int c = 0; c < 2; c++) {
        const uint32_t dst = sb + slot * 16384 + (c ? NST * 16384 + H * 8192 : (comp ^ H) * 8192);
        if (c != H) mbar_wait(sb + B_EMPTY + 8 * slot, i != 0);
        until(th + (c ? (H ? L_RD1 : L_RD0) : (H ? E_RD1 : E_RD0)));
#pragma unroll 1
        for (uint32_t r = 0; r < SPIN_LIMIT; r++) {
            tma2d_elect(dst, &p.mF, 0, (src * 2 + (comp ^ c)) * 128 + H * 64, land);
            mbar_wait(land, ph);
            ph ^= 1;
            const uint32_t a = dst + (lane >> 2) * 132 + (lane & 3) * 32;
            uint32_t v[8], m0 = 0, m1 = ~0u;
#pragma unroll
            for (int k = 0; k < 8; k++) v[k] = lds32(a + k * 1024);
#pragma unroll
            for (int k = 0; k < 8; k++) { m0 |= v[k]; m1 &= v[k]; }
            if (__all_sync(0xffffffffu, (par ? m1 : ~m0) & 1u)) break;
            mbar_expect_tx_elect(land, 8192);
        }
        mbar_arrive_if(sb + B_VAL + 8 * (6 * c + 3 * H + i), lane == 0);
        if (c == 0) mbar_expect_tx_elect(land, 8192);
    }
}

__global__ void __cluster_dims__(2, 1, 1) __launch_bounds__(NTHREADS, 1)
fused_kernel(const char* pc0, const char* pc1, const char* px, char* pout, Scratch* g, const __grid_constant__ Params p) {
    extern __shared__ __align__(1024) unsigned char smem[];
    const uint32_t sb = smem_u32(smem);
    const int tid = threadIdx.x, warp = tid >> 5, lane = tid & 31;
    const int rank = blockIdx.x & 1;
    {
        const uint32_t b = blockIdx.x & 127;
        const char* u0 = (rank ? pc1 : pc0) + (b >> 1) * (32 * S_ * 2);
        const char* u1 = px + b * 512 - 4096;
        asm volatile("{.reg .pred p, q; .reg .b64 a; .reg .b32 t; setp.lt.u32 p, %2, 32; mad.wide.u32 a, %2, 4096, %0; @p prefetch.global.L2 [a];"
                     " sub.u32 t, %2, 32; setp.lt.u32 q, t, 4; mad.wide.u32 a, %2, 128, %1; @q prefetch.global.L2 [a];}" ::"l"(u0), "l"(u1), "r"(tid));
    }
    const uint32_t tstart = clk();
    uint32_t smid;
    asm volatile("mov.u32 %0, %%smid;" : "=r"(smid));
    const int u = smid >> 1, v7 = ((u - 32) * 37) >> 8;
    const int tn = sel(u >> 3, sel(v7, u - 62, u < 60), u < 32);
    const int tm = sel(u & 7, sel(u - 23 - 7 * v7, 8, u < 60), u < 32);
    const bool spare = tn < 0;
    const int role = tm * 4 + tn, cta = role * 2 + rank;
    const int comp = rank;
    const CUtensorMap* mC = comp ? &p.mCim : &p.mCre;
#define ARM(j) do { mbar_init(sb + B_FULL + 8 * (j), 1); mbar_expect_tx(sb + B_FULL + 8 * (j), 32768); } while (0)
#define FIRST(j) do { tma2d(sb + a_addr(j), mC, (j) * 64, tm * 128, sb + B_FULL + 8 * (j));                        \
                      tma3d(sb + b_addr(j), &p.mX2, (j) * 64, tn * 2, sb + B_FULL + 8 * (j)); } while (0)
    if (tid == 384) {
        ARM(0);
        if (!spare) FIRST(0);
    }
    const int wu = __shfl_sync(0xffffffffu, warp, 0);
    if (wu < 12) {
        if (lane == 0) {
            mbar_init(sb + B_EMPTY + 8 * wu, wu < 7 ? 4 : 1);
#pragma unroll
            for (int i = 12; i < NBAR; i += 12) if (i + 12 <= NBAR || wu < NBAR - i) mbar_init(sb + B_EMPTY + 8 * (i + wu), 1);
            if (wu >= 7 && wu < 10) mbar_expect_tx(sb + B_EMPTY + 8 * wu, wu < 9 ? 8192 : 256);
        }
        asm volatile("fence.mbarrier_init.release.cluster;" ::: "memory");
        __syncwarp();
        asm volatile("barrier.cluster.arrive.relaxed.aligned;" ::: "memory");
        if (spare) {
            spare_job(p, g, smem, smid & 3, tstart);
        } else if (wu >= 8) {
            asm volatile("setmaxnreg.dec.sync.aligned.u32 " STR(RS_) ";");
            asm volatile("barrier.cluster.wait.acquire.aligned;" ::: "memory");
            const int t = tid - 256, w = wu - 8;
            const bool ffn = cta < FFN_CTAS;
            nap_until(tstart + SIDE_T0);
            const uint4 gw0 = ldg_nc_off<0>(p.gate_w + lane * 8), gw1 = ldg_nc_off<512>(p.gate_w + lane * 8);
            const uint4 rw0 = ldg_nc_off<0>(p.w_r + lane * 8), rw1 = ldg_nc_off<512>(p.w_r + lane * 8);
            const uint32_t epoch = ld_relaxed(g->epoch + cta) + 1u, par = epoch & 1u;
            nap_until(tstart + ROUTER_T0 + (2 * w + rank) * ROUTER_DT);
            {
                const int row0 = cta * 16 + w * 4;
                const char* xp = px + (uint32_t)row0 * (D_ * 2) + lane * 16;
                uint4 xa[4], xb[4];
                xa[0] = ldg_nc_off<0>(xp);    xb[0] = ldg_nc_off<512>(xp);  xa[1] = ldg_nc_off<1024>(xp); xb[1] = ldg_nc_off<1536>(xp);
                xa[2] = ldg_nc_off<2048>(xp); xb[2] = ldg_nc_off<2560>(xp); xa[3] = ldg_nc_off<3072>(xp); xb[3] = ldg_nc_off<3584>(xp);
                float a[8];
#pragma unroll
                for (int i = 0; i < 4; i++) {
                    const uint32_t xv[8] = {xa[i].x, xa[i].y, xa[i].z, xa[i].w, xb[i].x, xb[i].y, xb[i].z, xb[i].w};
                    const uint32_t gv[8] = {gw0.x, gw0.y, gw0.z, gw0.w, gw1.x, gw1.y, gw1.z, gw1.w};
                    const uint32_t rv[8] = {rw0.x, rw0.y, rw0.z, rw0.w, rw1.x, rw1.y, rw1.z, rw1.w};
                    float uu = 0.f, vv = 0.f;
#pragma unroll
                    for (int j = 0; j < 8; j++) {
                        uu = fmaf(bflo(xv[j]), bflo(gv[j]), uu); uu = fmaf(bfhi(xv[j]), bfhi(gv[j]), uu);
                        vv = fmaf(bflo(xv[j]), bflo(rv[j]), vv); vv = fmaf(bfhi(xv[j]), bfhi(rv[j]), vv);
                    }
                    a[i] = uu; a[4 + i] = vv;
                }
                halve<4, 16>(a); halve<2, 8>(a); halve<1, 4>(a);
                {
                    const float b1 = __shfl_xor_sync(0xffffffffu, a[0], 1), b2 = __shfl_xor_sync(0xffffffffu, a[0], 2),
                                b3 = __shfl_xor_sync(0xffffffffu, a[0], 3);
                    a[0] = (a[0] + b1) + (b2 + b3);
                }
                const int row = row0 + ((lane >> 2) & 3);
                if (lane < 16 && (lane & 3) == 0) st_relaxed(&g->gate[row], tagf(sigmoidf_(a[0]), par));
                const uint32_t best = __reduce_max_sync(0xffffffffu, lane >= 16 && (lane & 3) == 0 ? router_key(a[0], row) : 0u);
                if (lane == 0) *(volatile uint32_t*)(smem + M_RED + w * 4) = best;
                named_bar(1, 128);
                if (t < 8) {
                    const uint4 k = *(const uint4*)(smem + M_RED);
                    st_key(&g->keys[t * NCTA + cta], max(max(k.x, k.y), max(k.z, k.w)) | (par << 15));
                }
            }
            uint32_t vd[32];
            if (ffn) {
                mbar_wait(sb + B_FFN + 24, 0);
#pragma unroll
                for (int j = 0; j < 32; j++) vd[j] = lds32(sb + R6 + ((j >> 3) & 1) * 16384 + (2 + (j >> 4)) * 4096 + (j & 7) * 512 + t * 4);
                mbar_arrive_warp(sb + B_VD);
            }
            if (w == 0) {
                const uint4 k4 = wait_tags(g->keys + (tm & 7) * NCTA + lane * 4, 15, par);
                const uint32_t k = __reduce_max_sync(0xffffffffu, max(max(k4.x, k4.y), max(k4.z, k4.w)));
                if (lane == 0) { *(volatile uint32_t*)(smem + M_KEY) = k; *(volatile uint32_t*)(smem + M_PAR) = par; st_relaxed(g->epoch + cta, epoch); }
                sts128(sb + M_UPD + lane * 16, ldg_nc_off<0>(px + (0x7fff - (k & 0x7fffu)) * (D_ * 2) + rank * 512 + lane * 16));
            } else if (w == 1) {
                const uint4 g4 = wait_tags(g->gate + tm * 128 + lane * 4, 0, par);
                *(uint4*)(smem + M_G + lane * 16) = make_uint4(g4.x & ~1u, g4.y & ~1u, g4.z & ~1u, g4.w & ~1u);
            }
            named_bar(1, 128);
            mbar_arrive_if(sb + B_GATE, t == 0);
            const int idx = 0x7fff - (int)(*(volatile uint32_t*)(smem + M_KEY) & 0x7fffu);
            if (ffn) {
                float a[16], xs[8];
#pragma unroll
                for (int i = 0; i < 8; i++) {
                    a[i] = 0.f; a[8 + i] = 0.f;
                    xs[i] = __bfloat162float(((const bf16*)(smem + M_UPD))[32 * i + (t >> 2)]);
                }
#pragma unroll
                for (int i = 0; i < 8; i++) {
                    if (!(i & 1)) mbar_wait(sb + B_FFN + 4 * i, i == 6);
                    const uint4 vg = lds128(sb + R6 + i * 2048 + t * 16);
                    const uint4 vu = lds128(sb + R6 + 16384 + i * 2048 + t * 16);
                    const uint32_t g4[4] = {vg.x, vg.y, vg.z, vg.w};
                    const uint32_t u4[4] = {vu.x, vu.y, vu.z, vu.w};
#pragma unroll
                    for (int j = 0; j < 4; j++) {
                        a[2 * j] = fmaf(xs[i], bflo(g4[j]), a[2 * j]);         a[2 * j + 1] = fmaf(xs[i], bfhi(g4[j]), a[2 * j + 1]);
                        a[8 + 2 * j] = fmaf(xs[i], bflo(u4[j]), a[8 + 2 * j]); a[9 + 2 * j] = fmaf(xs[i], bfhi(u4[j]), a[9 + 2 * j]);
                    }
                }
                halve<8, 16>(a); halve<4, 8>(a); halve<2, 4>(a);
                float* red = (float*)(smem + M_UPD);
                *(float2*)&red[w * 64 + (lane >> 4) * 32 + (lane & 3) * 8 + ((lane >> 2) & 3) * 2] = make_float2(a[0], a[1]);
                named_bar(1, 128);
                mbar_arrive_if(sb + B_R6, t == 0);
                const float sg = red[lane] + red[64 + lane] + red[128 + lane] + red[192 + lane];
                const float su = red[32 + lane] + red[96 + lane] + red[160 + lane] + red[224 + lane];
                if (w < 2) {
                    asm volatile("st.async.weak.shared::cluster.mbarrier::complete_tx::bytes.f32 [%0], %1, [%2];"
                                 ::"r"(mapa(sb + M_HX + t * 4, rank ^ 1)), "f"(w ? su : sg), "r"(mapa(sb + B_HX, rank ^ 1)) : "memory");
                }
                named_bar(1, 128);
                mbar_wait(sb + B_HX, 0);
                const float pg = ((const float*)(smem + M_HX))[lane], pu = ((const float*)(smem + M_HX))[32 + lane];
                const float gs = sg + pg, us = su + pu;
                float* hrow = red + w * 32;
                hrow[lane] = gs * sigmoidf_(gs) * us;
                __syncwarp();
                float o0 = 0.f, o1 = 0.f;
#pragma unroll
                for (int j4 = 0; j4 < 8; j4++) {
                    const float4 hv = *(const float4*)&hrow[j4 * 4];
                    o0 = fmaf(hv.x, bflo(vd[4 * j4]), o0);     o1 = fmaf(hv.x, bfhi(vd[4 * j4]), o1);
                    o0 = fmaf(hv.y, bflo(vd[4 * j4 + 1]), o0); o1 = fmaf(hv.y, bfhi(vd[4 * j4 + 1]), o1);
                    o0 = fmaf(hv.z, bflo(vd[4 * j4 + 2]), o0); o1 = fmaf(hv.z, bfhi(vd[4 * j4 + 2]), o1);
                    o0 = fmaf(hv.w, bflo(vd[4 * j4 + 3]), o0); o1 = fmaf(hv.w, bfhi(vd[4 * j4 + 3]), o1);
                }
                asm volatile("st.relaxed.gpu.global.v2.u32 [%0], {%1,%2};" ::"l"(&g->part[role * D_ + rank * 256 + t * 2]),
                             "r"(tagf(o0, par)), "r"(tagf(o1, par)) : "memory");
                if (lane == 0) asm volatile("red.relaxed.gpu.global.add.u32 [%0], 1;" ::"l"(g->phint + ((rank * 2 + (w >> 1)) * 8 + role / 7) * 8) : "memory");
            }
            if (!ffn) mbar_arrive_if(sb + B_R6, t == 0);
            if (w < 3) {
                fetch_job<1>(p, g, smem, sb, cta, w, par);
            } else {
                if (lds32(sb + M_ROLE) != (uint32_t)role) __trap();
                if ((idx >> 6) == 2 * tm + 1 - comp) {
                    *(uint4*)(smem + M_RED + lane * 16) = wait_tags(g->upd + tn * 128 + lane * 4, 0, par);
                    mbar_arrive_warp(sb + B_SIDE);
                }
            }
        } else {
            const int wg = wu >> 2;
            const uint32_t sbd = (sb & 0x3FFFF) >> 4;
            const bool lead = (tid & 127) == 0;
            const bool early = wg == comp;
            const int q = lane & 3;
            const int r0 = (warp & 3) * 16 + (lane >> 2);
            float acc[64];
            const uint32_t da0 = sbd + 0x10000 + wg * 512, db0 = sbd + 0x2000000, dd0 = sbd + 0x10000;
            const uint32_t rE = mapa(sb + B_EMPTY, rank ^ 1);
#define WAITFULL(s) mbar_wait(sb + B_FULL + 8 * ((s) % NST), ((s) / NST) & 1)
#define TESTFULL(s) mbar_test(sb + B_FULL + 8 * ((s) % NST), ((s) / NST) & 1)
#define WAITD(pos) do { if ((pos) >= 4) mbar_wait(sb + B_DL + 8 * ((pos) - 4), 0); else if ((pos) >= 2) mbar_wait(sb + B_D6, 0); else WAITFULL(32); } while (0)
#define MMA_A(s, kk) wgmma128(acc, desc_lo(da0 + a_addr(s) / 16 + (kk) * 2), desc_lo(db0 + b_addr(s) / 16 + (kk) * 128), 1)
            asm volatile("setmaxnreg.inc.sync.aligned.u32 " STR(RC) ";");
            asm volatile("barrier.cluster.wait.acquire.aligned;" ::: "memory");
            WAITFULL(0);
            wg_fence();
#pragma unroll
            for (int kk = 0; kk < 4; kk++) wgmma128(acc, desc_lo(da0 + kk * 2), desc_lo(db0 + b_addr(0) / 16 + kk * 128), kk != 0);
            wg_commit();
            int slot = 1, ph = 0, pslot = 0;
            const uint32_t ooff = (uint32_t)((tm * 128 + wg * 64 + r0) * D_ + tn * 128 + q * 8) * 2u;
            uint32_t* fout = g->frag + (cta * 2 + wg) * 4096 + (warp & 3) * 128 + lane;
            uint32_t tagm[4];
#pragma unroll
            for (int c = 0; c < 4; c++) tagm[c] = (lane & 7) == (warp & 1) * 4 + c;
            const char* xp = px + ooff;
            asm volatile("" : "+r"(tagm[0]), "+r"(tagm[1]), "+r"(tagm[2]), "+r"(tagm[3]), "+l"(xp), "+l"(fout));
            uint4 w[8];
#pragma unroll
            for (int i = 0; i < 8; i++) w[i] = make_uint4(0, 0, 0, 0);
#pragma unroll
            for (int part = 0; part <= XN; part++) {
                if (part) {
#pragma unroll
                    for (int i = (part - 1) * 8 / XN; i < part * 8 / XN; i++) ldg_nc_if(w[i], xp + (i & 1) * 8192 + (i >> 1) * 64, early);
                }
#pragma unroll 1
                for (int step = part ? XLD + (part - 1) * XD : 1; step < (part < XN ? XLD + part * XD : SP0); step++) {
                    mbar_wait(sb + B_FULL + 8 * slot, ph);
                    const uint32_t a = da0 + slot * 1024, b = db0 + b_addr(0) / 16 + slot * 1024;
                    wg_fence();
                    wgmma128(acc, desc_lo(a), desc_lo(b), 1);
                    wg_commit();
                    wg_wait<1>();
                    mbar_arrive_if(sb + B_EMPTY + 8 * pslot, lead);
                    mbar_arrive_cluster_if(rE + 8 * pslot, lead);
                    pslot = slot;
                    if (++slot == NST) { slot = 0; ph ^= 1; }
                    wg_fence();
#pragma unroll
                    for (int kk = 1; kk < 4; kk++) wgmma128(acc, desc_lo(a + kk * 2), desc_lo(b + kk * 128), 1);
                    wg_commit();
                }
            }
            uint32_t par;
            float g0, g1;
#define GATES() do { par = lds32(sb + M_PAR); g0 = __uint_as_float(lds32(sb + M_G + (wg * 64 + r0) * 4)); g1 = __uint_as_float(lds32(sb + M_G + (wg * 64 + r0 + 8) * 4)); } while (0)
            if (early) {
                WAITFULL(SP0);
                wg_fence();
                MMA_A(SP0, 0); MMA_A(SP0, 1);
                wg_commit();
                wg_wait<1>();
                mbar_arrive_n_if<2>(sb + B_EMPTY + 8 * ((SP0 - 1) % NST), lead);
                bool ok = TESTFULL(SP0 + 1);
                MMA_A(SP0, 2); MMA_A(SP0, 3);
                wg_commit();
#pragma unroll
                for (int s = SP0 + 1; s < 32; s++) {
                    if (!ok) { WAITFULL(s); if (s == 29) mbar_wait(sb + B_GATE, 0); }
                    wg_fence();
                    MMA_A(s, 0); MMA_A(s, 1);
                    if (s == 29) GATES();
                    if (s >= 30) { wg_commit(); wg_wait<1>(); mbar_arrive_if(sb + (s == 30 ? B_S0 : B_S1), lead); wg_fence(); }
                    if (s < 31) ok = TESTFULL(s + 1) & (s != 28 || mbar_test(sb + B_GATE, 0));
                    MMA_A(s, 2); MMA_A(s, 3);
                    wg_commit();
                }
                wg_wait<0>();
                mbar_arrive_if(sb + B_EA, lead);
            } else {
                wg_wait<0>();
                mbar_arrive_n_if<2>(sb + B_EMPTY + 8 * ((SP0 - 1) % NST), lead);
#pragma unroll
                for (int s = SP0; s < 32; s++) WAITFULL(s);
                mbar_wait(sb + B_GATE, 0);
                GATES();
                mbar_wait(sb + B_S1, 0);
                wg_fence();
#pragma unroll
                for (int s = SP0; s < 32; s++) {
                    MMA_A(s, 0); MMA_A(s, 1);
                    if (s > SP0) {
                        wg_commit();
                        wg_wait<1>();
                        mbar_arrive_n_if<4>(sb + B_EMPTY + 8 * ((s - 1) % NST), lead);
                        if (s == 31) mbar_arrive_if(sb + B_S3, lead);
                        if (s == 30) WAITD(0);
                        wg_fence();
                    }
                    MMA_A(s, 2); MMA_A(s, 3);
                    wg_commit();
                }
                wg_wait<0>();
                mbar_arrive_n_if<4>(sb + B_EMPTY + 8 * (31 % NST), lead);
            }
            fence_regs<0, 64>(acc);
            uint4 f[8];
#define TAG(v, c) (((v) & ~tagm[c]) | (par & tagm[c]))
#define PACK(k) f[k] = make_uint4(TAG(pack_bf16(acc[8 * (k)], acc[8 * (k) + 1]), 0), TAG(pack_bf16(acc[8 * (k) + 2], acc[8 * (k) + 3]), 2), \
                                  TAG(pack_bf16(acc[8 * (k) + 4], acc[8 * (k) + 5]), 1), TAG(pack_bf16(acc[8 * (k) + 6], acc[8 * (k) + 7]), 3))
#define SEND(k) do { st_relaxed(fout + 512 * (k), f[k].x); st_relaxed(fout + 512 * (k) + 32, f[k].z);                        \
                     st_relaxed(fout + 512 * (k) + 64, f[k].y); st_relaxed(fout + 512 * (k) + 96, f[k].w); } while (0)
#define OWN(k) wgmma128rs(acc, f[k], desc_lo(dd0 + d_addr((k) >> 2) / 16 + ((k) & 3) * 2), (k) != 0)
            const uint32_t dfa = sbd + 0x80000 + (early ? comp * 512 : NST * 1024), dfb = sbd + 0x80000 + (early ? (1 - comp) * 512 : NST * 1024 + 512);
#define MMA_F(pos, kk) wgmma128<0>(acc, (uint64_t)(((pos) < 5 ? dfa : dfb) + a_addr(29 + ((pos) - 2) % 3) / 16 + (kk) * 128) | (0x10ull << 32), \
                                   desc_lo(dd0 + d_addr(pos) / 16 + (kk) * 2), 1)
#define WAITF(pos) mbar_wait(vb + 8 * ((pos) - 2), 0)
            const uint32_t vb = sb + B_VAL + (early ? 0 : 48);
            const uint32_t ts = clk();
            if (early) {
                PACK(0); SEND(0); PACK(1); SEND(1); PACK(2); SEND(2); PACK(3); SEND(3);
                until(ts);
                PACK(4); PACK(5); PACK(6); PACK(7);
                const float s0 = comp ? -g0 : g0, s1 = comp ? -g1 : g1;
                const uint32_t og0 = pack_bf16(1.f - g0, 1.f - g0), og1 = pack_bf16(1.f - g1, 1.f - g1);
#pragma unroll
                for (int k = 4; k < 8; k++) {
                    if (k < ESEND) { until(ts + ET1 + (k - 4) * STP); SEND(k); }
#pragma unroll
                    for (int i = 2 * k - 8; i < 2 * k - 6; i++) {
                        const uint32_t og = (i & 1) ? og1 : og0;
                        w[i] = make_uint4(hmul2_bf16(og, w[i].x), hmul2_bf16(og, w[i].y), hmul2_bf16(og, w[i].z), hmul2_bf16(og, w[i].w));
                        asm volatile("" : "+r"(w[i].x), "+r"(w[i].y), "+r"(w[i].z), "+r"(w[i].w));
                    }
                }
                WAITD(0);
                mbar_wait(sb + B_S3, 0);
                wg_fence();
#pragma unroll
                for (int k = 0; k < 8; k++) {
                    OWN(k);
                    if (k >= 1 && k + ESEND - 1 < 8) { wg_commit(); until(ts + ET1 + (k + ESEND - 5) * STP); SEND(k + ESEND - 1); wg_fence(); }
                }
                wg_commit();
                WAITD(2);
                bool ok = false;
#pragma unroll
                for (int pos = 2; pos < 8; pos++) {
                    if (!ok) {
                        if (pos >= 4) WAITD(pos);
                        WAITF(pos);
                    }
                    wg_fence();
                    MMA_F(pos, 0); MMA_F(pos, 1);
                    if (pos == 6) { wg_commit(); wg_wait<1>(); mbar_arrive_cluster_if(mapa(sb + B_XF, rank ^ 1), lead); wg_fence(); }
                    if (pos == 7) mbar_arrive_if(sb + B_S2, lead);
                    if (pos < 7) ok = mbar_test(vb + 8 * (pos - 1), 0) & (pos < 3 || mbar_test(sb + B_DL + 8 * (pos - 3), 0));
                    MMA_F(pos, 2); MMA_F(pos, 3);
                    wg_commit();
                }
                const uint32_t xd = mapa(sb + a_addr(29) + (tid & 127) * 16, rank ^ 1), xb = mapa(sb + B_X, rank ^ 1);
                mbar_wait(sb + B_XF, 0);
                wg_wait<0>();
                fence_regs<0, 64>(acc);
                keep_regs<0, 8>(f);
#pragma unroll
                for (int i = 0; i < 8; i++) {
                    const uint4 z = scale_add((i & 1) ? s1 : s0, acc, 16 * (i >> 1) + 2 * (i & 1), w[i]);
                    st_async16(xd + i * 2048, z.x, z.y, z.z, z.w, xb + 2 * (i & 4));
                    if (i & 1) until(ts);
                }
            } else {
                PACK(0); PACK(1); PACK(2); PACK(3); PACK(4); PACK(5); PACK(6); PACK(7);
                wg_fence();
#pragma unroll
                for (int k = 0; k < 8; k++) {
                    OWN(k);
                    if ((k & 1) && k / 2 < LSEND) { wg_commit(); until(ts + LT0 + k / 2 * LTP); SEND(k / 2); wg_fence(); }
                }
                wg_commit();
#pragma unroll
                for (int k = LSEND; k < 8; k++) { until(ts + LT0 + k * LTP); SEND(k); }
                float s0 = comp ? -g0 : g0, s1 = comp ? -g1 : g1;
                const int rr = 0x7fff - (int)(lds32(sb + M_KEY) & 0x7fffu) - (tm * 128 + wg * 64 + r0);
                uint32_t xs = sb + a_addr(29) + (tid & 127) * 16;
                char* op = pout + ooff;
                asm volatile("" : "+f"(s0), "+f"(s1), "+r"(xs), "+l"(op));
                WAITF(2);
                mbar_wait(sb + B_S2, 0);
                bool there = false, there1 = false, ok = true;
#pragma unroll
                for (int pos = 2; pos < 8; pos++) {
                    if (!ok) WAITF(pos);
                    wg_fence();
                    MMA_F(pos, 0);
                    if (pos == XPOS) there = mbar_test(sb + B_X, 0);
                    MMA_F(pos, 1);
                    if (pos == XPOS) {
#pragma unroll
                        for (int i = 0; i < 4; i++) lds128_if(w[i], xs + i * 2048, there);
                    }
                    if (pos < 7) ok = mbar_test(vb + 8 * (pos - 1), 0);
                    MMA_F(pos, 2);
                    if (pos == 7) there1 = mbar_test(sb + B_X + 8, 0);
                    MMA_F(pos, 3);
                    wg_commit();
                }
#pragma unroll
                for (int i = 4; i < 8; i++) lds128_if(w[i], xs + i * 2048, there1);
#pragma unroll
                for (int h = 0; h < 2; h++) {
                    if (!(h ? there1 : there)) {
                        mbar_wait(sb + B_X + 8 * h, 0);
#pragma unroll
                        for (int i = 4 * h; i < 4 * h + 4; i++) w[i] = lds128(xs + i * 2048);
                    }
                    if (h == 0) {
                        wg_wait<0>();
                        fence_regs<0, 64>(acc);
                        keep_regs<0, 8>(f);
                    }
#pragma unroll
                    for (int i = 4 * h; i < 4 * h + 4; i++) {
                        stg_off<0>(op + (i & 1) * 8192 + (i >> 1) * 64, scale_add((i & 1) ? s1 : s0, acc, 16 * (i >> 1) + 2 * (i & 1), w[i]));
                        __syncwarp();
                    }
                }
                if (rr == 0 || rr == 8) {
                    const bool hi = rr == 8;
                    const float og = 1.f - (hi ? g1 : g0), s = hi ? s1 : s0;
                    mbar_wait(sb + B_SIDE, 0);
#pragma unroll
                    for (int j = 0; j < 4; j++) {
                        const float4 ua = *(const float4*)(smem + M_RED + j * 128 + q * 32), ub = *(const float4*)(smem + M_RED + j * 128 + q * 32 + 16);
                        const uint4 v = hi ? w[2 * j + 1] : w[2 * j];
                        float a[8];
#pragma unroll
                        for (int k = 0; k < 8; k++) a[k] = selpf(acc[16 * j + 4 * (k >> 1) + (k & 1) + 2], acc[16 * j + 4 * (k >> 1) + (k & 1)], hi);
                        stg_off<0>(op + rr * 1024 + j * 64,
                                   make_uint4(pack_bf16(fmaf(og, ua.x, fmaf(s, a[0], bflo(v.x))), fmaf(og, ua.y, fmaf(s, a[1], bfhi(v.x)))),
                                              pack_bf16(fmaf(og, ua.z, fmaf(s, a[2], bflo(v.y))), fmaf(og, ua.w, fmaf(s, a[3], bfhi(v.y)))),
                                              pack_bf16(fmaf(og, ub.x, fmaf(s, a[4], bflo(v.z))), fmaf(og, ub.y, fmaf(s, a[5], bfhi(v.z)))),
                                              pack_bf16(fmaf(og, ub.z, fmaf(s, a[6], bflo(v.w))), fmaf(og, ub.w, fmaf(s, a[7], bfhi(v.w))))));
                    }
                }
            }
        }
    } else {
#define STEP0(j) do { tma2d_elect(sb + (j) * 16384, mC, (j) * 64, tm * 128, sb + B_FULL + 8 * (j));                            \
                      tma3d_elect(sb + (NST + (j)) * 16384, &p.mX2, (j) * 64, tn * 2, sb + B_FULL + 8 * (j)); } while (0)
        if (wu >= 14) {
            const uint32_t b = blockIdx.x;
            const char* q = wu == 14 ? (rank ? pc1 : pc0) + (uint32_t)((b >> 1) * 32 + lane) * (S_ * 2) + 128 : px + (uint32_t)(b * 4 + lane) * 128 + 65536;
            until(tstart + P_1);
            if (b < 128 && (wu == 14 || lane < 4)) prefetch_l2(q);
        } else if (wu == 13 && !spare) {
            if (lane == 0) ARM(1);
            __syncwarp();
            until(tstart + T_1);
            STEP0(1);
        }
        if (lane == 0) ARM(wu - 10);
        asm volatile("fence.mbarrier_init.release.cluster;" ::: "memory");
        __syncwarp();
        asm volatile("barrier.cluster.arrive.relaxed.aligned;" ::: "memory");
        if (spare) return;
        asm volatile("setmaxnreg.dec.sync.aligned.u32 " STR(RU) ";");
        if (wu < 14) {
            until(tstart + T_2 + (wu - 12) * PACE);
            STEP0(wu - 10);
        }
        asm volatile("barrier.cluster.wait.acquire.aligned;" ::: "memory");
        if (wu == 13) {
            const CUtensorMap* mD = comp ? &p.mDim : &p.mDre;
#pragma unroll
            for (int step = 4; step < 32; step++) {
                const uint32_t full = sb + B_FULL + 8 * (step % NST);
                if (step < NST) {
                    until(tstart + T_2 + (step - 2) * PACE);
                    tma3d_elect(sb + b_addr(step), &p.mX2, step * 64, tn * 2, full);
                } else {
                    mbar_wait(sb + B_EMPTY + 8 * (step % NST), (step / NST - 1) & 1);
                    tma2d_pair_elect(sb + b_addr(step) + rank * 8192, &p.mX, tn * 128 + rank * 64, step * 64, full);
                }
            }
#pragma unroll
            for (int c = 0; c < 4; c += 2) {
                const uint32_t bar = sb + (c ? B_D6 : B_FULL + 8 * (32 % NST));
                if (c) mbar_wait(sb + B_R6, 0);
                else mbar_wait(sb + B_EMPTY + 8 * (26 % NST), (26 / NST) & 1);
                tma5d_elect(sb + d_addr(c), mD, dcol(c, tn), tn * 4, bar);
                tma5d_elect(sb + d_addr(c + 1), mD, dcol(c + 1, tn), tn * 4, bar);
                mbar_expect_tx_elect(bar, 32768);
            }
#pragma unroll
            for (int c = 0; c < 4; c++) mbar_expect_tx_elect(sb + B_DL + 8 * c, 16384);
            mbar_wait(sb + B_S1, 0);
            const uint32_t tq = clk();
#pragma unroll
            for (int c = 0; c < 4; c++) {
                if (!(c & 1)) mbar_wait(sb + B_EMPTY + 8 * ((27 + c / 2) % NST), ((27 + c / 2) / NST) & 1);
                if (c) until(tq + (c == 1 ? T_D5 : c == 2 ? T_D6 : T_D7));
                tma5d_elect(sb + d_addr(4 + c), mD, dcol(4 + c, tn), tn * 4, sb + B_DL + 8 * c);
            }
        } else {
            if (wu == 12) {
#pragma unroll
                for (int step = 4; step < 32; step++) {
                    const uint32_t full = sb + B_FULL + 8 * (step % NST);
                    if (step >= NST) mbar_wait(sb + B_EMPTY + 8 * (step % NST), (step / NST - 1) & 1);
                    else until(tstart + T_2 + (step - 2) * PACE);
                    tma2d_elect(sb + a_addr(step), mC, step * 64, tm * 128, full);
                    if (step >= NST) mbar_expect_tx_elect(full, 32768);
                }
            } else if (wu == 14) {
                if (lane == 0) {
                    asm volatile("prefetch.tensormap [%0];" ::"l"(&p.mX) : "memory");
                    asm volatile("prefetch.tensormap [%0];" ::"l"(&p.mF) : "memory");
                    asm volatile("prefetch.tensormap [%0];" ::"l"(comp ? &p.mDim : &p.mDre) : "memory");
                    asm volatile("st.shared::cluster.u32 [%0], %1;" ::"r"(mapa(sb + M_ROLE, rank ^ 1)), "r"(role) : "memory");
                }
                mbar_wait(sb + B_GATE, 0);
                if (lane < 2) stg_off<0>(g->stamp + cta * 32 + lane * 4, make_uint4(lds32(sb + M_PAR) ^ 1u, 0, 0, 0));
            } else {
                const uint32_t t1 = tstart + FFN_T0 + (rank + 2 * (tm & 1)) * (FFN_DT / 4);
                if (cta < FFN_CTAS) {
#pragma unroll
                    for (int i = 0; i < 12; i++) {
                        const int qu = i < 4 ? 2 + (i >> 1) : (i - 4) >> 1;
                        const uint32_t bar = sb + B_FFN + 8 * (i < 4 ? 3 : qu), dst = sb + R6 + (i & 1) * 16384 + qu * 4096;
                        if (i == 8) mbar_wait(sb + B_VD, 0);
                        if (i == 0 || (i >= 4 && !(i & 1))) mbar_expect_tx_elect(bar, i ? 8192 : 16384);
                        nap_until(t1 + i * FFN_DT);
                        if (i < 4) tma2d_elect(dst, &p.mWd, rank * 256, role * 32 + i * 8, bar);
                        else tma2d_elect(dst, (i & 1) ? &p.mWu : &p.mWg, role * 32, rank * 256 + qu * 64, bar);
                    }
                }
            }
            __syncwarp();
            mbar_wait(sb + B_GATE, 0);
            fetch_job<0>(p, g, smem, sb, cta, wu == 12 ? 2 : wu - 14, lds32(sb + M_PAR));
        }
    }
}

typedef CUresult (*EncodeTiledFn)(CUtensorMap*, CUtensorMapDataType, cuuint32_t, void*, const cuuint64_t*, const cuuint64_t*,
                                  const cuuint32_t*, const cuuint32_t*, CUtensorMapInterleave, CUtensorMapSwizzle,
                                  CUtensorMapL2promotion, CUtensorMapFloatOOBfill);

static void make_map(EncodeTiledFn enc, CUtensorMap* m, const void* base, uint64_t cols, uint64_t rows, uint32_t box_rows,
                     CUtensorMapSwizzle sw = CU_TENSOR_MAP_SWIZZLE_128B, uint32_t box_cols = 64,
                     CUtensorMapL2promotion promo = CU_TENSOR_MAP_L2_PROMOTION_L2_128B) {
    cuuint64_t dims[2] = {cols, rows};
    cuuint64_t str[1] = {cols * 2};
    cuuint32_t box[2] = {box_cols, box_rows};
    cuuint32_t es[2] = {1, 1};
    enc(m, CU_TENSOR_MAP_DATA_TYPE_BFLOAT16, 2, (void*)base, dims, str, box, es, CU_TENSOR_MAP_INTERLEAVE_NONE,
        sw, promo, CU_TENSOR_MAP_FLOAT_OOB_FILL_NONE);
}

static void make_map_chunks(EncodeTiledFn enc, CUtensorMap* m, const void* base, uint64_t rows) {
    cuuint64_t dims[3] = {64, rows, D_ / 64};
    cuuint64_t str[2] = {D_ * 2, 128};
    cuuint32_t box[3] = {64, 64, 2};
    cuuint32_t es[3] = {1, 1, 1};
    enc(m, CU_TENSOR_MAP_DATA_TYPE_BFLOAT16, 3, (void*)base, dims, str, box, es, CU_TENSOR_MAP_INTERLEAVE_NONE,
        CU_TENSOR_MAP_SWIZZLE_128B, CU_TENSOR_MAP_L2_PROMOTION_L2_128B, CU_TENSOR_MAP_FLOAT_OOB_FILL_NONE);
}

static void make_map_perm(EncodeTiledFn enc, CUtensorMap* m, const void* base) {
    cuuint64_t dims[5] = {D_, 2, 4, 4, D_ / 32};
    cuuint64_t str[4] = {D_ * 2, 8 * D_ * 2, 2 * D_ * 2, 32 * D_ * 2};
    cuuint32_t box[5] = {64, 2, 4, 4, 4};
    cuuint32_t es[5] = {1, 1, 1, 1, 1};
    enc(m, CU_TENSOR_MAP_DATA_TYPE_BFLOAT16, 5, (void*)base, dims, str, box, es, CU_TENSOR_MAP_INTERLEAVE_NONE,
        CU_TENSOR_MAP_SWIZZLE_128B, CU_TENSOR_MAP_L2_PROMOTION_L2_128B, CU_TENSOR_MAP_FLOAT_OOB_FILL_NONE);
}

extern "C" void kernel_launch(void* const* d_in, const int* in_sizes, int n_in, void* d_out, int out_size) {
    (void)in_sizes; (void)n_in; (void)out_size;
    static EncodeTiledFn enc = nullptr;
    static bool fused_ok = false;
    static void* scr = nullptr;
    if (!enc) {
        void* fn = nullptr;
        cudaDriverEntryPointQueryResult q;
        cudaGetDriverEntryPoint("cuTensorMapEncodeTiled", &fn, cudaEnableDefault, &q);
        enc = (EncodeTiledFn)fn;
        cudaGetSymbolAddress(&scr, g_scr);
        cudaFuncSetAttribute(fused_kernel, cudaFuncAttributeMaxDynamicSharedMemorySize, SMEM_BYTES);
        int dev = 0, nsm = 0, ncl = 0;
        cudaGetDevice(&dev);
        cudaDeviceGetAttribute(&nsm, cudaDevAttrMultiProcessorCount, dev);
        cudaLaunchConfig_t cfg = {};
        cfg.gridDim = dim3(132); cfg.blockDim = dim3(NTHREADS); cfg.dynamicSmemBytes = SMEM_BYTES;
        cudaLaunchAttribute at;
        at.id = cudaLaunchAttributeClusterDimension;
        at.val.clusterDim.x = 2; at.val.clusterDim.y = 1; at.val.clusterDim.z = 1;
        cfg.attrs = &at; cfg.numAttrs = 1;
        fused_ok = cudaOccupancyMaxActiveClusters(&ncl, fused_kernel, &cfg) == cudaSuccess && nsm == 132 && ncl == 66;
        (void)cudaGetLastError();
    }
    if (!fused_ok) {
        const bf16* const* in = (const bf16* const*)d_in;
        fb_hidden<<<S_, D_, 0, cudaStreamPerThread>>>(in[0], in[3], in[4], in[10], in[6]);
        fb_ffn1<<<F_ / 128, 128, 0, cudaStreamPerThread>>>(in[0], in[7], in[8]);
        fb_ffn2<<<D_ / 64, 64, 0, cudaStreamPerThread>>>(in[9]);
        fb_seq<<<S_, D_, 0, cudaStreamPerThread>>>(in[0], in[1], in[2], (bf16*)d_out);
        return;
    }
    Params p;
    p.dre = (const bf16*)d_in[3];
    p.dim = (const bf16*)d_in[4];
    p.w_r = (const bf16*)d_in[6];
    p.gate_w = (const bf16*)d_in[10];
    make_map_chunks(enc, &p.mX2, d_in[0], S_);
    make_map(enc, &p.mX, d_in[0], D_, S_, 64);
    make_map(enc, &p.mCre, d_in[1], S_, S_, 128);
    make_map(enc, &p.mCim, d_in[2], S_, S_, 128);
    make_map_perm(enc, &p.mDre, d_in[3]);
    make_map_perm(enc, &p.mDim, d_in[4]);
    make_map(enc, &p.mF, scr, 64, NCTA * 256, 64, CU_TENSOR_MAP_SWIZZLE_NONE);
    make_map(enc, &p.mWg, d_in[7], F_, D_, 64, CU_TENSOR_MAP_SWIZZLE_NONE, 32, CU_TENSOR_MAP_L2_PROMOTION_NONE);
    make_map(enc, &p.mWu, d_in[8], F_, D_, 64, CU_TENSOR_MAP_SWIZZLE_NONE, 32, CU_TENSOR_MAP_L2_PROMOTION_NONE);
    make_map(enc, &p.mWd, d_in[9], D_, F_, 8, CU_TENSOR_MAP_SWIZZLE_NONE, 256);
    fused_kernel<<<132, NTHREADS, SMEM_BYTES, cudaStreamPerThread>>>((const char*)d_in[1], (const char*)d_in[2], (const char*)d_in[0], (char*)d_out, (Scratch*)scr, p);
}
```

```cpp
#include <cuda_runtime.h>
#include <cuda.h>
#include <cuda_bf16.h>
#include <stdint.h>

typedef __nv_bfloat16 bf16;

constexpr int S_ = 2048, D_ = 512, F_ = 1792;
constexpr int NCTA = 128;
constexpr int NTHREADS = 512;
constexpr int NST = 6;
constexpr int SP0 = 27;
constexpr int FFN_CTAS = F_ / 16;
constexpr uint32_t SPIN_LIMIT = 1u << 16;

#define P_1 500
#define T_1 550
#define T_2 1050
#define PACE 400
#define ROUTER_T0 3000
#define ROUTER_DT 280
#define FFN_T0 5200
#define FFN_DT 640
#define XLD 10
#define XN 8
#define XD 1
#define PFD_T0 12200
#define PFD_DT 250
#define SUM_T0 14000
#define ET1 600
#define STP 170
#define ESEND 6
#define LT0 450
#define LTP 170
#define LSEND 3
#define SDEL 280
#define E_RD0 1330
#define E_RD1 2180
#define L_RD0 3300
#define L_RD1 3930
#define SG 130
#define T_D5 1500
#define T_D6 1700
#define T_D7 2400
#define XPOS 7
#define RC 168
#define RS_ 112
#define RU 64
#define KEY_T0 9800
#define NOFFN_MASK 0x00c8800f00000000ull
#define SIDE_T0 2800
#define STR2(x) #x
#define STR(x) STR2(x)

__host__ __device__ constexpr int a_addr(int s) { return s % NST * 16384; }
__host__ __device__ constexpr int b_addr(int s) { return (NST + s % NST) * 16384; }
constexpr int R6 = 2 * NST * 16384;
__host__ __device__ constexpr int d_addr(int p) { return p / 2 == 1 ? R6 + (p & 1) * 16384 : (p & 1) ? b_addr(26 + p / 3) : a_addr(26 + p / 3); }
static_assert(d_addr(0) == a_addr(26) && d_addr(4) == a_addr(27) && d_addr(6) == a_addr(28), "");
constexpr int OFF_MISC = R6 + 32768;
constexpr int B_FULL = OFF_MISC;
constexpr int B_EMPTY = B_FULL + 48;
constexpr int B_VD = B_EMPTY + 48;
constexpr int B_X = B_VD + 8;
constexpr int B_HX = B_X + 16;
constexpr int B_XF = B_HX + 8;
constexpr int B_S0 = B_XF + 8;
constexpr int B_S1 = B_S0 + 8;
constexpr int B_EA = B_S1 + 8;
constexpr int B_S2 = B_EA + 8;
constexpr int B_S3 = B_S2 + 8;
constexpr int B_D6 = B_S3 + 8;
constexpr int B_DL = B_D6 + 8;
constexpr int B_GATE = B_DL + 32;
constexpr int B_SIDE = B_GATE + 8;
constexpr int B_FFN = B_SIDE + 8;
constexpr int B_R6 = B_FFN + 32;
constexpr int B_LAND = B_R6 + 8;
constexpr int B_VAL = B_LAND + 48;
constexpr int B_TH = B_VAL + 96;
constexpr int M_TH = B_TH + 24;
constexpr int NBAR = (M_TH - B_EMPTY) / 8;
constexpr int M_KEY = M_TH + 12;
constexpr int M_PAR = M_KEY + 4;
constexpr int M_ROLE = M_PAR + 4;
constexpr int M_HX = OFF_MISC + 512;
constexpr int M_G = M_HX + 256;
constexpr int M_UPD = M_G + 512;
constexpr int M_RED = M_UPD + 512;
constexpr int SMEM_BYTES = 232448;
static_assert(M_RED + 512 <= SMEM_BYTES && M_ROLE + 4 <= M_HX, "smem");

struct Params {
    const bf16 *gate_w, *w_r, *dre, *dim;
    CUtensorMap mCre, mCim, mX2, mX, mDre, mDim, mF, mWg, mWu, mWd;
};

struct Scratch {
    uint32_t frag[NCTA * 2 * 4096];
    uint32_t stamp[NCTA * 32];
    uint32_t gate[S_];
    uint32_t keys[8 * NCTA];
    uint32_t part[FFN_CTAS / 2 * D_];
    uint32_t phint[4 * 8 * 8];
    uint32_t upd[D_];
    uint32_t epoch[NCTA + 4];
};
__device__ __align__(1024) Scratch g_scr;

__device__ __forceinline__ uint32_t smem_u32(const void* p) { return (uint32_t)__cvta_generic_to_shared(p); }
__device__ __forceinline__ void mbar_init(uint32_t bar, uint32_t cnt) {
    asm volatile("mbarrier.init.shared::cta.b64 [%0], %1;" ::"r"(bar), "r"(cnt) : "memory");
}
__device__ __forceinline__ void mbar_expect_tx(uint32_t bar, uint32_t bytes) {
    asm volatile("mbarrier.arrive.expect_tx.shared::cta.b64 _, [%0], %1;" ::"r"(bar), "r"(bytes) : "memory");
}
__device__ __forceinline__ void mbar_arrive(uint32_t bar) {
    asm volatile("mbarrier.arrive.shared::cta.b64 _, [%0];" ::"r"(bar) : "memory");
}
template <int N>
__device__ __forceinline__ void mbar_arrive_n_if(uint32_t bar, bool pred) {
    asm volatile("{.reg .pred p; setp.ne.b32 p, %1, 0; @p mbarrier.arrive.shared::cta.b64 _, [%0], %2;}" ::"r"(bar), "r"((int)pred), "n"(N) : "memory");
}
__device__ __forceinline__ void mbar_arrive_if(uint32_t bar, bool pred) {
    asm volatile("{.reg .pred p; setp.ne.b32 p, %1, 0; @p mbarrier.arrive.shared::cta.b64 _, [%0];}" ::"r"(bar), "r"((int)pred) : "memory");
}
__device__ __forceinline__ void mbar_arrive_warp(uint32_t bar) {
    __syncwarp();
    mbar_arrive_if(bar, (threadIdx.x & 31) == 0);
}
__device__ __forceinline__ void mbar_arrive_cluster_if(uint32_t bar, bool pred) {
    asm volatile("{.reg .pred p; setp.ne.b32 p, %1, 0; @p mbarrier.arrive.shared::cluster.b64 _, [%0], 1;}"
                 ::"r"(bar), "r"((int)pred) : "memory");
}
__device__ __forceinline__ uint32_t mapa(uint32_t a, uint32_t cta) {
    uint32_t r;
    asm volatile("mapa.shared::cluster.u32 %0, %1, %2;" : "=r"(r) : "r"(a), "r"(cta));
    return r;
}
__device__ __forceinline__ bool mbar_try(uint32_t bar, uint32_t parity) {
    uint32_t ok;
    asm volatile("{.reg .pred p; mbarrier.try_wait.parity.shared::cta.b64 p, [%1], %2; selp.u32 %0,1,0,p;}"
                 : "=r"(ok) : "r"(bar), "r"(parity) : "memory");
    return ok;
}
__device__ __forceinline__ bool mbar_test(uint32_t bar, uint32_t parity) {
    uint32_t ok;
    asm volatile("{.reg .pred p; mbarrier.test_wait.parity.shared::cta.b64 p, [%1], %2; selp.u32 %0,1,0,p;}"
                 : "=r"(ok) : "r"(bar), "r"(parity) : "memory");
    return ok;
}
__device__ __forceinline__ void mbar_wait(uint32_t bar, uint32_t parity) {
    uint32_t n = 0;
#pragma unroll 1
    while (!mbar_try(bar, parity)) { if (++n > SPIN_LIMIT) break; }
}
__device__ __forceinline__ void tma2d(uint32_t dst, const CUtensorMap* m, int c0, int c1, uint32_t bar) {
    asm volatile("cp.async.bulk.tensor.2d.shared::cluster.global.mbarrier::complete_tx::bytes [%0], [%1, {%3,%4}], [%2];"
                 ::"r"(dst), "l"(m), "r"(bar), "r"(c0), "r"(c1) : "memory");
}
__device__ __forceinline__ void tma3d(uint32_t dst, const CUtensorMap* m, int row, int chunk, uint32_t bar) {
    asm volatile("cp.async.bulk.tensor.3d.shared::cluster.global.mbarrier::complete_tx::bytes [%0], [%1, {%3,%4,%5}], [%2];"
                 ::"r"(dst), "l"(m), "r"(bar), "r"(0), "r"(row), "r"(chunk) : "memory");
}
__device__ __forceinline__ void tma2d_elect(uint32_t dst, const CUtensorMap* m, int c0, int c1, uint32_t bar) {
    asm volatile("{.reg .pred p; elect.sync _|p, 0xffffffff;"
                 " @p cp.async.bulk.tensor.2d.shared::cluster.global.mbarrier::complete_tx::bytes [%0], [%1, {%3,%4}], [%2];}"
                 ::"r"(dst), "l"(m), "r"(bar), "r"(c0), "r"(c1) : "memory");
}
__device__ __forceinline__ void tma2d_pair_elect(uint32_t dst, const CUtensorMap* m, int c0, int c1, uint32_t bar) {
    asm volatile("{.reg .pred p; elect.sync _|p, 0xffffffff;"
                 " @p cp.async.bulk.tensor.2d.shared::cluster.global.mbarrier::complete_tx::bytes.multicast::cluster"
                 " [%0], [%1, {%3,%4}], [%2], %5;}" ::"r"(dst), "l"(m), "r"(bar), "r"(c0), "r"(c1), "h"((uint16_t)3) : "memory");
}
__device__ __forceinline__ void tma3d_elect(uint32_t dst, const CUtensorMap* m, int row, int chunk, uint32_t bar) {
    asm volatile("{.reg .pred p; elect.sync _|p, 0xffffffff;"
                 " @p cp.async.bulk.tensor.3d.shared::cluster.global.mbarrier::complete_tx::bytes [%0], [%1, {%3,%4,%5}], [%2];}"
                 ::"r"(dst), "l"(m), "r"(bar), "r"(0), "r"(row), "r"(chunk) : "memory");
}
__device__ __forceinline__ void tma5d_elect(uint32_t dst, const CUtensorMap* m, int c0, int c4, uint32_t bar) {
    asm volatile("{.reg .pred p; elect.sync _|p, 0xffffffff;"
                 " @p cp.async.bulk.tensor.5d.shared::cluster.global.mbarrier::complete_tx::bytes [%0], [%1, {%3,%5,%5,%5,%4}], [%2];}"
                 ::"r"(dst), "l"(m), "r"(bar), "r"(c0), "r"(c4), "r"(0) : "memory");
}
__device__ __forceinline__ void mbar_expect_tx_elect(uint32_t bar, uint32_t bytes) {
    asm volatile("{.reg .pred p; elect.sync _|p, 0xffffffff; @p mbarrier.arrive.expect_tx.shared::cta.b64 _, [%0], %1;}"
                 ::"r"(bar), "r"(bytes) : "memory");
}
__device__ __forceinline__ void fence_proxy_async_smem() { asm volatile("fence.proxy.async.shared::cta;" ::: "memory"); }
__device__ __forceinline__ void prefetch_l2(const void* p) { asm volatile("prefetch.global.L2 [%0];" ::"l"(p)); }
__device__ __forceinline__ uint32_t ld_relaxed(const void* p) {
    uint32_t v;
    asm volatile("ld.relaxed.gpu.global.u32 %0, [%1];" : "=r"(v) : "l"(p) : "memory");
    return v;
}
__device__ __forceinline__ uint4 ld_relaxed4(const void* p) {
    uint4 v;
    asm volatile("ld.relaxed.gpu.global.v4.u32 {%0,%1,%2,%3}, [%4];" : "=r"(v.x), "=r"(v.y), "=r"(v.z), "=r"(v.w) : "l"(p) : "memory");
    return v;
}
__device__ __forceinline__ void st_relaxed(unsigned int* p, uint32_t v) {
    asm volatile("st.relaxed.gpu.global.u32 [%0], %1;" ::"l"(p), "r"(v) : "memory");
}
__device__ __forceinline__ uint32_t tagf(float v, uint32_t par) { return (__float_as_uint(v) & ~1u) | par; }
template <int BIT = 0>
__device__ __forceinline__ uint4 wait_tags(const unsigned int* p, uint32_t par) {
    uint32_t n = 0;
#pragma unroll 1
    while (true) {
        const uint4 v = ld_relaxed4(p);
        const uint32_t m = par ? (v.x & v.y & v.z & v.w) : ~(v.x | v.y | v.z | v.w);
        if (__all_sync(0xffffffffu, (m >> BIT) & 1u)) return v;
        __nanosleep(100);
        if (++n > SPIN_LIMIT) return v;
    }
}
__device__ __forceinline__ uint32_t best_key(const uint32_t* keys, uint32_t par) {
    const uint4 k = wait_tags<15>(keys + (threadIdx.x & 31) * 4, par);
    return __reduce_max_sync(0xffffffffu, max(max(k.x, k.y), max(k.z, k.w)));
}
__device__ __forceinline__ void named_bar(int id, int n) { asm volatile("bar.sync %0, %1;" ::"r"(id), "r"(n) : "memory"); }
template <int OFF>
__device__ __forceinline__ uint4 ldg_nc_off(const void* p) {
    uint4 v;
    asm volatile("ld.global.nc.v4.u32 {%0,%1,%2,%3}, [%4+%5];" : "=r"(v.x), "=r"(v.y), "=r"(v.z), "=r"(v.w) : "l"(p), "n"(OFF));
    return v;
}
__device__ __forceinline__ void ldg_nc_if(uint4& v, const void* a, bool pred) {
    asm volatile("{.reg .pred p; setp.ne.b32 p, %5, 0; @p ld.global.nc.v4.u32 {%0,%1,%2,%3}, [%4];}"
                 : "+r"(v.x), "+r"(v.y), "+r"(v.z), "+r"(v.w) : "l"(a), "r"((int)pred) : "memory");
}
template <int OFF>
__device__ __forceinline__ void stg_off(void* p, const uint4& v) {
    asm volatile("st.global.v4.u32 [%0+%5], {%1,%2,%3,%4};" ::"l"(p), "r"(v.x), "r"(v.y), "r"(v.z), "r"(v.w), "n"(OFF) : "memory");
}
__device__ __forceinline__ void sts128(uint32_t a, const uint4& v) {
    asm volatile("st.shared.v4.u32 [%0], {%1,%2,%3,%4};" ::"r"(a), "r"(v.x), "r"(v.y), "r"(v.z), "r"(v.w) : "memory");
}
__device__ __forceinline__ uint4 lds128(uint32_t a) {
    uint4 v;
    asm volatile("ld.shared.v4.u32 {%0,%1,%2,%3}, [%4];" : "=r"(v.x), "=r"(v.y), "=r"(v.z), "=r"(v.w) : "r"(a) : "memory");
    return v;
}
__device__ __forceinline__ void lds128_if(uint4& v, uint32_t a, bool pred) {
    asm volatile("{.reg .pred p; setp.ne.b32 p, %5, 0; @p ld.shared.v4.u32 {%0,%1,%2,%3}, [%4];}"
                 : "+r"(v.x), "+r"(v.y), "+r"(v.z), "+r"(v.w) : "r"(a), "r"((int)pred) : "memory");
}
__device__ __forceinline__ uint32_t lds32(uint32_t a) {
    uint32_t v;
    asm volatile("ld.shared.u32 %0, [%1];" : "=r"(v) : "r"(a) : "memory");
    return v;
}
__device__ __forceinline__ void st_async16(uint32_t dst, uint32_t x, uint32_t y, uint32_t z, uint32_t w, uint32_t bar) {
    asm volatile("st.async.weak.shared::cluster.mbarrier::complete_tx::bytes.v4.b32 [%0], {%1,%2,%3,%4}, [%5];"
                 ::"r"(dst), "r"(x), "r"(y), "r"(z), "r"(w), "r"(bar) : "memory");
}
__device__ __forceinline__ int sel(int a, int b, bool p) {
    int r;
    asm("{.reg .pred q; setp.ne.b32 q, %3, 0; selp.b32 %0, %1, %2, q;}" : "=r"(r) : "r"(a), "r"(b), "r"((int)p));
    return r;
}
__device__ __forceinline__ float selpf(float a, float b, bool p) {
    float r;
    asm("{.reg .pred q; setp.ne.b32 q, %3, 0; selp.f32 %0, %1, %2, q;}" : "=f"(r) : "f"(a), "f"(b), "r"((int)p));
    return r;
}
template <int N, int MASK, int SZ>
__device__ __forceinline__ void halve(float (&a)[SZ]) {
    const bool up = threadIdx.x & MASK;
#pragma unroll
    for (int j = 0; j < N; j++) a[j] = selpf(a[N + j], a[j], up) + __shfl_xor_sync(0xffffffffu, selpf(a[j], a[N + j], up), MASK);
}
__device__ __forceinline__ float bflo(uint32_t u) { return __uint_as_float(u << 16); }
__device__ __forceinline__ float bfhi(uint32_t u) { return __uint_as_float(u & 0xffff0000u); }
__device__ __forceinline__ uint32_t pack_bf16(float lo, float hi) {
    uint32_t r;
    asm("cvt.rn.bf16x2.f32 %0, %1, %2;" : "=r"(r) : "f"(hi), "f"(lo));
    return r;
}
__device__ __forceinline__ uint32_t hmul2_bf16(uint32_t a, uint32_t b) {
    uint32_t r;
    asm("mul.rn.bf16x2 %0, %1, %2;" : "=r"(r) : "r"(a), "r"(b));
    return r;
}
__device__ __forceinline__ float sigmoidf_(float v) { return 1.0f / (1.0f + __expf(-v)); }
__device__ __forceinline__ void wg_fence() { asm volatile("wgmma.fence.sync.aligned;" ::: "memory"); }
__device__ __forceinline__ void wg_commit() { asm volatile("wgmma.commit_group.sync.aligned;" ::: "memory"); }
template <int N> __device__ __forceinline__ void wg_wait() { asm volatile("wgmma.wait_group.sync.aligned %0;" ::"n"(N) : "memory"); }
__device__ __forceinline__ uint64_t desc_lo(uint32_t lo) { return (uint64_t)lo | (0x40000040ull << 32); }
template <int LO, int HI, int N>
__device__ __forceinline__ void fence_regs(float (&d)[N]) {
#pragma unroll
    for (int i = LO; i < HI; i++) asm volatile("" : "+f"(d[i])::"memory");
}
template <int LO, int HI, int N>
__device__ __forceinline__ void keep_regs(uint4 (&f)[N]) {
#pragma unroll
    for (int i = LO; i < HI; i++) asm volatile("" ::"r"(f[i].x), "r"(f[i].y), "r"(f[i].z), "r"(f[i].w) : "memory");
}
template <int TB = 1>
__device__ __forceinline__ void wgmma128(float (&d)[64], uint64_t da, uint64_t db, int scaleD) {
    asm volatile(
        "{ .reg .pred p; setp.ne.b32 p, %66, 0;\n"
        "wgmma.mma_async.sync.aligned.m64n128k16.f32.bf16.bf16 "
        "{%0,%1,%2,%3,%4,%5,%6,%7,%8,%9,%10,%11,%12,%13,%14,%15,%16,%17,%18,%19,%20,%21,%22,%23,%24,%25,%26,%27,%28,%29,%30,%31,"
        "%32,%33,%34,%35,%36,%37,%38,%39,%40,%41,%42,%43,%44,%45,%46,%47,%48,%49,%50,%51,%52,%53,%54,%55,%56,%57,%58,%59,%60,%61,%62,%63}, "
        "%64, %65, p, 1, 1, 0, %67;\n}"
        : "+f"(d[0]), "+f"(d[1]), "+f"(d[2]), "+f"(d[3]), "+f"(d[4]), "+f"(d[5]), "+f"(d[6]), "+f"(d[7]),
          "+f"(d[8]), "+f"(d[9]), "+f"(d[10]), "+f"(d[11]), "+f"(d[12]), "+f"(d[13]), "+f"(d[14]), "+f"(d[15]),
          "+f"(d[16]), "+f"(d[17]), "+f"(d[18]), "+f"(d[19]), "+f"(d[20]), "+f"(d[21]), "+f"(d[22]), "+f"(d[23]),
          "+f"(d[24]), "+f"(d[25]), "+f"(d[26]), "+f"(d[27]), "+f"(d[28]), "+f"(d[29]), "+f"(d[30]), "+f"(d[31]),
          "+f"(d[32]), "+f"(d[33]), "+f"(d[34]), "+f"(d[35]), "+f"(d[36]), "+f"(d[37]), "+f"(d[38]), "+f"(d[39]),
          "+f"(d[40]), "+f"(d[41]), "+f"(d[42]), "+f"(d[43]), "+f"(d[44]), "+f"(d[45]), "+f"(d[46]), "+f"(d[47]),
          "+f"(d[48]), "+f"(d[49]), "+f"(d[50]), "+f"(d[51]), "+f"(d[52]), "+f"(d[53]), "+f"(d[54]), "+f"(d[55]),
          "+f"(d[56]), "+f"(d[57]), "+f"(d[58]), "+f"(d[59]), "+f"(d[60]), "+f"(d[61]), "+f"(d[62]), "+f"(d[63])
        : "l"(da), "l"(db), "r"(scaleD), "n"(TB));
}
__device__ __forceinline__ void wgmma128rs(float (&d)[64], const uint4& a, uint64_t db, int scaleD) {
    asm volatile(
        "{ .reg .pred p; setp.ne.b32 p, %69, 0;\n"
        "wgmma.mma_async.sync.aligned.m64n128k16.f32.bf16.bf16 "
        "{%0,%1,%2,%3,%4,%5,%6,%7,%8,%9,%10,%11,%12,%13,%14,%15,%16,%17,%18,%19,%20,%21,%22,%23,%24,%25,%26,%27,%28,%29,%30,%31,"
        "%32,%33,%34,%35,%36,%37,%38,%39,%40,%41,%42,%43,%44,%45,%46,%47,%48,%49,%50,%51,%52,%53,%54,%55,%56,%57,%58,%59,%60,%61,%62,%63}, "
        "{%64,%65,%66,%67}, %68, p, 1, 1, 0;\n}"
        : "+f"(d[0]), "+f"(d[1]), "+f"(d[2]), "+f"(d[3]), "+f"(d[4]), "+f"(d[5]), "+f"(d[6]), "+f"(d[7]),
          "+f"(d[8]), "+f"(d[9]), "+f"(d[10]), "+f"(d[11]), "+f"(d[12]), "+f"(d[13]), "+f"(d[14]), "+f"(d[15]),
          "+f"(d[16]), "+f"(d[17]), "+f"(d[18]), "+f"(d[19]), "+f"(d[20]), "+f"(d[21]), "+f"(d[22]), "+f"(d[23]),
          "+f"(d[24]), "+f"(d[25]), "+f"(d[26]), "+f"(d[27]), "+f"(d[28]), "+f"(d[29]), "+f"(d[30]), "+f"(d[31]),
          "+f"(d[32]), "+f"(d[33]), "+f"(d[34]), "+f"(d[35]), "+f"(d[36]), "+f"(d[37]), "+f"(d[38]), "+f"(d[39]),
          "+f"(d[40]), "+f"(d[41]), "+f"(d[42]), "+f"(d[43]), "+f"(d[44]), "+f"(d[45]), "+f"(d[46]), "+f"(d[47]),
          "+f"(d[48]), "+f"(d[49]), "+f"(d[50]), "+f"(d[51]), "+f"(d[52]), "+f"(d[53]), "+f"(d[54]), "+f"(d[55]),
          "+f"(d[56]), "+f"(d[57]), "+f"(d[58]), "+f"(d[59]), "+f"(d[60]), "+f"(d[61]), "+f"(d[62]), "+f"(d[63])
        : "r"(a.x), "r"(a.y), "r"(a.z), "r"(a.w), "l"(db), "r"(scaleD));
}
__device__ __forceinline__ uint32_t clk() { uint64_t c; asm volatile("mov.u64 %0, %%clock64;" : "=l"(c)::"memory"); return (uint32_t)c; }
__device__ __forceinline__ uint32_t gtime() { uint64_t t; asm volatile("mov.u64 %0, %%globaltimer;" : "=l"(t)::"memory"); return (uint32_t)t; }
__device__ __forceinline__ void until(uint32_t t) { while (t - clk() < 0x8000u) {} }
__device__ __forceinline__ void nap_until(uint32_t t) { while (t - clk() < 0x8000u) __nanosleep(20); }
__device__ __forceinline__ uint4 scale_add(float s, const float (&a)[64], int o, const uint4& w) {
    return make_uint4(pack_bf16(fmaf(s, a[o], bflo(w.x)), fmaf(s, a[o + 1], bfhi(w.x))), pack_bf16(fmaf(s, a[o + 4], bflo(w.y)), fmaf(s, a[o + 5], bfhi(w.y))),
                      pack_bf16(fmaf(s, a[o + 8], bflo(w.z)), fmaf(s, a[o + 9], bfhi(w.z))), pack_bf16(fmaf(s, a[o + 12], bflo(w.w)), fmaf(s, a[o + 13], bfhi(w.w))));
}

__device__ __forceinline__ uint32_t router_key(float score, int row) {
    const float r = score + 0.0f;
    uint32_t u = pack_bf16(r, 0.f) & 0xffffu;
    u = (u & 0x8000u) ? (~u & 0xffffu) : (u | 0x8000u);
    if (r != r) u = 0;
    return (u << 16) | (uint32_t)(0x7fff - row);
}

#define g_ab g_scr.frag
#define g_fb_h ((float*)g_scr.part)
#define g_fb_upd (g_fb_h + 2048)
#define g_fb_gate (g_fb_h + 4096)
#define g_fb_keys (g_scr.part + 8192)
__global__ void fb_hidden(const bf16* x, const bf16* dre, const bf16* dim, const bf16* gw, const bf16* wr) {
    __shared__ float xs[D_];
    const int s = blockIdx.x, t = threadIdx.x;
    xs[t] = __bfloat162float(x[s * D_ + t]);
    __syncthreads();
    float a = 0.f, b = 0.f;
    for (int d = 0; d < D_; d++) { a = fmaf(xs[d], __bfloat162float(dre[t * D_ + d]), a); b = fmaf(xs[d], __bfloat162float(dim[t * D_ + d]), b); }
    ((bf16*)g_ab)[s * 1024 + t] = __float2bfloat16(a);
    ((bf16*)g_ab)[s * 1024 + 512 + t] = __float2bfloat16(b);
    if (t == 0) {
        float u = 0.f, v = 0.f;
        for (int d = 0; d < D_; d++) { u = fmaf(xs[d], __bfloat162float(gw[d]), u); v = fmaf(xs[d], __bfloat162float(wr[d]), v); }
        g_fb_gate[s] = sigmoidf_(u);
        g_fb_keys[s] = router_key(v, s);
    }
}
__device__ uint32_t fb_best() {
    uint32_t k = 0;
    for (int i = 0; i < S_; i++) k = max(k, g_fb_keys[i]);
    return k;
}
__global__ void fb_ffn1(const bf16* x, const bf16* wg, const bf16* wu) {
    const int f = blockIdx.x * blockDim.x + threadIdx.x, idx = 0x7fff - (int)(fb_best() & 0x7fffu);
    float a = 0.f, b = 0.f;
    for (int d = 0; d < D_; d++) {
        const float xv = __bfloat162float(x[idx * D_ + d]);
        a = fmaf(xv, __bfloat162float(wg[d * F_ + f]), a); b = fmaf(xv, __bfloat162float(wu[d * F_ + f]), b);
    }
    g_fb_h[f] = a * sigmoidf_(a) * b;
}
__global__ void fb_ffn2(const bf16* wd) {
    const int e = blockIdx.x * blockDim.x + threadIdx.x;
    const uint32_t u = fb_best() >> 16, rb = (u & 0x8000u) ? (u & 0x7fffu) : (~u & 0xffffu);
    float a = 0.f;
    for (int f = 0; f < F_; f++) a = fmaf(g_fb_h[f], __bfloat162float(wd[f * D_ + e]), a);
    g_fb_upd[e] = a * sigmoidf_(__uint_as_float(rb << 16));
}
__global__ void fb_seq(const bf16* x, const bf16* cre, const bf16* cim, bf16* out) {
    __shared__ float c[2][S_];
    __shared__ int idx;
    const int t = blockIdx.x, e = threadIdx.x;
    for (int i = e; i < S_; i += D_) { c[0][i] = __bfloat162float(cre[t * S_ + i]); c[1][i] = __bfloat162float(cim[t * S_ + i]); }
    if (e == 0) idx = 0x7fff - (int)(fb_best() & 0x7fffu);
    __syncthreads();
    float y = 0.f;
    for (int s = 0; s < S_; s++)
        y += c[0][s] * __bfloat162float(((const bf16*)g_ab)[s * 1024 + e]) - c[1][s] * __bfloat162float(((const bf16*)g_ab)[s * 1024 + 512 + e]);
    const float g = g_fb_gate[t];
    out[t * D_ + e] = __float2bfloat16(g * y + (1.f - g) * (__bfloat162float(x[t * D_ + e]) + (t == idx ? g_fb_upd[e] : 0.f)));
}

__device__ __forceinline__ void spare_job(const Params& p, Scratch* g, unsigned char* smem, int sp, uint32_t tstart) {
    const int tid = threadIdx.x, warp = tid >> 5, lane = tid & 31;
    if (warp >= 8) {
#pragma unroll 1
        for (int i = 0; i < 16; i++) {
            nap_until(tstart + PFD_T0 + i * (PFD_DT / 2));
            prefetch_l2((const char*)((sp & 2) ? p.dim : p.dre) + (sp & 1) * 262144 + i * 16384 + (tid - 256) * 128);
        }
        return;
    }
    nap_until(tstart + SUM_T0 - 2000);
    const uint32_t e1 = ld_relaxed(g->epoch + NCTA + sp) + 1u, par = e1 & 1u;
    const uint32_t u = best_key(g->keys + warp * NCTA, par) >> 16;
    const float rs = sigmoidf_(__uint_as_float(((u & 0x8000u) ? (u & 0x7fffu) : (~u & 0xffffu)) << 16));
    nap_until(tstart + SUM_T0);
    uint32_t n = 0;
#pragma unroll 1
    while ((int)(ld_relaxed(g->phint + (sp * 8 + warp) * 8) - e1 * 14u) < 0) {
        __nanosleep(40);
        if (++n > SPIN_LIMIT) break;
    }
    const unsigned int* src = g->part + warp * 7 * D_ + sp * 128 + lane * 4;
    uint4 v[7];
#pragma unroll 1
    while (true) {
        uint32_t bad = 0;
#pragma unroll
        for (int i = 0; i < 7; i++) v[i] = ld_relaxed4(src + i * D_);
#pragma unroll
        for (int i = 0; i < 7; i++) bad |= (v[i].x ^ par) | (v[i].y ^ par) | (v[i].z ^ par) | (v[i].w ^ par);
        if (!__any_sync(0xffffffffu, bad & 1u)) break;
        if (++n > SPIN_LIMIT) break;
    }
    float4 s = make_float4(0.f, 0.f, 0.f, 0.f);
#pragma unroll
    for (int i = 0; i < 7; i++) {
        s.x += __uint_as_float(v[i].x); s.y += __uint_as_float(v[i].y);
        s.z += __uint_as_float(v[i].z); s.w += __uint_as_float(v[i].w);
    }
    float* acc = (float*)smem;
    *(float4*)&acc[warp * 128 + lane * 4] = s;
    named_bar(1, 256);
    if (tid < 128) {
        float t = 0.f;
#pragma unroll
        for (int i = 0; i < 8; i++) t += acc[i * 128 + tid];
        st_relaxed(&g->upd[sp * 128 + tid], tagf(t * rs, par));
        if (tid == 0) st_relaxed(g->epoch + NCTA + sp, e1);
    }
}

__device__ __forceinline__ int ffn_pair(int role) { return role - __popcll(NOFFN_MASK & ((1ull << role) - 1)); }
__device__ __forceinline__ int other(int i, int tn) { return i + (i >= tn); }
__device__ __forceinline__ int dcol(int p, int tn) { return p < 2 ? tn * 128 + p * 64 : other((p - 2) % 3, tn) * 128 + (p >= 5 ? 64 : 0); }

template <int H>
__device__ __forceinline__ void fetch_job(const Params& p, Scratch* g, unsigned char* smem, uint32_t sb, int cta, int i, uint32_t par) {
    const int lane = threadIdx.x & 31, comp = cta & 1;
    const int j = other(i, (cta >> 1) & 3), src = (cta & ~6) + 2 * j;
    const int slot = i == 0 ? 29 % NST : i - 1;
    const uint32_t land = sb + B_LAND + 8 * (3 * H + i);
    uint32_t ph = 0, th;
    mbar_expect_tx_elect(land, 8192);
    if (H == 0) {
        mbar_wait(sb + B_S0, 0);
        const uint32_t t0 = clk();
        if (i == 0) {
            mbar_wait(sb + B_FULL + 8 * (31 % NST), (31 / NST) & 1);
            const uint32_t t1 = t0 + max(clk() - t0, 180u) - 180u;
            asm volatile("{.reg .pred p; .reg .b64 t; setp.eq.b32 p, %3, 0; mov.b64 t, {%1, %2}; @p st.relaxed.gpu.global.b64 [%0], t;}"
                         ::"l"(g->stamp + cta * 32), "r"((t1 & ~1u) | par), "r"(gtime()), "r"(lane) : "memory");
        }
        until(t0 + SDEL);
        uint32_t gt;
#pragma unroll 1
        for (uint32_t n = 0; n < SPIN_LIMIT; n++) {
            asm volatile("{.reg .b64 t; ld.relaxed.gpu.global.b64 t, [%2]; mov.b64 {%0,%1}, t;}" : "=r"(th), "=r"(gt) : "l"(g->stamp + src * 32) : "memory");
            if (!__any_sync(0xffffffffu, (th ^ par) & 1u)) break;
        }
        const uint32_t ns = min(gtime() - gt, 4096u), now = clk();
        if (now - th >= 8192u) th = now - (ns + (ns >> 1) + (ns >> 4));
        th += SG * j;
        if (lane == 0) { *(volatile uint32_t*)(smem + M_TH + 4 * i) = th; mbar_arrive(sb + B_TH + 8 * i); }
        __syncwarp();
    } else {
        mbar_wait(sb + B_TH + 8 * i, 0);
        th = lds32(sb + M_TH + 4 * i);
    }
    mbar_wait(sb + B_EA, 0);
#pragma unroll 1
    for (int c = 0; c < 2; c++) {
        const uint32_t dst = sb + slot * 16384 + (c ? NST * 16384 + H * 8192 : (comp ^ H) * 8192);
        if (c != H) mbar_wait(sb + B_EMPTY + 8 * slot, i != 0);
        until(th + (c ? (H ? L_RD1 : L_RD0) : (H ? E_RD1 : E_RD0)));
#pragma unroll 1
        for (uint32_t r = 0; r < SPIN_LIMIT; r++) {
            tma2d_elect(dst, &p.mF, 0, (src * 2 + (comp ^ c)) * 128 + H * 64, land);
            mbar_wait(land, ph);
            ph ^= 1;
            const uint32_t a = dst + (lane >> 2) * 132 + (lane & 3) * 32;
            uint32_t v[8], m0 = 0, m1 = ~0u;
#pragma unroll
            for (int k = 0; k < 8; k++) v[k] = lds32(a + k * 1024);
#pragma unroll
            for (int k = 0; k < 8; k++) { m0 |= v[k]; m1 &= v[k]; }
            if (__all_sync(0xffffffffu, (par ? m1 : ~m0) & 1u)) break;
            mbar_expect_tx_elect(land, 8192);
        }
        mbar_arrive_if(sb + B_VAL + 8 * (6 * c + 3 * H + i), lane == 0);
        if (c == 0) mbar_expect_tx_elect(land, 8192);
    }
}

__global__ void __cluster_dims__(2, 1, 1) __launch_bounds__(NTHREADS, 1)
fused_kernel(const char* pc0, const char* pc1, const char* px, char* pout, Scratch* g, const __grid_constant__ Params p) {
    extern __shared__ __align__(1024) unsigned char smem[];
    const uint32_t sb = smem_u32(smem);
    const int tid = threadIdx.x, warp = tid >> 5, lane = tid & 31;
    const int rank = blockIdx.x & 1;
    {
        const uint32_t b = blockIdx.x & 127;
        const char* u0 = (rank ? pc1 : pc0) + (b >> 1) * (32 * S_ * 2);
        const char* u1 = px + b * 512 - 4096;
        asm volatile("{.reg .pred p, q; .reg .b64 a; .reg .b32 t; setp.lt.u32 p, %2, 32; mad.wide.u32 a, %2, 4096, %0; @p prefetch.global.L2 [a];"
                     " sub.u32 t, %2, 32; setp.lt.u32 q, t, 4; mad.wide.u32 a, %2, 128, %1; @q prefetch.global.L2 [a];}" ::"l"(u0), "l"(u1), "r"(tid));
    }
    const uint32_t tstart = clk();
    uint32_t smid;
    asm volatile("mov.u32 %0, %%smid;" : "=r"(smid));
    const int u = smid >> 1, v7 = ((u - 32) * 37) >> 8;
    const int tn = sel(u >> 3, sel(v7, u - 62, u < 60), u < 32);
    const int tm = sel(u & 7, sel(u - 23 - 7 * v7, 8, u < 60), u < 32);
    const bool spare = tn < 0;
    const int role = tm * 4 + tn, cta = role * 2 + rank;
    const int comp = rank;
    const CUtensorMap* mC = comp ? &p.mCim : &p.mCre;
#define ARM(j) do { mbar_init(sb + B_FULL + 8 * (j), 1); mbar_expect_tx(sb + B_FULL + 8 * (j), 32768); } while (0)
#define FIRST(j) do { tma2d(sb + a_addr(j), mC, (j) * 64, tm * 128, sb + B_FULL + 8 * (j));                        \
                      tma3d(sb + b_addr(j), &p.mX2, (j) * 64, tn * 2, sb + B_FULL + 8 * (j)); } while (0)
    if (tid == 384) {
        ARM(0);
        if (!spare) FIRST(0);
    }
    const int wu = __shfl_sync(0xffffffffu, warp, 0);
    if (wu < 12) {
        if (lane == 0) {
            mbar_init(sb + B_EMPTY + 8 * wu, wu < 7 ? 4 : 1);
#pragma unroll
            for (int i = 12; i < NBAR; i += 12) if (i + 12 <= NBAR || wu < NBAR - i) mbar_init(sb + B_EMPTY + 8 * (i + wu), 1);
            if (wu >= 7 && wu < 10) mbar_expect_tx(sb + B_EMPTY + 8 * wu, wu < 9 ? 8192 : 256);
        }
        asm volatile("fence.mbarrier_init.release.cluster;" ::: "memory");
        __syncwarp();
        asm volatile("barrier.cluster.arrive.relaxed.aligned;" ::: "memory");
        if (spare) {
            spare_job(p, g, smem, smid & 3, tstart);
        } else if (wu >= 8) {
            asm volatile("setmaxnreg.dec.sync.aligned.u32 " STR(RS_) ";");
            asm volatile("barrier.cluster.wait.acquire.aligned;" ::: "memory");
            const int t = tid - 256, w = wu - 8, fr = ffn_pair(role);
            const bool ffn = !((NOFFN_MASK >> role) & 1);
            nap_until(tstart + SIDE_T0);
            const uint4 gw0 = ldg_nc_off<0>(p.gate_w + lane * 8), gw1 = ldg_nc_off<512>(p.gate_w + lane * 8);
            const uint4 rw0 = ldg_nc_off<0>(p.w_r + lane * 8), rw1 = ldg_nc_off<512>(p.w_r + lane * 8);
            const uint32_t par = ~ld_relaxed(g->epoch + cta) & 1u;
            nap_until(tstart + ROUTER_T0 + (2 * w + rank) * ROUTER_DT);
            {
                const int row0 = cta * 16 + w * 4;
                const char* xp = px + (uint32_t)row0 * (D_ * 2) + lane * 16;
                uint4 xa[4], xb[4];
                xa[0] = ldg_nc_off<0>(xp);    xb[0] = ldg_nc_off<512>(xp);  xa[1] = ldg_nc_off<1024>(xp); xb[1] = ldg_nc_off<1536>(xp);
                xa[2] = ldg_nc_off<2048>(xp); xb[2] = ldg_nc_off<2560>(xp); xa[3] = ldg_nc_off<3072>(xp); xb[3] = ldg_nc_off<3584>(xp);
                float a[8];
#pragma unroll
                for (int i = 0; i < 4; i++) {
                    const uint32_t xv[8] = {xa[i].x, xa[i].y, xa[i].z, xa[i].w, xb[i].x, xb[i].y, xb[i].z, xb[i].w};
                    const uint32_t gv[8] = {gw0.x, gw0.y, gw0.z, gw0.w, gw1.x, gw1.y, gw1.z, gw1.w};
                    const uint32_t rv[8] = {rw0.x, rw0.y, rw0.z, rw0.w, rw1.x, rw1.y, rw1.z, rw1.w};
                    float uu = 0.f, vv = 0.f;
#pragma unroll
                    for (int j = 0; j < 8; j++) {
                        uu = fmaf(bflo(xv[j]), bflo(gv[j]), uu); uu = fmaf(bfhi(xv[j]), bfhi(gv[j]), uu);
                        vv = fmaf(bflo(xv[j]), bflo(rv[j]), vv); vv = fmaf(bfhi(xv[j]), bfhi(rv[j]), vv);
                    }
                    a[i] = uu; a[4 + i] = vv;
                }
                halve<4, 16>(a); halve<2, 8>(a); halve<1, 4>(a);
                {
                    const float b1 = __shfl_xor_sync(0xffffffffu, a[0], 1), b2 = __shfl_xor_sync(0xffffffffu, a[0], 2),
                                b3 = __shfl_xor_sync(0xffffffffu, a[0], 3);
                    a[0] = (a[0] + b1) + (b2 + b3);
                }
                const int row = row0 + ((lane >> 2) & 3);
                const uint32_t best = __reduce_max_sync(0xffffffffu, lane >= 16 && (lane & 3) == 0 ? router_key(a[0], row) : 0u);
                if (lane <= 16 && (lane & 3) == 0)
                    *(volatile uint32_t*)(smem + M_RED + (lane < 16 ? w * 16 + lane : 64 + w * 4)) = lane < 16 ? tagf(sigmoidf_(a[0]), par) : best;
                named_bar(1, 128);
                if (t < 8) {
                    const uint4 k = lds128(sb + M_RED + 64);
                    asm volatile("{.reg .b32 old; atom.relaxed.gpu.global.exch.b32 old, [%0], %1;}"
                                 ::"l"(g->keys + t * NCTA + cta), "r"(max(max(k.x, k.y), max(k.z, k.w)) | (par << 15)) : "memory");
                }
                if (w == 1 && lane < 16) st_relaxed(g->gate + cta * 16 + lane, lds32(sb + M_RED + lane * 4));
            }
            uint32_t vd[32];
            if (ffn) {
                mbar_wait(sb + B_FFN + 24, 0);
#pragma unroll
                for (int j = 0; j < 32; j++) vd[j] = lds32(sb + R6 + ((j >> 3) & 1) * 16384 + (2 + (j >> 4)) * 4096 + (j & 7) * 512 + t * 4);
                mbar_arrive_warp(sb + B_VD);
            }
            mbar_wait(sb + B_GATE, 0);
            const int idx = 0x7fff - (int)(*(volatile uint32_t*)(smem + M_KEY) & 0x7fffu);
            if (ffn) {
                float a[16];
#pragma unroll
                for (int i = 0; i < 16; i++) a[i] = 0.f;
#pragma unroll 1
                for (int qu = 0; qu < 4; qu++) {
                    mbar_wait(sb + B_FFN + 8 * qu, qu == 3);
#pragma unroll
                    for (int i = 2 * qu; i < 2 * qu + 2; i++) {
                        const float xs = __bfloat162float(((const bf16*)(smem + M_UPD))[32 * i + (t >> 2)]);
                        const uint4 vg = lds128(sb + R6 + i * 2048 + t * 16);
                        const uint4 vu = lds128(sb + R6 + 16384 + i * 2048 + t * 16);
                        const uint32_t g4[4] = {vg.x, vg.y, vg.z, vg.w};
                        const uint32_t u4[4] = {vu.x, vu.y, vu.z, vu.w};
#pragma unroll
                        for (int j = 0; j < 4; j++) {
                            a[2 * j] = fmaf(xs, bflo(g4[j]), a[2 * j]);         a[2 * j + 1] = fmaf(xs, bfhi(g4[j]), a[2 * j + 1]);
                            a[8 + 2 * j] = fmaf(xs, bflo(u4[j]), a[8 + 2 * j]); a[9 + 2 * j] = fmaf(xs, bfhi(u4[j]), a[9 + 2 * j]);
                        }
                    }
                }
                named_bar(1, 128);
                mbar_arrive_if(sb + B_R6, t == 0);
                halve<8, 16>(a); halve<4, 8>(a); halve<2, 4>(a);
                float* red = (float*)(smem + M_UPD);
                *(float2*)&red[w * 64 + (lane >> 4) * 32 + (lane & 3) * 8 + ((lane >> 2) & 3) * 2] = make_float2(a[0], a[1]);
                named_bar(1, 128);
                const float sg = red[lane] + red[64 + lane] + red[128 + lane] + red[192 + lane];
                const float su = red[32 + lane] + red[96 + lane] + red[160 + lane] + red[224 + lane];
                if (w < 2) {
                    asm volatile("st.async.weak.shared::cluster.mbarrier::complete_tx::bytes.f32 [%0], %1, [%2];"
                                 ::"r"(mapa(sb + M_HX + t * 4, rank ^ 1)), "f"(w ? su : sg), "r"(mapa(sb + B_HX, rank ^ 1)) : "memory");
                }
                named_bar(1, 128);
                mbar_wait(sb + B_HX, 0);
                const float pg = ((const float*)(smem + M_HX))[lane], pu = ((const float*)(smem + M_HX))[32 + lane];
                const float gs = sg + pg, us = su + pu;
                float* hrow = red + w * 32;
                hrow[lane] = gs * sigmoidf_(gs) * us;
                __syncwarp();
                float o0 = 0.f, o1 = 0.f;
#pragma unroll
                for (int j4 = 0; j4 < 8; j4++) {
                    const float4 hv = *(const float4*)&hrow[j4 * 4];
                    o0 = fmaf(hv.x, bflo(vd[4 * j4]), o0);     o1 = fmaf(hv.x, bfhi(vd[4 * j4]), o1);
                    o0 = fmaf(hv.y, bflo(vd[4 * j4 + 1]), o0); o1 = fmaf(hv.y, bfhi(vd[4 * j4 + 1]), o1);
                    o0 = fmaf(hv.z, bflo(vd[4 * j4 + 2]), o0); o1 = fmaf(hv.z, bfhi(vd[4 * j4 + 2]), o1);
                    o0 = fmaf(hv.w, bflo(vd[4 * j4 + 3]), o0); o1 = fmaf(hv.w, bfhi(vd[4 * j4 + 3]), o1);
                }
                asm volatile("st.relaxed.gpu.global.v2.u32 [%0], {%1,%2};" ::"l"(&g->part[fr * D_ + rank * 256 + t * 2]),
                             "r"(tagf(o0, par)), "r"(tagf(o1, par)) : "memory");
                if (lane == 0) asm volatile("red.relaxed.gpu.global.add.u32 [%0], 1;" ::"l"(g->phint + ((rank * 2 + (w >> 1)) * 8 + fr / 7) * 8) : "memory");
            }
            if (!ffn) mbar_arrive_if(sb + B_R6, t == 0);
            if (w < 3) {
                fetch_job<1>(p, g, smem, sb, cta, w, par);
            } else {
                if (lds32(sb + M_ROLE) != (uint32_t)role) __trap();
                if ((idx >> 6) == 2 * tm + comp) {
                    const uint4 u4 = wait_tags(g->upd + tn * 128 + lane * 4, par);
                    const float og = 1.f - ((const float*)(smem + M_G))[idx & 127];
                    *(float4*)(smem + M_RED + lane * 16) = make_float4(og * __uint_as_float(u4.x), og * __uint_as_float(u4.y),
                                                                       og * __uint_as_float(u4.z), og * __uint_as_float(u4.w));
                    mbar_arrive_warp(sb + B_SIDE);
                }
            }
        } else {
            const int wg = wu >> 2;
            const uint32_t sbd = (sb & 0x3FFFF) >> 4;
            const bool lead = (tid & 127) == 0;
            const bool early = wg == comp;
            const int q = lane & 3;
            const int r0 = (warp & 3) * 16 + (lane >> 2);
            float acc[64];
            const uint32_t da0 = sbd + 0x10000 + wg * 512, db0 = sbd + 0x2000000, dd0 = sbd + 0x10000;
            const uint32_t rE = mapa(sb + B_EMPTY, rank ^ 1);
#define WAITFULL(s) mbar_wait(sb + B_FULL + 8 * ((s) % NST), ((s) / NST) & 1)
#define TESTFULL(s) mbar_test(sb + B_FULL + 8 * ((s) % NST), ((s) / NST) & 1)
#define WAITD(pos) do { if ((pos) >= 4) mbar_wait(sb + B_DL + 8 * ((pos) - 4), 0); else if ((pos) >= 2) mbar_wait(sb + B_D6, 0); else WAITFULL(32); } while (0)
#define MMA_A(s, kk) wgmma128(acc, desc_lo(da0 + a_addr(s) / 16 + (kk) * 2), desc_lo(db0 + b_addr(s) / 16 + (kk) * 128), 1)
            asm volatile("setmaxnreg.inc.sync.aligned.u32 " STR(RC) ";");
            asm volatile("barrier.cluster.wait.acquire.aligned;" ::: "memory");
            WAITFULL(0);
            wg_fence();
#pragma unroll
            for (int kk = 0; kk < 4; kk++) wgmma128(acc, desc_lo(da0 + kk * 2), desc_lo(db0 + b_addr(0) / 16 + kk * 128), kk != 0);
            wg_commit();
            int slot = 1, ph = 0, pslot = 0;
            const uint32_t ooff = (uint32_t)((tm * 128 + wg * 64 + r0) * D_ + tn * 128 + q * 8) * 2u;
            uint32_t* fout = g->frag + (cta * 2 + wg) * 4096 + (warp & 3) * 128 + lane;
            uint32_t tagm[4];
#pragma unroll
            for (int c = 0; c < 4; c++) tagm[c] = (lane & 7) == (warp & 1) * 4 + c;
            const char* xp = px + ooff;
            asm volatile("" : "+r"(tagm[0]), "+r"(tagm[1]), "+r"(tagm[2]), "+r"(tagm[3]), "+l"(xp), "+l"(fout));
            uint4 w[8];
#pragma unroll
            for (int i = 0; i < 8; i++) w[i] = make_uint4(0, 0, 0, 0);
#pragma unroll
            for (int part = 0; part <= XN; part++) {
                if (part) {
#pragma unroll
                    for (int i = (part - 1) * 8 / XN; i < part * 8 / XN; i++) ldg_nc_if(w[i], xp + (i & 1) * 8192 + (i >> 1) * 64, early);
                }
#pragma unroll 1
                for (int step = part ? XLD + (part - 1) * XD : 1; step < (part < XN ? XLD + part * XD : SP0); step++) {
                    mbar_wait(sb + B_FULL + 8 * slot, ph);
                    const uint32_t a = da0 + slot * 1024, b = db0 + b_addr(0) / 16 + slot * 1024;
                    wg_fence();
                    wgmma128(acc, desc_lo(a), desc_lo(b), 1);
                    wg_commit();
                    wg_wait<1>();
                    mbar_arrive_if(sb + B_EMPTY + 8 * pslot, lead);
                    mbar_arrive_cluster_if(rE + 8 * pslot, lead);
                    pslot = slot;
                    if (++slot == NST) { slot = 0; ph ^= 1; }
                    wg_fence();
#pragma unroll
                    for (int kk = 1; kk < 4; kk++) wgmma128(acc, desc_lo(a + kk * 2), desc_lo(b + kk * 128), 1);
                    wg_commit();
                }
            }
            uint32_t par;
            float g0, g1;
#define GATES() do { par = lds32(sb + M_PAR); g0 = __uint_as_float(lds32(sb + M_G + (wg * 64 + r0) * 4)); g1 = __uint_as_float(lds32(sb + M_G + (wg * 64 + r0 + 8) * 4)); } while (0)
            if (early) {
                WAITFULL(SP0);
                wg_fence();
                MMA_A(SP0, 0); MMA_A(SP0, 1);
                wg_commit();
                wg_wait<1>();
                mbar_arrive_n_if<2>(sb + B_EMPTY + 8 * ((SP0 - 1) % NST), lead);
                bool ok = TESTFULL(SP0 + 1);
                MMA_A(SP0, 2); MMA_A(SP0, 3);
                wg_commit();
#pragma unroll
                for (int s = SP0 + 1; s < 32; s++) {
                    if (!ok) { WAITFULL(s); if (s == 29) mbar_wait(sb + B_GATE, 0); }
                    wg_fence();
                    MMA_A(s, 0); MMA_A(s, 1);
                    if (s == 29) GATES();
                    if (s >= 30) { wg_commit(); wg_wait<1>(); mbar_arrive_if(sb + (s == 30 ? B_S0 : B_S1), lead); wg_fence(); }
                    if (s < 31) ok = TESTFULL(s + 1) & (s != 28 || mbar_test(sb + B_GATE, 0));
                    MMA_A(s, 2); MMA_A(s, 3);
                    wg_commit();
                }
                wg_wait<0>();
                mbar_arrive_if(sb + B_EA, lead);
            } else {
                wg_wait<0>();
                mbar_arrive_n_if<2>(sb + B_EMPTY + 8 * ((SP0 - 1) % NST), lead);
#pragma unroll
                for (int s = SP0; s < 32; s++) WAITFULL(s);
                mbar_wait(sb + B_GATE, 0);
                GATES();
                mbar_wait(sb + B_S1, 0);
                wg_fence();
#pragma unroll
                for (int s = SP0; s < 32; s++) {
                    MMA_A(s, 0); MMA_A(s, 1);
                    if (s > SP0) {
                        wg_commit();
                        wg_wait<1>();
                        mbar_arrive_n_if<4>(sb + B_EMPTY + 8 * ((s - 1) % NST), lead);
                        if (s == 31) mbar_arrive_if(sb + B_S3, lead);
                        if (s == 30) WAITD(0);
                        wg_fence();
                    }
                    MMA_A(s, 2); MMA_A(s, 3);
                    wg_commit();
                }
                wg_wait<0>();
                mbar_arrive_n_if<4>(sb + B_EMPTY + 8 * (31 % NST), lead);
            }
            fence_regs<0, 64>(acc);
            uint4 f[8];
#define TAG(v, c) (((v) & ~tagm[c]) | (par & tagm[c]))
#define PACK(k) f[k] = make_uint4(TAG(pack_bf16(acc[8 * (k)], acc[8 * (k) + 1]), 0), TAG(pack_bf16(acc[8 * (k) + 2], acc[8 * (k) + 3]), 2), \
                                  TAG(pack_bf16(acc[8 * (k) + 4], acc[8 * (k) + 5]), 1), TAG(pack_bf16(acc[8 * (k) + 6], acc[8 * (k) + 7]), 3))
#define SEND(k) do { st_relaxed(fout + 512 * (k), f[k].x); st_relaxed(fout + 512 * (k) + 32, f[k].z);                        \
                     st_relaxed(fout + 512 * (k) + 64, f[k].y); st_relaxed(fout + 512 * (k) + 96, f[k].w); } while (0)
#define OWN(k) wgmma128rs(acc, f[k], desc_lo(dd0 + d_addr((k) >> 2) / 16 + ((k) & 3) * 2), (k) != 0)
            const uint32_t dfa = sbd + 0x80000 + (early ? comp * 512 : NST * 1024), dfb = sbd + 0x80000 + (early ? (1 - comp) * 512 : NST * 1024 + 512);
#define MMA_F(pos, kk) wgmma128<0>(acc, (uint64_t)(((pos) < 5 ? dfa : dfb) + a_addr(29 + ((pos) - 2) % 3) / 16 + (kk) * 128) | (0x10ull << 32), \
                                   desc_lo(dd0 + d_addr(pos) / 16 + (kk) * 2), 1)
#define WAITF(pos) mbar_wait(vb + 8 * ((pos) - 2), 0)
            const uint32_t vb = sb + B_VAL + (early ? 0 : 48);
            const uint32_t ts = clk();
            if (early) {
                PACK(0); SEND(0); PACK(1); SEND(1); PACK(2); SEND(2); PACK(3); SEND(3);
                until(ts);
                PACK(4); PACK(5); PACK(6); PACK(7);
                const float s0 = comp ? -g0 : g0, s1 = comp ? -g1 : g1;
                const uint32_t og0 = pack_bf16(1.f - g0, 1.f - g0), og1 = pack_bf16(1.f - g1, 1.f - g1);
                const int rr = 0x7fff - (int)(lds32(sb + M_KEY) & 0x7fffu) - (tm * 128 + wg * 64 + r0);
#pragma unroll
                for (int k = 4; k < 8; k++) {
                    if (k < ESEND) { until(ts + ET1 + (k - 4) * STP); SEND(k); }
#pragma unroll
                    for (int i = 2 * k - 8; i < 2 * k - 6; i++) {
                        const uint32_t og = (i & 1) ? og1 : og0;
                        w[i] = make_uint4(hmul2_bf16(og, w[i].x), hmul2_bf16(og, w[i].y), hmul2_bf16(og, w[i].z), hmul2_bf16(og, w[i].w));
                        asm volatile("" : "+r"(w[i].x), "+r"(w[i].y), "+r"(w[i].z), "+r"(w[i].w));
                    }
                }
                WAITD(0);
                mbar_wait(sb + B_S3, 0);
                wg_fence();
#pragma unroll
                for (int k = 0; k < 8; k++) {
                    OWN(k);
                    if (k >= 1 && k + ESEND - 1 < 8) { wg_commit(); until(ts + ET1 + (k + ESEND - 5) * STP); SEND(k + ESEND - 1); wg_fence(); }
                }
                wg_commit();
                WAITD(2);
                bool ok = false;
#pragma unroll
                for (int pos = 2; pos < 8; pos++) {
                    if (!ok) {
                        if (pos >= 4) WAITD(pos);
                        WAITF(pos);
                    }
                    wg_fence();
                    MMA_F(pos, 0); MMA_F(pos, 1);
                    if (pos == 6) { wg_commit(); wg_wait<1>(); mbar_arrive_cluster_if(mapa(sb + B_XF, rank ^ 1), lead); wg_fence(); }
                    if (pos == 7) mbar_arrive_if(sb + B_S2, lead);
                    if (pos < 7) ok = mbar_test(vb + 8 * (pos - 1), 0) & (pos < 3 || mbar_test(sb + B_DL + 8 * (pos - 3), 0));
                    MMA_F(pos, 2); MMA_F(pos, 3);
                    wg_commit();
                }
                const uint32_t xd = mapa(sb + a_addr(29) + (tid & 127) * 16, rank ^ 1), xb = mapa(sb + B_X, rank ^ 1);
                if (rr == 0 || rr == 8) {
                    mbar_wait(sb + B_SIDE, 0);
#pragma unroll
                    for (int j = 0; j < 4; j++) {
                        const float4 ua = *(const float4*)(smem + M_RED + j * 128 + q * 32), ub = *(const float4*)(smem + M_RED + j * 128 + q * 32 + 16);
                        uint4 v = rr ? w[2 * j + 1] : w[2 * j];
                        v = make_uint4(pack_bf16(ua.x + bflo(v.x), ua.y + bfhi(v.x)), pack_bf16(ua.z + bflo(v.y), ua.w + bfhi(v.y)),
                                       pack_bf16(ub.x + bflo(v.z), ub.y + bfhi(v.z)), pack_bf16(ub.z + bflo(v.w), ub.w + bfhi(v.w)));
                        if (rr) w[2 * j + 1] = v; else w[2 * j] = v;
                    }
                }
                __syncwarp();
                mbar_wait(sb + B_XF, 0);
                wg_wait<0>();
                fence_regs<0, 64>(acc);
                keep_regs<0, 8>(f);
#pragma unroll
                for (int i = 0; i < 8; i++) {
                    const uint4 z = scale_add((i & 1) ? s1 : s0, acc, 16 * (i >> 1) + 2 * (i & 1), w[i]);
                    st_async16(xd + i * 2048, z.x, z.y, z.z, z.w, xb + 2 * (i & 4));
                    if (i & 1) until(ts);
                }
            } else {
                PACK(0); PACK(1); PACK(2); PACK(3); PACK(4); PACK(5); PACK(6); PACK(7);
                wg_fence();
#pragma unroll
                for (int k = 0; k < 8; k++) {
                    OWN(k);
                    if ((k & 1) && k / 2 < LSEND) { wg_commit(); until(ts + LT0 + k / 2 * LTP); SEND(k / 2); wg_fence(); }
                }
                wg_commit();
#pragma unroll
                for (int k = LSEND; k < 8; k++) { until(ts + LT0 + k * LTP); SEND(k); }
                float s0 = comp ? -g0 : g0, s1 = comp ? -g1 : g1;
                uint32_t xs = sb + a_addr(29) + (tid & 127) * 16;
                char* op = pout + ooff;
                asm volatile("" : "+f"(s0), "+f"(s1), "+r"(xs), "+l"(op));
                WAITF(2);
                mbar_wait(sb + B_S2, 0);
                bool there = false, there1 = false, ok = true;
#pragma unroll
                for (int pos = 2; pos < 8; pos++) {
                    if (!ok) WAITF(pos);
                    wg_fence();
                    MMA_F(pos, 0);
                    if (pos == XPOS) there = mbar_test(sb + B_X, 0);
                    MMA_F(pos, 1);
                    if (pos == XPOS) {
#pragma unroll
                        for (int i = 0; i < 4; i++) lds128_if(w[i], xs + i * 2048, there);
                    }
                    if (pos < 7) ok = mbar_test(vb + 8 * (pos - 1), 0);
                    MMA_F(pos, 2);
                    if (pos == 7) there1 = mbar_test(sb + B_X + 8, 0);
                    MMA_F(pos, 3);
                    wg_commit();
                }
#pragma unroll
                for (int i = 4; i < 8; i++) lds128_if(w[i], xs + i * 2048, there1);
#pragma unroll
                for (int h = 0; h < 2; h++) {
                    if (!(h ? there1 : there)) {
                        mbar_wait(sb + B_X + 8 * h, 0);
#pragma unroll
                        for (int i = 4 * h; i < 4 * h + 4; i++) w[i] = lds128(xs + i * 2048);
                    }
                    if (h == 0) {
                        wg_wait<0>();
                        fence_regs<0, 64>(acc);
                        keep_regs<0, 8>(f);
                    }
#pragma unroll
                    for (int i = 4 * h; i < 4 * h + 4; i++) {
                        stg_off<0>(op + (i & 1) * 8192 + (i >> 1) * 64, scale_add((i & 1) ? s1 : s0, acc, 16 * (i >> 1) + 2 * (i & 1), w[i]));
                        __syncwarp();
                    }
                }
            }
        }
    } else {
#define STEP0(j) do { tma2d_elect(sb + (j) * 16384, mC, (j) * 64, tm * 128, sb + B_FULL + 8 * (j));                            \
                      tma3d_elect(sb + (NST + (j)) * 16384, &p.mX2, (j) * 64, tn * 2, sb + B_FULL + 8 * (j)); } while (0)
        if (wu >= 14) {
            const uint32_t b = blockIdx.x;
            const char* q = wu == 14 ? (rank ? pc1 : pc0) + (uint32_t)((b >> 1) * 32 + lane) * (S_ * 2) + 128 : px + (uint32_t)(b * 4 + lane) * 128 + 65536;
            until(tstart + P_1);
            if (b < 128 && (wu == 14 || lane < 4)) prefetch_l2(q);
        } else if (wu == 13 && !spare) {
            if (lane == 0) ARM(1);
            __syncwarp();
            until(tstart + T_1);
            STEP0(1);
        }
        if (lane == 0) ARM(wu - 10);
        asm volatile("fence.mbarrier_init.release.cluster;" ::: "memory");
        __syncwarp();
        asm volatile("barrier.cluster.arrive.relaxed.aligned;" ::: "memory");
        if (spare) return;
        asm volatile("setmaxnreg.dec.sync.aligned.u32 " STR(RU) ";");
        if (wu < 14) {
            until(tstart + T_2 + (wu - 12) * PACE);
            STEP0(wu - 10);
        }
        asm volatile("barrier.cluster.wait.acquire.aligned;" ::: "memory");
        if (wu == 13) {
            const CUtensorMap* mD = comp ? &p.mDim : &p.mDre;
#pragma unroll
            for (int step = 4; step < NST; step++) {
                until(tstart + T_2 + (step - 2) * PACE);
                tma3d_elect(sb + b_addr(step), &p.mX2, step * 64, tn * 2, sb + B_FULL + 8 * step);
            }
#pragma unroll 1
            for (int step = NST, slot = 0, ph = 0; step < 32; step++) {
                mbar_wait(sb + B_EMPTY + 8 * slot, ph);
                tma2d_pair_elect(sb + b_addr(0) + slot * 16384 + rank * 8192, &p.mX, tn * 128 + rank * 64, step * 64, sb + B_FULL + 8 * slot);
                if (++slot == NST) { slot = 0; ph ^= 1; }
            }
#pragma unroll
            for (int c = 0; c < 4; c += 2) {
                const uint32_t bar = sb + (c ? B_D6 : B_FULL + 8 * (32 % NST));
                if (c) mbar_wait(sb + B_R6, 0);
                else mbar_wait(sb + B_EMPTY + 8 * (26 % NST), (26 / NST) & 1);
                tma5d_elect(sb + d_addr(c), mD, dcol(c, tn), tn * 4, bar);
                tma5d_elect(sb + d_addr(c + 1), mD, dcol(c + 1, tn), tn * 4, bar);
                mbar_expect_tx_elect(bar, 32768);
            }
#pragma unroll
            for (int c = 0; c < 4; c++) mbar_expect_tx_elect(sb + B_DL + 8 * c, 16384);
            mbar_wait(sb + B_S1, 0);
            const uint32_t tq = clk();
#pragma unroll
            for (int c = 0; c < 4; c++) {
                if (!(c & 1)) mbar_wait(sb + B_EMPTY + 8 * ((27 + c / 2) % NST), ((27 + c / 2) / NST) & 1);
                if (c) until(tq + (c == 1 ? T_D5 : c == 2 ? T_D6 : T_D7));
                tma5d_elect(sb + d_addr(4 + c), mD, dcol(4 + c, tn), tn * 4, sb + B_DL + 8 * c);
            }
        } else {
            if (wu == 12) {
#pragma unroll
                for (int step = 4; step < NST; step++) {
                    until(tstart + T_2 + (step - 2) * PACE);
                    tma2d_elect(sb + a_addr(step), mC, step * 64, tm * 128, sb + B_FULL + 8 * step);
                }
#pragma unroll 1
                for (int step = NST, slot = 0, ph = 0; step < 32; step++) {
                    mbar_wait(sb + B_EMPTY + 8 * slot, ph);
                    tma2d_elect(sb + slot * 16384, mC, step * 64, tm * 128, sb + B_FULL + 8 * slot);
                    mbar_expect_tx_elect(sb + B_FULL + 8 * slot, 32768);
                    if (++slot == NST) { slot = 0; ph ^= 1; }
                }
            } else if (wu == 14) {
                if (lane == 0) {
                    asm volatile("prefetch.tensormap [%0];" ::"l"(&p.mX) : "memory");
                    asm volatile("prefetch.tensormap [%0];" ::"l"(&p.mF) : "memory");
                    asm volatile("prefetch.tensormap [%0];" ::"l"(comp ? &p.mDim : &p.mDre) : "memory");
                    asm volatile("st.shared::cluster.u32 [%0], %1;" ::"r"(mapa(sb + M_ROLE, rank ^ 1)), "r"(role) : "memory");
                }
                nap_until(tstart + KEY_T0 - 1000);
                const uint32_t epoch = ld_relaxed(g->epoch + cta) + 1u, par = epoch & 1u;
                if (lane < 8) stg_off<0>(g->stamp + cta * 32 + lane * 4, make_uint4(par ^ 1u, 0, 0, 0));
                nap_until(tstart + KEY_T0);
                const uint32_t k = best_key(g->keys + (tm & 7) * NCTA, par);
                const uint4 xr = ldg_nc_off<0>(px + (0x7fff - (k & 0x7fffu)) * (D_ * 2) + rank * 512 + lane * 16);
                const uint4 g4 = wait_tags(g->gate + tm * 128 + lane * 4, par);
                sts128(sb + M_G + lane * 16, make_uint4(g4.x & ~1u, g4.y & ~1u, g4.z & ~1u, g4.w & ~1u));
                sts128(sb + M_UPD + lane * 16, xr);
                if (lane == 0) {
                    *(volatile uint32_t*)(smem + M_KEY) = k;
                    *(volatile uint32_t*)(smem + M_PAR) = par;
                    st_relaxed(g->epoch + cta, epoch);
                }
                mbar_arrive_warp(sb + B_GATE);
            } else {
                const int fr = ffn_pair(role);
                const uint32_t t1 = tstart + FFN_T0 + (rank + ((fr >> 1) & 2)) * (FFN_DT / 4);
                if (!((NOFFN_MASK >> role) & 1)) {
#pragma unroll 1
                    for (int i = 0; i < 12; i++) {
                        const int qu = i < 4 ? 2 + (i >> 1) : (i - 4) >> 1;
                        const uint32_t bar = sb + B_FFN + 8 * (i < 4 ? 3 : qu), dst = sb + R6 + (i & 1) * 16384 + qu * 4096;
                        if (i == 8) mbar_wait(sb + B_VD, 0);
                        if (i == 0 || (i >= 4 && !(i & 1))) mbar_expect_tx_elect(bar, i ? 8192 : 16384);
                        nap_until(t1 + i * FFN_DT);
                        tma2d_elect(dst, i < 4 ? &p.mWd : (i & 1) ? &p.mWu : &p.mWg, i < 4 ? rank * 256 : fr * 32, i < 4 ? fr * 32 + i * 8 : rank * 256 + qu * 64, bar);
                    }
                }
            }
            __syncwarp();
            mbar_wait(sb + B_GATE, 0);
            fetch_job<0>(p, g, smem, sb, cta, wu == 12 ? 2 : wu - 14, lds32(sb + M_PAR));
        }
    }
}

typedef CUresult (*EncodeTiledFn)(CUtensorMap*, CUtensorMapDataType, cuuint32_t, void*, const cuuint64_t*, const cuuint64_t*,
                                  const cuuint32_t*, const cuuint32_t*, CUtensorMapInterleave, CUtensorMapSwizzle,
                                  CUtensorMapL2promotion, CUtensorMapFloatOOBfill);

static void make_map(EncodeTiledFn enc, CUtensorMap* m, const void* base, uint64_t cols, uint64_t rows, uint32_t box_rows,
                     CUtensorMapSwizzle sw = CU_TENSOR_MAP_SWIZZLE_128B, uint32_t box_cols = 64,
                     CUtensorMapL2promotion promo = CU_TENSOR_MAP_L2_PROMOTION_L2_128B) {
    cuuint64_t dims[2] = {cols, rows};
    cuuint64_t str[1] = {cols * 2};
    cuuint32_t box[2] = {box_cols, box_rows};
    cuuint32_t es[2] = {1, 1};
    enc(m, CU_TENSOR_MAP_DATA_TYPE_BFLOAT16, 2, (void*)base, dims, str, box, es, CU_TENSOR_MAP_INTERLEAVE_NONE,
        sw, promo, CU_TENSOR_MAP_FLOAT_OOB_FILL_NONE);
}

static void make_map_chunks(EncodeTiledFn enc, CUtensorMap* m, const void* base, uint64_t rows) {
    cuuint64_t dims[3] = {64, rows, D_ / 64};
    cuuint64_t str[2] = {D_ * 2, 128};
    cuuint32_t box[3] = {64, 64, 2};
    cuuint32_t es[3] = {1, 1, 1};
    enc(m, CU_TENSOR_MAP_DATA_TYPE_BFLOAT16, 3, (void*)base, dims, str, box, es, CU_TENSOR_MAP_INTERLEAVE_NONE,
        CU_TENSOR_MAP_SWIZZLE_128B, CU_TENSOR_MAP_L2_PROMOTION_L2_128B, CU_TENSOR_MAP_FLOAT_OOB_FILL_NONE);
}

static void make_map_perm(EncodeTiledFn enc, CUtensorMap* m, const void* base) {
    cuuint64_t dims[5] = {D_, 2, 4, 4, D_ / 32};
    cuuint64_t str[4] = {D_ * 2, 8 * D_ * 2, 2 * D_ * 2, 32 * D_ * 2};
    cuuint32_t box[5] = {64, 2, 4, 4, 4};
    cuuint32_t es[5] = {1, 1, 1, 1, 1};
    enc(m, CU_TENSOR_MAP_DATA_TYPE_BFLOAT16, 5, (void*)base, dims, str, box, es, CU_TENSOR_MAP_INTERLEAVE_NONE,
        CU_TENSOR_MAP_SWIZZLE_128B, CU_TENSOR_MAP_L2_PROMOTION_L2_128B, CU_TENSOR_MAP_FLOAT_OOB_FILL_NONE);
}

extern "C" void kernel_launch(void* const* d_in, const int* in_sizes, int n_in, void* d_out, int out_size) {
    (void)in_sizes; (void)n_in; (void)out_size;
    static EncodeTiledFn enc = nullptr;
    static bool fused_ok = false;
    static void* scr = nullptr;
    if (!enc) {
        void* fn = nullptr;
        cudaDriverEntryPointQueryResult q;
        cudaGetDriverEntryPoint("cuTensorMapEncodeTiled", &fn, cudaEnableDefault, &q);
        enc = (EncodeTiledFn)fn;
        cudaGetSymbolAddress(&scr, g_scr);
        cudaFuncSetAttribute(fused_kernel, cudaFuncAttributeMaxDynamicSharedMemorySize, SMEM_BYTES);
        int dev = 0, nsm = 0, ncl = 0;
        cudaGetDevice(&dev);
        cudaDeviceGetAttribute(&nsm, cudaDevAttrMultiProcessorCount, dev);
        cudaLaunchConfig_t cfg = {};
        cfg.gridDim = dim3(132); cfg.blockDim = dim3(NTHREADS); cfg.dynamicSmemBytes = SMEM_BYTES;
        cudaLaunchAttribute at;
        at.id = cudaLaunchAttributeClusterDimension;
        at.val.clusterDim.x = 2; at.val.clusterDim.y = 1; at.val.clusterDim.z = 1;
        cfg.attrs = &at; cfg.numAttrs = 1;
        fused_ok = cudaOccupancyMaxActiveClusters(&ncl, fused_kernel, &cfg) == cudaSuccess && nsm == 132 && ncl == 66;
        (void)cudaGetLastError();
    }
    if (!fused_ok) {
        const bf16* const* in = (const bf16* const*)d_in;
        fb_hidden<<<S_, D_, 0, cudaStreamPerThread>>>(in[0], in[3], in[4], in[10], in[6]);
        fb_ffn1<<<F_ / 128, 128, 0, cudaStreamPerThread>>>(in[0], in[7], in[8]);
        fb_ffn2<<<D_ / 64, 64, 0, cudaStreamPerThread>>>(in[9]);
        fb_seq<<<S_, D_, 0, cudaStreamPerThread>>>(in[0], in[1], in[2], (bf16*)d_out);
        return;
    }
    Params p;
    p.dre = (const bf16*)d_in[3];
    p.dim = (const bf16*)d_in[4];
    p.w_r = (const bf16*)d_in[6];
    p.gate_w = (const bf16*)d_in[10];
    make_map_chunks(enc, &p.mX2, d_in[0], S_);
    make_map(enc, &p.mX, d_in[0], D_, S_, 64);
    make_map(enc, &p.mCre, d_in[1], S_, S_, 128);
    make_map(enc, &p.mCim, d_in[2], S_, S_, 128);
    make_map_perm(enc, &p.mDre, d_in[3]);
    make_map_perm(enc, &p.mDim, d_in[4]);
    make_map(enc, &p.mF, scr, 64, NCTA * 256, 64, CU_TENSOR_MAP_SWIZZLE_NONE);
    make_map(enc, &p.mWg, d_in[7], F_, D_, 64, CU_TENSOR_MAP_SWIZZLE_NONE, 32, CU_TENSOR_MAP_L2_PROMOTION_NONE);
    make_map(enc, &p.mWu, d_in[8], F_, D_, 64, CU_TENSOR_MAP_SWIZZLE_NONE, 32, CU_TENSOR_MAP_L2_PROMOTION_NONE);
    make_map(enc, &p.mWd, d_in[9], D_, F_, 8, CU_TENSOR_MAP_SWIZZLE_NONE, 256);
    fused_kernel<<<132, NTHREADS, SMEM_BYTES, cudaStreamPerThread>>>((const char*)d_in[1], (const char*)d_in[2], (const char*)d_in[0], (char*)d_out, (Scratch*)scr, p);
}
```

```cpp
#include <cuda_runtime.h>
#include <cuda.h>
#include <cuda_bf16.h>
#include <stdint.h>

typedef __nv_bfloat16 bf16;

constexpr int S_ = 2048, D_ = 512, F_ = 1792;
constexpr int NCTA = 128;
constexpr int NTHREADS = 512;
constexpr int NST = 6;
constexpr int SP0 = 27;
constexpr int FFN_CTAS = F_ / 16;
constexpr uint32_t SPIN_LIMIT = 1u << 16;

#define P_1 500
#define T_1 550
#define T_2 1050
#define PACE 400
#define ROUTER_T0 3000
#define ROUTER_DT 280
#define FFN_T0 5200
#define FFN_DT 640
#define XLD 10
#define XN 8
#define XD 1
#define PFD_T0 12200
#define PFD_DT 250
#define SUM_T0 14000
#define ET1 600
#define STP 170
#define ESEND 6
#define LT0 450
#define LTP 170
#define LSEND 3
#define SDEL 280
#define E_RD0 1330
#define E_RD1 2180
#define L_RD0 3300
#define L_RD1 3930
#define SG 130
#define T_D5 1500
#define T_D6 1700
#define T_D7 2400
#define XPOS 7
#define RC 168
#define RS_ 112
#define RU 64
#define KEY_T0 9800
#define NOFFN_MASK 0x00c8800f00000000ull
#define SIDE_T0 2800
#define STR2(x) #x
#define STR(x) STR2(x)

__host__ __device__ constexpr int a_addr(int s) { return s % NST * 16384; }
__host__ __device__ constexpr int b_addr(int s) { return (NST + s % NST) * 16384; }
constexpr int R6 = 2 * NST * 16384;
__host__ __device__ constexpr int d_addr(int p) { return p / 2 == 1 ? R6 + (p & 1) * 16384 : (p & 1) ? b_addr(26 + p / 3) : a_addr(26 + p / 3); }
static_assert(d_addr(0) == a_addr(26) && d_addr(4) == a_addr(27) && d_addr(6) == a_addr(28), "");
constexpr int OFF_MISC = R6 + 32768;
constexpr int B_FULL = OFF_MISC;
constexpr int B_EMPTY = B_FULL + 48;
constexpr int B_EMPR = B_EMPTY + 48;
constexpr int B_VD = B_EMPR + 48;
constexpr int B_X = B_VD + 8;
constexpr int B_HX = B_X + 16;
constexpr int B_XF = B_HX + 8;
constexpr int B_S0 = B_XF + 8;
constexpr int B_S1 = B_S0 + 8;
constexpr int B_EA = B_S1 + 8;
constexpr int B_S2 = B_EA + 8;
constexpr int B_S3 = B_S2 + 8;
constexpr int B_D6 = B_S3 + 8;
constexpr int B_DL = B_D6 + 8;
constexpr int B_GATE = B_DL + 32;
constexpr int B_SIDE = B_GATE + 8;
constexpr int B_FFN = B_SIDE + 8;
constexpr int B_R6 = B_FFN + 32;
constexpr int B_LAND = B_R6 + 8;
constexpr int B_VAL = B_LAND + 48;
constexpr int B_TH = B_VAL + 96;
constexpr int M_TH = B_TH + 24;
constexpr int NBAR = (M_TH - B_EMPTY) / 8;
constexpr int M_KEY = M_TH + 12;
constexpr int M_PAR = M_KEY + 4;
constexpr int M_ROLE = M_PAR + 4;
constexpr int M_HX = OFF_MISC + 544;
constexpr int M_G = M_HX + 256;
constexpr int M_UPD = M_G + 512;
constexpr int M_RED = M_UPD + 512;
constexpr int SMEM_BYTES = 232448;
static_assert(M_RED + 512 <= SMEM_BYTES && M_ROLE + 4 <= M_HX, "smem");

struct Params {
    const bf16 *gate_w, *w_r, *dre, *dim;
    CUtensorMap mCre, mCim, mX2, mX, mDre, mDim, mF, mWg, mWu, mWd;
};

struct Scratch {
    uint32_t frag[NCTA * 2 * 4096];
    uint32_t stamp[NCTA * 32];
    uint32_t gate[S_];
    uint32_t keys[8 * NCTA];
    uint32_t part[FFN_CTAS / 2 * D_];
    uint32_t phint[4 * 8 * 8];
    uint32_t upd[D_];
    uint32_t epoch[NCTA + 4];
};
__device__ __align__(1024) Scratch g_scr;

__device__ __forceinline__ uint32_t smem_u32(const void* p) { return (uint32_t)__cvta_generic_to_shared(p); }
__device__ __forceinline__ void mbar_init(uint32_t bar, uint32_t cnt) {
    asm volatile("mbarrier.init.shared::cta.b64 [%0], %1;" ::"r"(bar), "r"(cnt) : "memory");
}
__device__ __forceinline__ void mbar_expect_tx(uint32_t bar, uint32_t bytes) {
    asm volatile("mbarrier.arrive.expect_tx.shared::cta.b64 _, [%0], %1;" ::"r"(bar), "r"(bytes) : "memory");
}
__device__ __forceinline__ void mbar_arrive(uint32_t bar) {
    asm volatile("mbarrier.arrive.shared::cta.b64 _, [%0];" ::"r"(bar) : "memory");
}
template <int N>
__device__ __forceinline__ void mbar_arrive_n_if(uint32_t bar, bool pred) {
    asm volatile("{.reg .pred p; setp.ne.b32 p, %1, 0; @p mbarrier.arrive.shared::cta.b64 _, [%0], %2;}" ::"r"(bar), "r"((int)pred), "n"(N) : "memory");
}
__device__ __forceinline__ void mbar_arrive_if(uint32_t bar, bool pred) {
    asm volatile("{.reg .pred p; setp.ne.b32 p, %1, 0; @p mbarrier.arrive.shared::cta.b64 _, [%0];}" ::"r"(bar), "r"((int)pred) : "memory");
}
__device__ __forceinline__ void mbar_arrive_warp(uint32_t bar) {
    __syncwarp();
    mbar_arrive_if(bar, (threadIdx.x & 31) == 0);
}
__device__ __forceinline__ void mbar_arrive_cluster_if(uint32_t bar, bool pred) {
    asm volatile("{.reg .pred p; setp.ne.b32 p, %1, 0; @p mbarrier.arrive.shared::cluster.b64 _, [%0], 1;}"
                 ::"r"(bar), "r"((int)pred) : "memory");
}
__device__ __forceinline__ uint32_t mapa(uint32_t a, uint32_t cta) {
    uint32_t r;
    asm volatile("mapa.shared::cluster.u32 %0, %1, %2;" : "=r"(r) : "r"(a), "r"(cta));
    return r;
}
__device__ __forceinline__ bool mbar_try(uint32_t bar, uint32_t parity) {
    uint32_t ok;
    asm volatile("{.reg .pred p; mbarrier.try_wait.parity.shared::cta.b64 p, [%1], %2; selp.u32 %0,1,0,p;}"
                 : "=r"(ok) : "r"(bar), "r"(parity) : "memory");
    return ok;
}
__device__ __forceinline__ bool mbar_test(uint32_t bar, uint32_t parity) {
    uint32_t ok;
    asm volatile("{.reg .pred p; mbarrier.test_wait.parity.shared::cta.b64 p, [%1], %2; selp.u32 %0,1,0,p;}"
                 : "=r"(ok) : "r"(bar), "r"(parity) : "memory");
    return ok;
}
__device__ __forceinline__ void mbar_wait(uint32_t bar, uint32_t parity) {
    uint32_t n = 0;
#pragma unroll 1
    while (!mbar_try(bar, parity)) { if (++n > SPIN_LIMIT) break; }
}
__device__ __forceinline__ void tma2d(uint32_t dst, const CUtensorMap* m, int c0, int c1, uint32_t bar) {
    asm volatile("cp.async.bulk.tensor.2d.shared::cluster.global.mbarrier::complete_tx::bytes [%0], [%1, {%3,%4}], [%2];"
                 ::"r"(dst), "l"(m), "r"(bar), "r"(c0), "r"(c1) : "memory");
}
__device__ __forceinline__ void tma3d(uint32_t dst, const CUtensorMap* m, int row, int chunk, uint32_t bar) {
    asm volatile("cp.async.bulk.tensor.3d.shared::cluster.global.mbarrier::complete_tx::bytes [%0], [%1, {%3,%4,%5}], [%2];"
                 ::"r"(dst), "l"(m), "r"(bar), "r"(0), "r"(row), "r"(chunk) : "memory");
}
__device__ __forceinline__ void tma2d_elect(uint32_t dst, const CUtensorMap* m, int c0, int c1, uint32_t bar) {
    asm volatile("{.reg .pred p; elect.sync _|p, 0xffffffff;"
                 " @p cp.async.bulk.tensor.2d.shared::cluster.global.mbarrier::complete_tx::bytes [%0], [%1, {%3,%4}], [%2];}"
                 ::"r"(dst), "l"(m), "r"(bar), "r"(c0), "r"(c1) : "memory");
}
__device__ __forceinline__ void tma2d_pair_elect(uint32_t dst, const CUtensorMap* m, int c0, int c1, uint32_t bar) {
    asm volatile("{.reg .pred p; elect.sync _|p, 0xffffffff;"
                 " @p cp.async.bulk.tensor.2d.shared::cluster.global.mbarrier::complete_tx::bytes.multicast::cluster"
                 " [%0], [%1, {%3,%4}], [%2], %5;}" ::"r"(dst), "l"(m), "r"(bar), "r"(c0), "r"(c1), "h"((uint16_t)3) : "memory");
}
__device__ __forceinline__ void tma3d_elect(uint32_t dst, const CUtensorMap* m, int row, int chunk, uint32_t bar) {
    asm volatile("{.reg .pred p; elect.sync _|p, 0xffffffff;"
                 " @p cp.async.bulk.tensor.3d.shared::cluster.global.mbarrier::complete_tx::bytes [%0], [%1, {%3,%4,%5}], [%2];}"
                 ::"r"(dst), "l"(m), "r"(bar), "r"(0), "r"(row), "r"(chunk) : "memory");
}
__device__ __forceinline__ void tma5d_elect(uint32_t dst, const CUtensorMap* m, int c0, int c4, uint32_t bar) {
    asm volatile("{.reg .pred p; elect.sync _|p, 0xffffffff;"
                 " @p cp.async.bulk.tensor.5d.shared::cluster.global.mbarrier::complete_tx::bytes [%0], [%1, {%3,%5,%5,%5,%4}], [%2];}"
                 ::"r"(dst), "l"(m), "r"(bar), "r"(c0), "r"(c4), "r"(0) : "memory");
}
__device__ __forceinline__ void mbar_expect_tx_elect(uint32_t bar, uint32_t bytes) {
    asm volatile("{.reg .pred p; elect.sync _|p, 0xffffffff; @p mbarrier.arrive.expect_tx.shared::cta.b64 _, [%0], %1;}"
                 ::"r"(bar), "r"(bytes) : "memory");
}
__device__ __forceinline__ void fence_proxy_async_smem() { asm volatile("fence.proxy.async.shared::cta;" ::: "memory"); }
__device__ __forceinline__ void prefetch_l2(const void* p) { asm volatile("prefetch.global.L2 [%0];" ::"l"(p)); }
__device__ __forceinline__ uint32_t ld_relaxed(const void* p) {
    uint32_t v;
    asm volatile("ld.relaxed.gpu.global.u32 %0, [%1];" : "=r"(v) : "l"(p) : "memory");
    return v;
}
__device__ __forceinline__ uint4 ld_relaxed4(const void* p) {
    uint4 v;
    asm volatile("ld.relaxed.gpu.global.v4.u32 {%0,%1,%2,%3}, [%4];" : "=r"(v.x), "=r"(v.y), "=r"(v.z), "=r"(v.w) : "l"(p) : "memory");
    return v;
}
__device__ __forceinline__ void st_relaxed(unsigned int* p, uint32_t v) {
    asm volatile("st.relaxed.gpu.global.u32 [%0], %1;" ::"l"(p), "r"(v) : "memory");
}
__device__ __forceinline__ uint32_t tagf(float v, uint32_t par) { return (__float_as_uint(v) & ~1u) | par; }
template <int BIT = 0>
__device__ __forceinline__ uint4 wait_tags(const unsigned int* p, uint32_t par) {
    uint32_t n = 0;
#pragma unroll 1
    while (true) {
        const uint4 v = ld_relaxed4(p);
        const uint32_t m = par ? (v.x & v.y & v.z & v.w) : ~(v.x | v.y | v.z | v.w);
        if (__all_sync(0xffffffffu, (m >> BIT) & 1u)) return v;
        __nanosleep(100);
        if (++n > SPIN_LIMIT) return v;
    }
}
__device__ __forceinline__ uint32_t best_key(const uint32_t* keys, uint32_t par) {
    const uint4 k = wait_tags<15>(keys + (threadIdx.x & 31) * 4, par);
    return __reduce_max_sync(0xffffffffu, max(max(k.x, k.y), max(k.z, k.w)));
}
__device__ __forceinline__ void named_bar(int id, int n) { asm volatile("bar.sync %0, %1;" ::"r"(id), "r"(n) : "memory"); }
template <int OFF>
__device__ __forceinline__ uint4 ldg_nc_off(const void* p) {
    uint4 v;
    asm volatile("ld.global.nc.v4.u32 {%0,%1,%2,%3}, [%4+%5];" : "=r"(v.x), "=r"(v.y), "=r"(v.z), "=r"(v.w) : "l"(p), "n"(OFF));
    return v;
}
__device__ __forceinline__ void ldg_nc_if(uint4& v, const void* a, bool pred) {
    asm volatile("{.reg .pred p; setp.ne.b32 p, %5, 0; @p ld.global.nc.v4.u32 {%0,%1,%2,%3}, [%4];}"
                 : "+r"(v.x), "+r"(v.y), "+r"(v.z), "+r"(v.w) : "l"(a), "r"((int)pred) : "memory");
}
template <int OFF>
__device__ __forceinline__ void stg_off(void* p, const uint4& v) {
    asm volatile("st.global.v4.u32 [%0+%5], {%1,%2,%3,%4};" ::"l"(p), "r"(v.x), "r"(v.y), "r"(v.z), "r"(v.w), "n"(OFF) : "memory");
}
__device__ __forceinline__ void sts128(uint32_t a, const uint4& v) {
    asm volatile("st.shared.v4.u32 [%0], {%1,%2,%3,%4};" ::"r"(a), "r"(v.x), "r"(v.y), "r"(v.z), "r"(v.w) : "memory");
}
__device__ __forceinline__ uint4 lds128(uint32_t a) {
    uint4 v;
    asm volatile("ld.shared.v4.u32 {%0,%1,%2,%3}, [%4];" : "=r"(v.x), "=r"(v.y), "=r"(v.z), "=r"(v.w) : "r"(a) : "memory");
    return v;
}
__device__ __forceinline__ void lds128_if(uint4& v, uint32_t a, bool pred) {
    asm volatile("{.reg .pred p; setp.ne.b32 p, %5, 0; @p ld.shared.v4.u32 {%0,%1,%2,%3}, [%4];}"
                 : "+r"(v.x), "+r"(v.y), "+r"(v.z), "+r"(v.w) : "r"(a), "r"((int)pred) : "memory");
}
__device__ __forceinline__ uint32_t lds32(uint32_t a) {
    uint32_t v;
    asm volatile("ld.shared.u32 %0, [%1];" : "=r"(v) : "r"(a) : "memory");
    return v;
}
__device__ __forceinline__ void st_async16(uint32_t dst, uint32_t x, uint32_t y, uint32_t z, uint32_t w, uint32_t bar) {
    asm volatile("st.async.weak.shared::cluster.mbarrier::complete_tx::bytes.v4.b32 [%0], {%1,%2,%3,%4}, [%5];"
                 ::"r"(dst), "r"(x), "r"(y), "r"(z), "r"(w), "r"(bar) : "memory");
}
__device__ __forceinline__ int sel(int a, int b, bool p) {
    int r;
    asm("{.reg .pred q; setp.ne.b32 q, %3, 0; selp.b32 %0, %1, %2, q;}" : "=r"(r) : "r"(a), "r"(b), "r"((int)p));
    return r;
}
__device__ __forceinline__ float selpf(float a, float b, bool p) {
    float r;
    asm("{.reg .pred q; setp.ne.b32 q, %3, 0; selp.f32 %0, %1, %2, q;}" : "=f"(r) : "f"(a), "f"(b), "r"((int)p));
    return r;
}
template <int N, int MASK, int SZ>
__device__ __forceinline__ void halve(float (&a)[SZ]) {
    const bool up = threadIdx.x & MASK;
#pragma unroll
    for (int j = 0; j < N; j++) a[j] = selpf(a[N + j], a[j], up) + __shfl_xor_sync(0xffffffffu, selpf(a[j], a[N + j], up), MASK);
}
__device__ __forceinline__ float bflo(uint32_t u) { return __uint_as_float(u << 16); }
__device__ __forceinline__ float bfhi(uint32_t u) { return __uint_as_float(u & 0xffff0000u); }
__device__ __forceinline__ uint32_t pack_bf16(float lo, float hi) {
    uint32_t r;
    asm("cvt.rn.bf16x2.f32 %0, %1, %2;" : "=r"(r) : "f"(hi), "f"(lo));
    return r;
}
__device__ __forceinline__ uint32_t hmul2_bf16(uint32_t a, uint32_t b) {
    uint32_t r;
    asm("mul.rn.bf16x2 %0, %1, %2;" : "=r"(r) : "r"(a), "r"(b));
    return r;
}
__device__ __forceinline__ float sigmoidf_(float v) { return 1.0f / (1.0f + __expf(-v)); }
__device__ __forceinline__ void wg_fence() { asm volatile("wgmma.fence.sync.aligned;" ::: "memory"); }
__device__ __forceinline__ void wg_commit() { asm volatile("wgmma.commit_group.sync.aligned;" ::: "memory"); }
template <int N> __device__ __forceinline__ void wg_wait() { asm volatile("wgmma.wait_group.sync.aligned %0;" ::"n"(N) : "memory"); }
__device__ __forceinline__ uint64_t desc_lo(uint32_t lo) { return (uint64_t)lo | (0x40000040ull << 32); }
template <int LO, int HI, int N>
__device__ __forceinline__ void fence_regs(float (&d)[N]) {
#pragma unroll
    for (int i = LO; i < HI; i++) asm volatile("" : "+f"(d[i])::"memory");
}
template <int LO, int HI, int N>
__device__ __forceinline__ void keep_regs(uint4 (&f)[N]) {
#pragma unroll
    for (int i = LO; i < HI; i++) asm volatile("" ::"r"(f[i].x), "r"(f[i].y), "r"(f[i].z), "r"(f[i].w) : "memory");
}
template <int TB = 1>
__device__ __forceinline__ void wgmma128(float (&d)[64], uint64_t da, uint64_t db, int scaleD) {
    asm volatile(
        "{ .reg .pred p; setp.ne.b32 p, %66, 0;\n"
        "wgmma.mma_async.sync.aligned.m64n128k16.f32.bf16.bf16 "
        "{%0,%1,%2,%3,%4,%5,%6,%7,%8,%9,%10,%11,%12,%13,%14,%15,%16,%17,%18,%19,%20,%21,%22,%23,%24,%25,%26,%27,%28,%29,%30,%31,"
        "%32,%33,%34,%35,%36,%37,%38,%39,%40,%41,%42,%43,%44,%45,%46,%47,%48,%49,%50,%51,%52,%53,%54,%55,%56,%57,%58,%59,%60,%61,%62,%63}, "
        "%64, %65, p, 1, 1, 0, %67;\n}"
        : "+f"(d[0]), "+f"(d[1]), "+f"(d[2]), "+f"(d[3]), "+f"(d[4]), "+f"(d[5]), "+f"(d[6]), "+f"(d[7]),
          "+f"(d[8]), "+f"(d[9]), "+f"(d[10]), "+f"(d[11]), "+f"(d[12]), "+f"(d[13]), "+f"(d[14]), "+f"(d[15]),
          "+f"(d[16]), "+f"(d[17]), "+f"(d[18]), "+f"(d[19]), "+f"(d[20]), "+f"(d[21]), "+f"(d[22]), "+f"(d[23]),
          "+f"(d[24]), "+f"(d[25]), "+f"(d[26]), "+f"(d[27]), "+f"(d[28]), "+f"(d[29]), "+f"(d[30]), "+f"(d[31]),
          "+f"(d[32]), "+f"(d[33]), "+f"(d[34]), "+f"(d[35]), "+f"(d[36]), "+f"(d[37]), "+f"(d[38]), "+f"(d[39]),
          "+f"(d[40]), "+f"(d[41]), "+f"(d[42]), "+f"(d[43]), "+f"(d[44]), "+f"(d[45]), "+f"(d[46]), "+f"(d[47]),
          "+f"(d[48]), "+f"(d[49]), "+f"(d[50]), "+f"(d[51]), "+f"(d[52]), "+f"(d[53]), "+f"(d[54]), "+f"(d[55]),
          "+f"(d[56]), "+f"(d[57]), "+f"(d[58]), "+f"(d[59]), "+f"(d[60]), "+f"(d[61]), "+f"(d[62]), "+f"(d[63])
        : "l"(da), "l"(db), "r"(scaleD), "n"(TB));
}
__device__ __forceinline__ void wgmma128rs(float (&d)[64], const uint4& a, uint64_t db, int scaleD) {
    asm volatile(
        "{ .reg .pred p; setp.ne.b32 p, %69, 0;\n"
        "wgmma.mma_async.sync.aligned.m64n128k16.f32.bf16.bf16 "
        "{%0,%1,%2,%3,%4,%5,%6,%7,%8,%9,%10,%11,%12,%13,%14,%15,%16,%17,%18,%19,%20,%21,%22,%23,%24,%25,%26,%27,%28,%29,%30,%31,"
        "%32,%33,%34,%35,%36,%37,%38,%39,%40,%41,%42,%43,%44,%45,%46,%47,%48,%49,%50,%51,%52,%53,%54,%55,%56,%57,%58,%59,%60,%61,%62,%63}, "
        "{%64,%65,%66,%67}, %68, p, 1, 1, 0;\n}"
        : "+f"(d[0]), "+f"(d[1]), "+f"(d[2]), "+f"(d[3]), "+f"(d[4]), "+f"(d[5]), "+f"(d[6]), "+f"(d[7]),
          "+f"(d[8]), "+f"(d[9]), "+f"(d[10]), "+f"(d[11]), "+f"(d[12]), "+f"(d[13]), "+f"(d[14]), "+f"(d[15]),
          "+f"(d[16]), "+f"(d[17]), "+f"(d[18]), "+f"(d[19]), "+f"(d[20]), "+f"(d[21]), "+f"(d[22]), "+f"(d[23]),
          "+f"(d[24]), "+f"(d[25]), "+f"(d[26]), "+f"(d[27]), "+f"(d[28]), "+f"(d[29]), "+f"(d[30]), "+f"(d[31]),
          "+f"(d[32]), "+f"(d[33]), "+f"(d[34]), "+f"(d[35]), "+f"(d[36]), "+f"(d[37]), "+f"(d[38]), "+f"(d[39]),
          "+f"(d[40]), "+f"(d[41]), "+f"(d[42]), "+f"(d[43]), "+f"(d[44]), "+f"(d[45]), "+f"(d[46]), "+f"(d[47]),
          "+f"(d[48]), "+f"(d[49]), "+f"(d[50]), "+f"(d[51]), "+f"(d[52]), "+f"(d[53]), "+f"(d[54]), "+f"(d[55]),
          "+f"(d[56]), "+f"(d[57]), "+f"(d[58]), "+f"(d[59]), "+f"(d[60]), "+f"(d[61]), "+f"(d[62]), "+f"(d[63])
        : "r"(a.x), "r"(a.y), "r"(a.z), "r"(a.w), "l"(db), "r"(scaleD));
}
__device__ __forceinline__ uint32_t clk() { uint64_t c; asm volatile("mov.u64 %0, %%clock64;" : "=l"(c)::"memory"); return (uint32_t)c; }
__device__ __forceinline__ uint32_t gtime() { uint64_t t; asm volatile("mov.u64 %0, %%globaltimer;" : "=l"(t)::"memory"); return (uint32_t)t; }
__device__ __forceinline__ void until(uint32_t t) { while (t - clk() < 0x8000u) {} }
__device__ __forceinline__ void nap_until(uint32_t t) { while (t - clk() < 0x8000u) __nanosleep(20); }
__device__ __forceinline__ uint4 scale_add(float s, const float (&a)[64], int o, const uint4& w) {
    return make_uint4(pack_bf16(fmaf(s, a[o], bflo(w.x)), fmaf(s, a[o + 1], bfhi(w.x))), pack_bf16(fmaf(s, a[o + 4], bflo(w.y)), fmaf(s, a[o + 5], bfhi(w.y))),
                      pack_bf16(fmaf(s, a[o + 8], bflo(w.z)), fmaf(s, a[o + 9], bfhi(w.z))), pack_bf16(fmaf(s, a[o + 12], bflo(w.w)), fmaf(s, a[o + 13], bfhi(w.w))));
}

__device__ __forceinline__ uint32_t router_key(float score, int row) {
    const float r = score + 0.0f;
    uint32_t u = pack_bf16(r, 0.f) & 0xffffu;
    u = (u & 0x8000u) ? (~u & 0xffffu) : (u | 0x8000u);
    if (r != r) u = 0;
    return (u << 16) | (uint32_t)(0x7fff - row);
}

#define g_ab g_scr.frag
#define g_fb_h ((float*)g_scr.part)
#define g_fb_upd (g_fb_h + 2048)
#define g_fb_gate (g_fb_h + 4096)
#define g_fb_keys (g_scr.part + 8192)
__global__ void fb_hidden(const bf16* x, const bf16* dre, const bf16* dim, const bf16* gw, const bf16* wr) {
    __shared__ float xs[D_];
    const int s = blockIdx.x, t = threadIdx.x;
    xs[t] = __bfloat162float(x[s * D_ + t]);
    __syncthreads();
    float a = 0.f, b = 0.f;
    for (int d = 0; d < D_; d++) { a = fmaf(xs[d], __bfloat162float(dre[t * D_ + d]), a); b = fmaf(xs[d], __bfloat162float(dim[t * D_ + d]), b); }
    ((bf16*)g_ab)[s * 1024 + t] = __float2bfloat16(a);
    ((bf16*)g_ab)[s * 1024 + 512 + t] = __float2bfloat16(b);
    if (t == 0) {
        float u = 0.f, v = 0.f;
        for (int d = 0; d < D_; d++) { u = fmaf(xs[d], __bfloat162float(gw[d]), u); v = fmaf(xs[d], __bfloat162float(wr[d]), v); }
        g_fb_gate[s] = sigmoidf_(u);
        g_fb_keys[s] = router_key(v, s);
    }
}
__device__ uint32_t fb_best() {
    uint32_t k = 0;
    for (int i = 0; i < S_; i++) k = max(k, g_fb_keys[i]);
    return k;
}
__global__ void fb_ffn1(const bf16* x, const bf16* wg, const bf16* wu) {
    const int f = blockIdx.x * blockDim.x + threadIdx.x, idx = 0x7fff - (int)(fb_best() & 0x7fffu);
    float a = 0.f, b = 0.f;
    for (int d = 0; d < D_; d++) {
        const float xv = __bfloat162float(x[idx * D_ + d]);
        a = fmaf(xv, __bfloat162float(wg[d * F_ + f]), a); b = fmaf(xv, __bfloat162float(wu[d * F_ + f]), b);
    }
    g_fb_h[f] = a * sigmoidf_(a) * b;
}
__global__ void fb_ffn2(const bf16* wd) {
    const int e = blockIdx.x * blockDim.x + threadIdx.x;
    const uint32_t u = fb_best() >> 16, rb = (u & 0x8000u) ? (u & 0x7fffu) : (~u & 0xffffu);
    float a = 0.f;
    for (int f = 0; f < F_; f++) a = fmaf(g_fb_h[f], __bfloat162float(wd[f * D_ + e]), a);
    g_fb_upd[e] = a * sigmoidf_(__uint_as_float(rb << 16));
}
__global__ void fb_seq(const bf16* x, const bf16* cre, const bf16* cim, bf16* out) {
    __shared__ float c[2][S_];
    __shared__ int idx;
    const int t = blockIdx.x, e = threadIdx.x;
    for (int i = e; i < S_; i += D_) { c[0][i] = __bfloat162float(cre[t * S_ + i]); c[1][i] = __bfloat162float(cim[t * S_ + i]); }
    if (e == 0) idx = 0x7fff - (int)(fb_best() & 0x7fffu);
    __syncthreads();
    float y = 0.f;
    for (int s = 0; s < S_; s++)
        y += c[0][s] * __bfloat162float(((const bf16*)g_ab)[s * 1024 + e]) - c[1][s] * __bfloat162float(((const bf16*)g_ab)[s * 1024 + 512 + e]);
    const float g = g_fb_gate[t];
    out[t * D_ + e] = __float2bfloat16(g * y + (1.f - g) * (__bfloat162float(x[t * D_ + e]) + (t == idx ? g_fb_upd[e] : 0.f)));
}

__device__ __forceinline__ void spare_job(const Params& p, Scratch* g, unsigned char* smem, int sp, uint32_t tstart) {
    const int tid = threadIdx.x, warp = tid >> 5, lane = tid & 31;
    if (warp >= 8) {
#pragma unroll 1
        for (int i = 0; i < 16; i++) {
            nap_until(tstart + PFD_T0 + i * (PFD_DT / 2));
            prefetch_l2((const char*)((sp & 2) ? p.dim : p.dre) + (sp & 1) * 262144 + i * 16384 + (tid - 256) * 128);
        }
        return;
    }
    nap_until(tstart + SUM_T0 - 2000);
    const uint32_t e1 = ld_relaxed(g->epoch + NCTA + sp) + 1u, par = e1 & 1u;
    const uint32_t u = best_key(g->keys + warp * NCTA, par) >> 16;
    const float rs = sigmoidf_(__uint_as_float(((u & 0x8000u) ? (u & 0x7fffu) : (~u & 0xffffu)) << 16));
    nap_until(tstart + SUM_T0);
    uint32_t n = 0;
#pragma unroll 1
    while ((int)(ld_relaxed(g->phint + (sp * 8 + warp) * 8) - e1 * 14u) < 0) {
        __nanosleep(40);
        if (++n > SPIN_LIMIT) break;
    }
    const unsigned int* src = g->part + warp * 7 * D_ + sp * 128 + lane * 4;
    uint4 v[7];
#pragma unroll 1
    while (true) {
        uint32_t bad = 0;
#pragma unroll
        for (int i = 0; i < 7; i++) v[i] = ld_relaxed4(src + i * D_);
#pragma unroll
        for (int i = 0; i < 7; i++) bad |= (v[i].x ^ par) | (v[i].y ^ par) | (v[i].z ^ par) | (v[i].w ^ par);
        if (!__any_sync(0xffffffffu, bad & 1u)) break;
        if (++n > SPIN_LIMIT) break;
    }
    float4 s = make_float4(0.f, 0.f, 0.f, 0.f);
#pragma unroll
    for (int i = 0; i < 7; i++) {
        s.x += __uint_as_float(v[i].x); s.y += __uint_as_float(v[i].y);
        s.z += __uint_as_float(v[i].z); s.w += __uint_as_float(v[i].w);
    }
    float* acc = (float*)smem;
    *(float4*)&acc[warp * 128 + lane * 4] = s;
    named_bar(1, 256);
    if (tid < 128) {
        float t = 0.f;
#pragma unroll
        for (int i = 0; i < 8; i++) t += acc[i * 128 + tid];
        st_relaxed(&g->upd[sp * 128 + tid], tagf(t * rs, par));
        if (tid == 0) st_relaxed(g->epoch + NCTA + sp, e1);
    }
}

__device__ __forceinline__ int ffn_pair(int role) { return role - __popcll(NOFFN_MASK & ((1ull << role) - 1)); }
__device__ __forceinline__ int other(int i, int tn) { return i + (i >= tn); }
__device__ __forceinline__ int dcol(int p, int tn) { return p < 2 ? tn * 128 + p * 64 : other((p - 2) % 3, tn) * 128 + (p >= 5 ? 64 : 0); }

template <int H>
__device__ __forceinline__ void fetch_job(const Params& p, Scratch* g, unsigned char* smem, uint32_t sb, int cta, int i, uint32_t par) {
    const int lane = threadIdx.x & 31, comp = cta & 1;
    const int j = other(i, (cta >> 1) & 3), src = (cta & ~6) + 2 * j;
    const int slot = i == 0 ? 29 % NST : i - 1;
    const uint32_t land = sb + B_LAND + 8 * (3 * H + i);
    uint32_t ph = 0, th;
    mbar_expect_tx_elect(land, 8192);
    if (H == 0) {
        mbar_wait(sb + B_S0, 0);
        const uint32_t t0 = clk();
        if (i == 0) {
            mbar_wait(sb + B_FULL + 8 * (31 % NST), (31 / NST) & 1);
            const uint32_t t1 = t0 + max(clk() - t0, 180u) - 180u;
            asm volatile("{.reg .pred p; .reg .b64 t; setp.eq.b32 p, %3, 0; mov.b64 t, {%1, %2}; @p st.relaxed.gpu.global.b64 [%0], t;}"
                         ::"l"(g->stamp + cta * 32), "r"((t1 & ~1u) | par), "r"(gtime()), "r"(lane) : "memory");
        }
        until(t0 + SDEL);
        uint32_t gt;
#pragma unroll 1
        for (uint32_t n = 0; n < SPIN_LIMIT; n++) {
            asm volatile("{.reg .b64 t; ld.relaxed.gpu.global.b64 t, [%2]; mov.b64 {%0,%1}, t;}" : "=r"(th), "=r"(gt) : "l"(g->stamp + src * 32) : "memory");
            if (!__any_sync(0xffffffffu, (th ^ par) & 1u)) break;
        }
        const uint32_t ns = min(gtime() - gt, 4096u), now = clk();
        if (now - th >= 8192u) th = now - (ns + (ns >> 1) + (ns >> 4));
        th += SG * j;
        if (lane == 0) { *(volatile uint32_t*)(smem + M_TH + 4 * i) = th; mbar_arrive(sb + B_TH + 8 * i); }
        __syncwarp();
    } else {
        mbar_wait(sb + B_TH + 8 * i, 0);
        th = lds32(sb + M_TH + 4 * i);
    }
    mbar_wait(sb + B_EA, 0);
#pragma unroll 1
    for (int c = 0; c < 2; c++) {
        const uint32_t dst = sb + slot * 16384 + (c ? NST * 16384 + H * 8192 : (comp ^ H) * 8192);
        if (c != H) mbar_wait(sb + B_EMPTY + 8 * slot, i != 0);
        until(th + (c ? (H ? L_RD1 : L_RD0) : (H ? E_RD1 : E_RD0)));
#pragma unroll 1
        for (uint32_t r = 0; r < SPIN_LIMIT; r++) {
            tma2d_elect(dst, &p.mF, 0, (src * 2 + (comp ^ c)) * 128 + H * 64, land);
            mbar_wait(land, ph);
            ph ^= 1;
            const uint32_t a = dst + (lane >> 2) * 132 + (lane & 3) * 32;
            uint32_t v[8], m0 = 0, m1 = ~0u;
#pragma unroll
            for (int k = 0; k < 8; k++) v[k] = lds32(a + k * 1024);
#pragma unroll
            for (int k = 0; k < 8; k++) { m0 |= v[k]; m1 &= v[k]; }
            if (__all_sync(0xffffffffu, (par ? m1 : ~m0) & 1u)) break;
            mbar_expect_tx_elect(land, 8192);
        }
        mbar_arrive_if(sb + B_VAL + 8 * (6 * c + 3 * H + i), lane == 0);
        if (c == 0) mbar_expect_tx_elect(land, 8192);
    }
}

__global__ void __cluster_dims__(2, 1, 1) __launch_bounds__(NTHREADS, 1)
fused_kernel(const char* pc0, const char* pc1, const char* px, char* pout, Scratch* g, const __grid_constant__ Params p) {
    extern __shared__ __align__(1024) unsigned char smem[];
    const uint32_t sb = smem_u32(smem);
    const int tid = threadIdx.x, warp = tid >> 5, lane = tid & 31;
    const int rank = blockIdx.x & 1;
    {
        const uint32_t b = blockIdx.x & 127;
        const char* u0 = (rank ? pc1 : pc0) + (b >> 1) * (32 * S_ * 2);
        const char* u1 = px + b * 512 - 4096;
        asm volatile("{.reg .pred p, q; .reg .b64 a; .reg .b32 t; setp.lt.u32 p, %2, 32; mad.wide.u32 a, %2, 4096, %0; @p prefetch.global.L2 [a];"
                     " sub.u32 t, %2, 32; setp.lt.u32 q, t, 4; mad.wide.u32 a, %2, 128, %1; @q prefetch.global.L2 [a];}" ::"l"(u0), "l"(u1), "r"(tid));
    }
    const uint32_t tstart = clk();
    uint32_t smid;
    asm volatile("mov.u32 %0, %%smid;" : "=r"(smid));
    const int u = smid >> 1, v7 = ((u - 32) * 37) >> 8;
    const int tn = sel(u >> 3, sel(v7, u - 62, u < 60), u < 32);
    const int tm = sel(u & 7, sel(u - 23 - 7 * v7, 8, u < 60), u < 32);
    const bool spare = tn < 0;
    const int role = tm * 4 + tn, cta = role * 2 + rank;
    const int comp = rank;
    const CUtensorMap* mC = comp ? &p.mCim : &p.mCre;
#define ARM(j) do { mbar_init(sb + B_FULL + 8 * (j), 1); mbar_expect_tx(sb + B_FULL + 8 * (j), 32768); } while (0)
#define FIRST(j) do { tma2d(sb + a_addr(j), mC, (j) * 64, tm * 128, sb + B_FULL + 8 * (j));                        \
                      tma3d(sb + b_addr(j), &p.mX2, (j) * 64, tn * 2, sb + B_FULL + 8 * (j)); } while (0)
    if (tid == 384) {
        ARM(0);
        if (!spare) FIRST(0);
    }
    const int wu = __shfl_sync(0xffffffffu, warp, 0);
    if (wu < 12) {
        if (lane == 0) {
            mbar_init(sb + B_EMPTY + 8 * wu, 2);
            mbar_init(sb + B_VD + 8 * wu, wu ? 1 : 4);
#pragma unroll
            for (int i = 24; i < NBAR; i += 12) if (i + 12 <= NBAR || wu < NBAR - i) mbar_init(sb + B_EMPTY + 8 * (i + wu), 1);
            if (wu >= 1 && wu < 4) mbar_expect_tx(sb + B_VD + 8 * wu, wu < 3 ? 8192 : 256);
        }
        asm volatile("fence.mbarrier_init.release.cluster;" ::: "memory");
        __syncwarp();
        asm volatile("barrier.cluster.arrive.relaxed.aligned;" ::: "memory");
        if (spare) {
            spare_job(p, g, smem, smid & 3, tstart);
        } else if (wu >= 8) {
            asm volatile("setmaxnreg.dec.sync.aligned.u32 " STR(RS_) ";");
            asm volatile("barrier.cluster.wait.acquire.aligned;" ::: "memory");
            const int t = tid - 256, w = wu - 8, fr = ffn_pair(role);
            const bool ffn = !((NOFFN_MASK >> role) & 1);
            nap_until(tstart + SIDE_T0);
            const uint4 gw0 = ldg_nc_off<0>(p.gate_w + lane * 8), gw1 = ldg_nc_off<512>(p.gate_w + lane * 8);
            const uint4 rw0 = ldg_nc_off<0>(p.w_r + lane * 8), rw1 = ldg_nc_off<512>(p.w_r + lane * 8);
            const uint32_t par = ~ld_relaxed(g->epoch + cta) & 1u;
            nap_until(tstart + ROUTER_T0 + (2 * w + rank) * ROUTER_DT);
            {
                const int row0 = cta * 16 + w * 4;
                const char* xp = px + (uint32_t)row0 * (D_ * 2) + lane * 16;
                uint4 xa[4], xb[4];
                xa[0] = ldg_nc_off<0>(xp);    xb[0] = ldg_nc_off<512>(xp);  xa[1] = ldg_nc_off<1024>(xp); xb[1] = ldg_nc_off<1536>(xp);
                xa[2] = ldg_nc_off<2048>(xp); xb[2] = ldg_nc_off<2560>(xp); xa[3] = ldg_nc_off<3072>(xp); xb[3] = ldg_nc_off<3584>(xp);
                float a[8];
#pragma unroll
                for (int i = 0; i < 4; i++) {
                    const uint32_t xv[8] = {xa[i].x, xa[i].y, xa[i].z, xa[i].w, xb[i].x, xb[i].y, xb[i].z, xb[i].w};
                    const uint32_t gv[8] = {gw0.x, gw0.y, gw0.z, gw0.w, gw1.x, gw1.y, gw1.z, gw1.w};
                    const uint32_t rv[8] = {rw0.x, rw0.y, rw0.z, rw0.w, rw1.x, rw1.y, rw1.z, rw1.w};
                    float uu = 0.f, vv = 0.f;
#pragma unroll
                    for (int j = 0; j < 8; j++) {
                        uu = fmaf(bflo(xv[j]), bflo(gv[j]), uu); uu = fmaf(bfhi(xv[j]), bfhi(gv[j]), uu);
                        vv = fmaf(bflo(xv[j]), bflo(rv[j]), vv); vv = fmaf(bfhi(xv[j]), bfhi(rv[j]), vv);
                    }
                    a[i] = uu; a[4 + i] = vv;
                }
                halve<4, 16>(a); halve<2, 8>(a); halve<1, 4>(a);
                {
                    const float b1 = __shfl_xor_sync(0xffffffffu, a[0], 1), b2 = __shfl_xor_sync(0xffffffffu, a[0], 2),
                                b3 = __shfl_xor_sync(0xffffffffu, a[0], 3);
                    a[0] = (a[0] + b1) + (b2 + b3);
                }
                const int row = row0 + ((lane >> 2) & 3);
                const uint32_t best = __reduce_max_sync(0xffffffffu, lane >= 16 && (lane & 3) == 0 ? router_key(a[0], row) : 0u);
                if (lane <= 16 && (lane & 3) == 0)
                    *(volatile uint32_t*)(smem + M_RED + (lane < 16 ? w * 16 + lane : 64 + w * 4)) = lane < 16 ? tagf(sigmoidf_(a[0]), par) : best;
                named_bar(1, 128);
                if (t < 8) {
                    const uint4 k = lds128(sb + M_RED + 64);
                    asm volatile("{.reg .b32 old; atom.relaxed.gpu.global.exch.b32 old, [%0], %1;}"
                                 ::"l"(g->keys + t * NCTA + cta), "r"(max(max(k.x, k.y), max(k.z, k.w)) | (par << 15)) : "memory");
                }
                if (w == 1 && lane < 16) st_relaxed(g->gate + cta * 16 + lane, lds32(sb + M_RED + lane * 4));
            }
            uint32_t vd[32];
            if (ffn) {
                mbar_wait(sb + B_FFN + 24, 0);
#pragma unroll
                for (int j = 0; j < 32; j++) vd[j] = lds32(sb + R6 + ((j >> 3) & 1) * 16384 + (2 + (j >> 4)) * 4096 + (j & 7) * 512 + t * 4);
                mbar_arrive_warp(sb + B_VD);
            }
            mbar_wait(sb + B_GATE, 0);
            const int idx = 0x7fff - (int)(*(volatile uint32_t*)(smem + M_KEY) & 0x7fffu);
            if (ffn) {
                float a[16];
#pragma unroll
                for (int i = 0; i < 16; i++) a[i] = 0.f;
#pragma unroll 1
                for (int qu = 0; qu < 4; qu++) {
                    mbar_wait(sb + B_FFN + 8 * qu, qu == 3);
#pragma unroll
                    for (int i = 2 * qu; i < 2 * qu + 2; i++) {
                        const float xs = __bfloat162float(((const bf16*)(smem + M_UPD))[32 * i + (t >> 2)]);
                        const uint4 vg = lds128(sb + R6 + i * 2048 + t * 16);
                        const uint4 vu = lds128(sb + R6 + 16384 + i * 2048 + t * 16);
                        const uint32_t g4[4] = {vg.x, vg.y, vg.z, vg.w};
                        const uint32_t u4[4] = {vu.x, vu.y, vu.z, vu.w};
#pragma unroll
                        for (int j = 0; j < 4; j++) {
                            a[2 * j] = fmaf(xs, bflo(g4[j]), a[2 * j]);         a[2 * j + 1] = fmaf(xs, bfhi(g4[j]), a[2 * j + 1]);
                            a[8 + 2 * j] = fmaf(xs, bflo(u4[j]), a[8 + 2 * j]); a[9 + 2 * j] = fmaf(xs, bfhi(u4[j]), a[9 + 2 * j]);
                        }
                    }
                }
                named_bar(1, 128);
                mbar_arrive_if(sb + B_R6, t == 0);
                halve<8, 16>(a); halve<4, 8>(a); halve<2, 4>(a);
                float* red = (float*)(smem + M_UPD);
                *(float2*)&red[w * 64 + (lane >> 4) * 32 + (lane & 3) * 8 + ((lane >> 2) & 3) * 2] = make_float2(a[0], a[1]);
                named_bar(1, 128);
                const float sg = red[lane] + red[64 + lane] + red[128 + lane] + red[192 + lane];
                const float su = red[32 + lane] + red[96 + lane] + red[160 + lane] + red[224 + lane];
                if (w < 2) {
                    asm volatile("st.async.weak.shared::cluster.mbarrier::complete_tx::bytes.f32 [%0], %1, [%2];"
                                 ::"r"(mapa(sb + M_HX + t * 4, rank ^ 1)), "f"(w ? su : sg), "r"(mapa(sb + B_HX, rank ^ 1)) : "memory");
                }
                named_bar(1, 128);
                mbar_wait(sb + B_HX, 0);
                const float pg = ((const float*)(smem + M_HX))[lane], pu = ((const float*)(smem + M_HX))[32 + lane];
                const float gs = sg + pg, us = su + pu;
                float* hrow = red + w * 32;
                hrow[lane] = gs * sigmoidf_(gs) * us;
                __syncwarp();
                float o0 = 0.f, o1 = 0.f;
#pragma unroll
                for (int j4 = 0; j4 < 8; j4++) {
                    const float4 hv = *(const float4*)&hrow[j4 * 4];
                    o0 = fmaf(hv.x, bflo(vd[4 * j4]), o0);     o1 = fmaf(hv.x, bfhi(vd[4 * j4]), o1);
                    o0 = fmaf(hv.y, bflo(vd[4 * j4 + 1]), o0); o1 = fmaf(hv.y, bfhi(vd[4 * j4 + 1]), o1);
                    o0 = fmaf(hv.z, bflo(vd[4 * j4 + 2]), o0); o1 = fmaf(hv.z, bfhi(vd[4 * j4 + 2]), o1);
                    o0 = fmaf(hv.w, bflo(vd[4 * j4 + 3]), o0); o1 = fmaf(hv.w, bfhi(vd[4 * j4 + 3]), o1);
                }
                asm volatile("st.relaxed.gpu.global.v2.u32 [%0], {%1,%2};" ::"l"(&g->part[fr * D_ + rank * 256 + t * 2]),
                             "r"(tagf(o0, par)), "r"(tagf(o1, par)) : "memory");
                if (lane == 0) asm volatile("red.relaxed.gpu.global.add.u32 [%0], 1;" ::"l"(g->phint + ((rank * 2 + (w >> 1)) * 8 + fr / 7) * 8) : "memory");
            }
            if (!ffn) mbar_arrive_if(sb + B_R6, t == 0);
            if (w < 3) {
                fetch_job<1>(p, g, smem, sb, cta, w, par);
            } else {
                if (lds32(sb + M_ROLE) != (uint32_t)role) __trap();
                if ((idx >> 6) == 2 * tm + comp) {
                    const uint4 u4 = wait_tags(g->upd + tn * 128 + lane * 4, par);
                    const float og = 1.f - ((const float*)(smem + M_G))[idx & 127];
                    *(float4*)(smem + M_RED + lane * 16) = make_float4(og * __uint_as_float(u4.x), og * __uint_as_float(u4.y),
                                                                       og * __uint_as_float(u4.z), og * __uint_as_float(u4.w));
                    mbar_arrive_warp(sb + B_SIDE);
                }
            }
        } else {
            const int wg = wu >> 2;
            const uint32_t sbd = (sb & 0x3FFFF) >> 4;
            const bool lead = (tid & 127) == 0;
            const bool early = wg == comp;
            const int q = lane & 3;
            const int r0 = (warp & 3) * 16 + (lane >> 2);
            float acc[64];
            const uint32_t da0 = sbd + 0x10000 + wg * 512, db0 = sbd + 0x2000000, dd0 = sbd + 0x10000;
            const uint32_t rE = mapa(sb + B_EMPR, rank ^ 1);
#define WAITFULL(s) mbar_wait(sb + B_FULL + 8 * ((s) % NST), ((s) / NST) & 1)
#define TESTFULL(s) mbar_test(sb + B_FULL + 8 * ((s) % NST), ((s) / NST) & 1)
#define WAITD(pos) do { if ((pos) >= 4) mbar_wait(sb + B_DL + 8 * ((pos) & 3), 0); else if ((pos) >= 2) mbar_wait(sb + B_D6, 0); else WAITFULL(32); } while (0)
#define MMA_A(s, kk) wgmma128(acc, desc_lo(da0 + a_addr(s) / 16 + (kk) * 2), desc_lo(db0 + b_addr(s) / 16 + (kk) * 128), 1)
            asm volatile("setmaxnreg.inc.sync.aligned.u32 " STR(RC) ";");
            asm volatile("barrier.cluster.wait.acquire.aligned;" ::: "memory");
            WAITFULL(0);
            wg_fence();
#pragma unroll
            for (int kk = 0; kk < 4; kk++) wgmma128(acc, desc_lo(da0 + kk * 2), desc_lo(db0 + b_addr(0) / 16 + kk * 128), kk != 0);
            wg_commit();
            int slot = 1, ph = 0, pslot = 0;
            const uint32_t ooff = (uint32_t)((tm * 128 + wg * 64 + r0) * D_ + tn * 128 + q * 8) * 2u;
            uint32_t* fout = g->frag + (cta * 2 + wg) * 4096 + (warp & 3) * 128 + lane;
            uint32_t tagm[4];
#pragma unroll
            for (int c = 0; c < 4; c++) tagm[c] = (lane & 7) == (warp & 1) * 4 + c;
            const char* xp = px + ooff;
            asm volatile("" : "+r"(tagm[0]), "+r"(tagm[1]), "+r"(tagm[2]), "+r"(tagm[3]), "+l"(xp), "+l"(fout));
            uint4 w[8];
#pragma unroll
            for (int i = 0; i < 8; i++) w[i] = make_uint4(0, 0, 0, 0);
#pragma unroll
            for (int part = 0; part <= XN; part++) {
                if (part) {
#pragma unroll
                    for (int i = (part - 1) * 8 / XN; i < part * 8 / XN; i++) ldg_nc_if(w[i], xp + (i & 1) * 8192 + (i >> 1) * 64, early);
                }
#pragma unroll 1
                for (int step = part ? XLD + (part - 1) * XD : 1; step < (part < XN ? XLD + part * XD : SP0); step++) {
                    mbar_wait(sb + B_FULL + 8 * slot, ph);
                    const uint32_t a = da0 + slot * 1024, b = db0 + b_addr(0) / 16 + slot * 1024;
                    wg_fence();
                    wgmma128(acc, desc_lo(a), desc_lo(b), 1);
                    wg_commit();
                    wg_wait<1>();
                    mbar_arrive_if(sb + B_EMPTY + 8 * pslot, lead);
                    mbar_arrive_cluster_if(rE + 8 * pslot, lead);
                    pslot = slot;
                    if (++slot == NST) { slot = 0; ph ^= 1; }
                    wg_fence();
#pragma unroll
                    for (int kk = 1; kk < 4; kk++) wgmma128(acc, desc_lo(a + kk * 2), desc_lo(b + kk * 128), 1);
                    wg_commit();
                }
            }
            uint32_t par;
            float g0, g1;
#define GATES() do { par = lds32(sb + M_PAR); g0 = __uint_as_float(lds32(sb + M_G + (wg * 64 + r0) * 4)); g1 = __uint_as_float(lds32(sb + M_G + (wg * 64 + r0 + 8) * 4)); } while (0)
            if (early) {
                WAITFULL(SP0);
                wg_fence();
                MMA_A(SP0, 0); MMA_A(SP0, 1);
                wg_commit();
                wg_wait<1>();
                mbar_arrive_if(sb + B_EMPTY + 8 * ((SP0 - 1) % NST), lead);
                bool ok = TESTFULL(SP0 + 1);
                MMA_A(SP0, 2); MMA_A(SP0, 3);
                wg_commit();
#pragma unroll
                for (int s = SP0 + 1; s < 32; s++) {
                    if (!ok) { WAITFULL(s); if (s == 29) mbar_wait(sb + B_GATE, 0); }
                    wg_fence();
                    MMA_A(s, 0); MMA_A(s, 1);
                    if (s == 29) GATES();
                    if (s >= 30) { wg_commit(); wg_wait<1>(); mbar_arrive_if(sb + (s == 30 ? B_S0 : B_S1), lead); wg_fence(); }
                    if (s < 31) ok = TESTFULL(s + 1) & (s != 28 || mbar_test(sb + B_GATE, 0));
                    MMA_A(s, 2); MMA_A(s, 3);
                    wg_commit();
                }
                wg_wait<0>();
                mbar_arrive_if(sb + B_EA, lead);
            } else {
                wg_wait<0>();
                mbar_arrive_if(sb + B_EMPTY + 8 * ((SP0 - 1) % NST), lead);
#pragma unroll
                for (int s = SP0; s < 32; s++) WAITFULL(s);
                mbar_wait(sb + B_GATE, 0);
                GATES();
                mbar_wait(sb + B_S1, 0);
                wg_fence();
#pragma unroll
                for (int s = SP0; s < 32; s++) {
                    MMA_A(s, 0); MMA_A(s, 1);
                    if (s > SP0) {
                        wg_commit();
                        wg_wait<1>();
                        mbar_arrive_n_if<2>(sb + B_EMPTY + 8 * ((s - 1) % NST), lead);
                        if (s == 31) mbar_arrive_if(sb + B_S3, lead);
                        if (s == 30) WAITD(0);
                        wg_fence();
                    }
                    MMA_A(s, 2); MMA_A(s, 3);
                    wg_commit();
                }
                wg_wait<0>();
                mbar_arrive_n_if<2>(sb + B_EMPTY + 8 * (31 % NST), lead);
            }
            fence_regs<0, 64>(acc);
            uint4 f[8];
#define TAG(v, c) (((v) & ~tagm[c]) | (par & tagm[c]))
#define PACK(k) f[k] = make_uint4(TAG(pack_bf16(acc[8 * (k)], acc[8 * (k) + 1]), 0), TAG(pack_bf16(acc[8 * (k) + 2], acc[8 * (k) + 3]), 2), \
                                  TAG(pack_bf16(acc[8 * (k) + 4], acc[8 * (k) + 5]), 1), TAG(pack_bf16(acc[8 * (k) + 6], acc[8 * (k) + 7]), 3))
#define SEND(k) do { st_relaxed(fout + 512 * (k), f[k].x); st_relaxed(fout + 512 * (k) + 32, f[k].z);                        \
                     st_relaxed(fout + 512 * (k) + 64, f[k].y); st_relaxed(fout + 512 * (k) + 96, f[k].w); } while (0)
#define OWN(k) wgmma128rs(acc, f[k], desc_lo(dd0 + d_addr((k) >> 2) / 16 + ((k) & 3) * 2), (k) != 0)
            const uint32_t dfa = sbd + 0x80000 + (early ? comp * 512 : NST * 1024), dfb = sbd + 0x80000 + (early ? (1 - comp) * 512 : NST * 1024 + 512);
#define MMA_F(pos, kk) wgmma128<0>(acc, (uint64_t)(((pos) < 5 ? dfa : dfb) + a_addr(29 + ((pos) - 2) % 3) / 16 + (kk) * 128) | (0x10ull << 32), \
                                   desc_lo(dd0 + d_addr(pos) / 16 + (kk) * 2), 1)
#define WAITF(pos) mbar_wait(vb + 8 * ((pos) - 2), 0)
            const uint32_t vb = sb + B_VAL + (early ? 0 : 48);
            const uint32_t ts = clk();
            if (early) {
                PACK(0); SEND(0); PACK(1); SEND(1); PACK(2); SEND(2); PACK(3); SEND(3);
                until(ts);
                PACK(4); PACK(5); PACK(6); PACK(7);
                const float s0 = comp ? -g0 : g0, s1 = comp ? -g1 : g1;
                const uint32_t og0 = pack_bf16(1.f - g0, 1.f - g0), og1 = pack_bf16(1.f - g1, 1.f - g1);
                const int rr = 0x7fff - (int)(lds32(sb + M_KEY) & 0x7fffu) - (tm * 128 + wg * 64 + r0);
#pragma unroll
                for (int k = 4; k < 8; k++) {
                    if (k < ESEND) { until(ts + ET1 + (k - 4) * STP); SEND(k); }
#pragma unroll
                    for (int i = 2 * k - 8; i < 2 * k - 6; i++) {
                        const uint32_t og = (i & 1) ? og1 : og0;
                        w[i] = make_uint4(hmul2_bf16(og, w[i].x), hmul2_bf16(og, w[i].y), hmul2_bf16(og, w[i].z), hmul2_bf16(og, w[i].w));
                        asm volatile("" : "+r"(w[i].x), "+r"(w[i].y), "+r"(w[i].z), "+r"(w[i].w));
                    }
                }
                WAITD(0);
                mbar_wait(sb + B_S3, 0);
                wg_fence();
#pragma unroll
                for (int k = 0; k < 8; k++) {
                    OWN(k);
                    if (k >= 1 && k + ESEND - 1 < 8) { wg_commit(); until(ts + ET1 + (k + ESEND - 5) * STP); SEND(k + ESEND - 1); wg_fence(); }
                }
                wg_commit();
                WAITD(2);
                bool ok = false;
#pragma unroll
                for (int pos = 2; pos < 8; pos++) {
                    if (!ok) {
                        if (pos >= 4) WAITD(pos);
                        WAITF(pos);
                    }
                    wg_fence();
                    MMA_F(pos, 0); MMA_F(pos, 1);
                    if (pos == 6) { wg_commit(); wg_wait<1>(); mbar_arrive_cluster_if(mapa(sb + B_XF, rank ^ 1), lead); wg_fence(); }
                    if (pos == 7) mbar_arrive_if(sb + B_S2, lead);
                    if (pos < 7) ok = mbar_test(vb + 8 * (pos - 1), 0) & (pos < 3 || mbar_test(sb + B_DL + 8 * (pos - 3), 0));
                    MMA_F(pos, 2); MMA_F(pos, 3);
                    wg_commit();
                }
                const uint32_t xd = mapa(sb + a_addr(29) + (tid & 127) * 16, rank ^ 1), xb = mapa(sb + B_X, rank ^ 1);
                if (rr == 0 || rr == 8) {
                    mbar_wait(sb + B_SIDE, 0);
#pragma unroll
                    for (int j = 0; j < 4; j++) {
                        const float4 ua = *(const float4*)(smem + M_RED + j * 128 + q * 32), ub = *(const float4*)(smem + M_RED + j * 128 + q * 32 + 16);
                        uint4 v = rr ? w[2 * j + 1] : w[2 * j];
                        v = make_uint4(pack_bf16(ua.x + bflo(v.x), ua.y + bfhi(v.x)), pack_bf16(ua.z + bflo(v.y), ua.w + bfhi(v.y)),
                                       pack_bf16(ub.x + bflo(v.z), ub.y + bfhi(v.z)), pack_bf16(ub.z + bflo(v.w), ub.w + bfhi(v.w)));
                        if (rr) w[2 * j + 1] = v; else w[2 * j] = v;
                    }
                }
                __syncwarp();
                mbar_wait(sb + B_XF, 0);
                wg_wait<0>();
                fence_regs<0, 64>(acc);
                keep_regs<0, 8>(f);
#pragma unroll
                for (int i = 0; i < 8; i++) {
                    const uint4 z = scale_add((i & 1) ? s1 : s0, acc, 16 * (i >> 1) + 2 * (i & 1), w[i]);
                    st_async16(xd + i * 2048, z.x, z.y, z.z, z.w, xb + 2 * (i & 4));
                    if (i & 1) until(ts);
                }
            } else {
                PACK(0); PACK(1); PACK(2); PACK(3); PACK(4); PACK(5); PACK(6); PACK(7);
                wg_fence();
#pragma unroll
                for (int k = 0; k < 8; k++) {
                    OWN(k);
                    if ((k & 1) && k / 2 < LSEND) { wg_commit(); until(ts + LT0 + k / 2 * LTP); SEND(k / 2); wg_fence(); }
                }
                wg_commit();
#pragma unroll
                for (int k = LSEND; k < 8; k++) { until(ts + LT0 + k * LTP); SEND(k); }
                float s0 = comp ? -g0 : g0, s1 = comp ? -g1 : g1;
                uint32_t xs = sb + a_addr(29) + (tid & 127) * 16;
                char* op = pout + ooff;
                asm volatile("" : "+f"(s0), "+f"(s1), "+r"(xs), "+l"(op));
                WAITF(2);
                mbar_wait(sb + B_S2, 0);
                bool there = false, there1 = false, ok = true;
#pragma unroll
                for (int pos = 2; pos < 8; pos++) {
                    if (!ok) WAITF(pos);
                    wg_fence();
                    MMA_F(pos, 0);
                    if (pos == XPOS) there = mbar_test(sb + B_X, 0);
                    MMA_F(pos, 1);
                    if (pos == XPOS) {
#pragma unroll
                        for (int i = 0; i < 4; i++) lds128_if(w[i], xs + i * 2048, there);
                    }
                    if (pos < 7) ok = mbar_test(vb + 8 * (pos - 1), 0);
                    MMA_F(pos, 2);
                    if (pos == 7) there1 = mbar_test(sb + B_X + 8, 0);
                    MMA_F(pos, 3);
                    wg_commit();
                }
#pragma unroll
                for (int i = 4; i < 8; i++) lds128_if(w[i], xs + i * 2048, there1);
#pragma unroll
                for (int h = 0; h < 2; h++) {
                    if (!(h ? there1 : there)) {
                        mbar_wait(sb + B_X + 8 * h, 0);
#pragma unroll
                        for (int i = 4 * h; i < 4 * h + 4; i++) w[i] = lds128(xs + i * 2048);
                    }
                    if (h == 0) {
                        wg_wait<0>();
                        fence_regs<0, 64>(acc);
                        keep_regs<0, 8>(f);
                    }
#pragma unroll
                    for (int i = 4 * h; i < 4 * h + 4; i++) {
                        stg_off<0>(op + (i & 1) * 8192 + (i >> 1) * 64, scale_add((i & 1) ? s1 : s0, acc, 16 * (i >> 1) + 2 * (i & 1), w[i]));
                        __syncwarp();
                    }
                }
            }
        }
    } else {
#define STEP0(j) do { tma2d_elect(sb + (j) * 16384, mC, (j) * 64, tm * 128, sb + B_FULL + 8 * (j));                            \
                      tma3d_elect(sb + (NST + (j)) * 16384, &p.mX2, (j) * 64, tn * 2, sb + B_FULL + 8 * (j)); } while (0)
        if (wu >= 14) {
            const uint32_t b = blockIdx.x;
            const char* q = wu == 14 ? (rank ? pc1 : pc0) + (uint32_t)((b >> 1) * 32 + lane) * (S_ * 2) + 128 : px + (uint32_t)(b * 4 + lane) * 128 + 65536;
            until(tstart + P_1);
            if (b < 128 && (wu == 14 || lane < 4)) prefetch_l2(q);
        } else if (wu == 13 && !spare) {
            if (lane == 0) ARM(1);
            __syncwarp();
            until(tstart + T_1);
            STEP0(1);
        }
        if (lane == 0) ARM(wu - 10);
        asm volatile("fence.mbarrier_init.release.cluster;" ::: "memory");
        __syncwarp();
        asm volatile("barrier.cluster.arrive.relaxed.aligned;" ::: "memory");
        if (spare) return;
        asm volatile("setmaxnreg.dec.sync.aligned.u32 " STR(RU) ";");
        if (wu < 14) {
            until(tstart + T_2 + (wu - 12) * PACE);
            STEP0(wu - 10);
        }
        asm volatile("barrier.cluster.wait.acquire.aligned;" ::: "memory");
        if (wu == 13) {
            const CUtensorMap* mD = comp ? &p.mDim : &p.mDre;
#pragma unroll
            for (int step = 4; step < NST; step++) {
                until(tstart + T_2 + (step - 2) * PACE);
                tma3d_elect(sb + b_addr(step), &p.mX2, step * 64, tn * 2, sb + B_FULL + 8 * step);
            }
#pragma unroll 1
            for (int step = NST, slot = 0, ph = 0; step < 32; step++) {
                mbar_wait(sb + B_EMPTY + 8 * slot, ph);
                mbar_wait(sb + B_EMPR + 8 * slot, ph);
                tma2d_pair_elect(sb + b_addr(0) + slot * 16384 + rank * 8192, &p.mX, tn * 128 + rank * 64, step * 64, sb + B_FULL + 8 * slot);
                if (++slot == NST) { slot = 0; ph ^= 1; }
            }
#pragma unroll
            for (int c = 0; c < 4; c += 2) {
                const uint32_t bar = sb + (c ? B_D6 : B_FULL + 8 * (32 % NST));
                if (c) mbar_wait(sb + B_R6, 0);
                else mbar_wait(sb + B_EMPTY + 8 * (26 % NST), (26 / NST) & 1);
                tma5d_elect(sb + d_addr(c), mD, dcol(c, tn), tn * 4, bar);
                tma5d_elect(sb + d_addr(c + 1), mD, dcol(c + 1, tn), tn * 4, bar);
                mbar_expect_tx_elect(bar, 32768);
            }
#pragma unroll
            for (int c = 0; c < 4; c++) mbar_expect_tx_elect(sb + B_DL + 8 * c, 16384);
            mbar_wait(sb + B_S1, 0);
            const uint32_t tq = clk();
#pragma unroll
            for (int c = 0; c < 4; c++) {
                if (!(c & 1)) mbar_wait(sb + B_EMPTY + 8 * ((27 + c / 2) % NST), ((27 + c / 2) / NST) & 1);
                if (c) until(tq + (c == 1 ? T_D5 : c == 2 ? T_D6 : T_D7));
                tma5d_elect(sb + d_addr(4 + c), mD, dcol(4 + c, tn), tn * 4, sb + B_DL + 8 * c);
            }
        } else {
            if (wu == 12) {
#pragma unroll
                for (int step = 4; step < NST; step++) {
                    until(tstart + T_2 + (step - 2) * PACE);
                    tma2d_elect(sb + a_addr(step), mC, step * 64, tm * 128, sb + B_FULL + 8 * step);
                }
#pragma unroll 1
                for (int step = NST, slot = 0, ph = 0; step < 32; step++) {
                    mbar_wait(sb + B_EMPTY + 8 * slot, ph);
                    tma2d_elect(sb + slot * 16384, mC, step * 64, tm * 128, sb + B_FULL + 8 * slot);
                    mbar_expect_tx_elect(sb + B_FULL + 8 * slot, 32768);
                    if (++slot == NST) { slot = 0; ph ^= 1; }
                }
            } else if (wu == 14) {
                if (lane == 0) {
                    asm volatile("prefetch.tensormap [%0];" ::"l"(&p.mX) : "memory");
                    asm volatile("prefetch.tensormap [%0];" ::"l"(&p.mF) : "memory");
                    asm volatile("prefetch.tensormap [%0];" ::"l"(comp ? &p.mDim : &p.mDre) : "memory");
                    asm volatile("st.shared::cluster.u32 [%0], %1;" ::"r"(mapa(sb + M_ROLE, rank ^ 1)), "r"(role) : "memory");
                }
                nap_until(tstart + KEY_T0 - 1000);
                const uint32_t epoch = ld_relaxed(g->epoch + cta) + 1u, par = epoch & 1u;
                if (lane < 8) stg_off<0>(g->stamp + cta * 32 + lane * 4, make_uint4(par ^ 1u, 0, 0, 0));
                nap_until(tstart + KEY_T0);
                const uint32_t k = best_key(g->keys + (tm & 7) * NCTA, par);
                const uint4 xr = ldg_nc_off<0>(px + (0x7fff - (k & 0x7fffu)) * (D_ * 2) + rank * 512 + lane * 16);
                const uint4 g4 = wait_tags(g->gate + tm * 128 + lane * 4, par);
                sts128(sb + M_G + lane * 16, make_uint4(g4.x & ~1u, g4.y & ~1u, g4.z & ~1u, g4.w & ~1u));
                sts128(sb + M_UPD + lane * 16, xr);
                if (lane == 0) {
                    *(volatile uint32_t*)(smem + M_KEY) = k;
                    *(volatile uint32_t*)(smem + M_PAR) = par;
                    st_relaxed(g->epoch + cta, epoch);
                }
                mbar_arrive_warp(sb + B_GATE);
            } else {
                const int fr = ffn_pair(role);
                const uint32_t t1 = tstart + FFN_T0 + (rank + ((fr >> 2) & 6)) * (FFN_DT / 8);
                if (!((NOFFN_MASK >> role) & 1)) {
#pragma unroll 1
                    for (int i = 0; i < 12; i++) {
                        const int qu = i < 4 ? 2 + (i >> 1) : (i - 4) >> 1;
                        const uint32_t bar = sb + B_FFN + 8 * (i < 4 ? 3 : qu), dst = sb + R6 + (i & 1) * 16384 + qu * 4096;
                        if (i == 8) mbar_wait(sb + B_VD, 0);
                        if (i == 0 || (i >= 4 && !(i & 1))) mbar_expect_tx_elect(bar, i ? 8192 : 16384);
                        nap_until(t1 + i * FFN_DT);
                        tma2d_elect(dst, i < 4 ? &p.mWd : (i & 1) ? &p.mWu : &p.mWg, i < 4 ? rank * 256 : fr * 32, i < 4 ? fr * 32 + i * 8 : rank * 256 + qu * 64, bar);
                    }
                }
            }
            __syncwarp();
            mbar_wait(sb + B_GATE, 0);
            fetch_job<0>(p, g, smem, sb, cta, wu == 12 ? 2 : wu - 14, lds32(sb + M_PAR));
        }
    }
}

typedef CUresult (*EncodeTiledFn)(CUtensorMap*, CUtensorMapDataType, cuuint32_t, void*, const cuuint64_t*, const cuuint64_t*,
                                  const cuuint32_t*, const cuuint32_t*, CUtensorMapInterleave, CUtensorMapSwizzle,
                                  CUtensorMapL2promotion, CUtensorMapFloatOOBfill);

static void make_map(EncodeTiledFn enc, CUtensorMap* m, const void* base, uint64_t cols, uint64_t rows, uint32_t box_rows,
                     CUtensorMapSwizzle sw = CU_TENSOR_MAP_SWIZZLE_128B, uint32_t box_cols = 64) {
    cuuint64_t dims[2] = {cols, rows};
    cuuint64_t str[1] = {cols * 2};
    cuuint32_t box[2] = {box_cols, box_rows};
    cuuint32_t es[2] = {1, 1};
    enc(m, CU_TENSOR_MAP_DATA_TYPE_BFLOAT16, 2, (void*)base, dims, str, box, es, CU_TENSOR_MAP_INTERLEAVE_NONE,
        sw, CU_TENSOR_MAP_L2_PROMOTION_L2_128B, CU_TENSOR_MAP_FLOAT_OOB_FILL_NONE);
}

static void make_map_chunks(EncodeTiledFn enc, CUtensorMap* m, const void* base, uint64_t rows) {
    cuuint64_t dims[3] = {64, rows, D_ / 64};
    cuuint64_t str[2] = {D_ * 2, 128};
    cuuint32_t box[3] = {64, 64, 2};
    cuuint32_t es[3] = {1, 1, 1};
    enc(m, CU_TENSOR_MAP_DATA_TYPE_BFLOAT16, 3, (void*)base, dims, str, box, es, CU_TENSOR_MAP_INTERLEAVE_NONE,
        CU_TENSOR_MAP_SWIZZLE_128B, CU_TENSOR_MAP_L2_PROMOTION_L2_128B, CU_TENSOR_MAP_FLOAT_OOB_FILL_NONE);
}

static void make_map_perm(EncodeTiledFn enc, CUtensorMap* m, const void* base) {
    cuuint64_t dims[5] = {D_, 2, 4, 4, D_ / 32};
    cuuint64_t str[4] = {D_ * 2, 8 * D_ * 2, 2 * D_ * 2, 32 * D_ * 2};
    cuuint32_t box[5] = {64, 2, 4, 4, 4};
    cuuint32_t es[5] = {1, 1, 1, 1, 1};
    enc(m, CU_TENSOR_MAP_DATA_TYPE_BFLOAT16, 5, (void*)base, dims, str, box, es, CU_TENSOR_MAP_INTERLEAVE_NONE,
        CU_TENSOR_MAP_SWIZZLE_128B, CU_TENSOR_MAP_L2_PROMOTION_L2_128B, CU_TENSOR_MAP_FLOAT_OOB_FILL_NONE);
}

extern "C" void kernel_launch(void* const* d_in, const int* in_sizes, int n_in, void* d_out, int out_size) {
    (void)in_sizes; (void)n_in; (void)out_size;
    static EncodeTiledFn enc = nullptr;
    static bool fused_ok = false;
    static void* scr = nullptr;
    if (!enc) {
        void* fn = nullptr;
        cudaDriverEntryPointQueryResult q;
        cudaGetDriverEntryPoint("cuTensorMapEncodeTiled", &fn, cudaEnableDefault, &q);
        enc = (EncodeTiledFn)fn;
        cudaGetSymbolAddress(&scr, g_scr);
        cudaFuncSetAttribute(fused_kernel, cudaFuncAttributeMaxDynamicSharedMemorySize, SMEM_BYTES);
        int dev = 0, nsm = 0, ncl = 0;
        cudaGetDevice(&dev);
        cudaDeviceGetAttribute(&nsm, cudaDevAttrMultiProcessorCount, dev);
        cudaLaunchConfig_t cfg = {};
        cfg.gridDim = dim3(132); cfg.blockDim = dim3(NTHREADS); cfg.dynamicSmemBytes = SMEM_BYTES;
        cudaLaunchAttribute at;
        at.id = cudaLaunchAttributeClusterDimension;
        at.val.clusterDim.x = 2; at.val.clusterDim.y = 1; at.val.clusterDim.z = 1;
        cfg.attrs = &at; cfg.numAttrs = 1;
        fused_ok = cudaOccupancyMaxActiveClusters(&ncl, fused_kernel, &cfg) == cudaSuccess && nsm == 132 && ncl == 66;
        (void)cudaGetLastError();
    }
    if (!fused_ok) {
        const bf16* const* in = (const bf16* const*)d_in;
        fb_hidden<<<S_, D_, 0, cudaStreamPerThread>>>(in[0], in[3], in[4], in[10], in[6]);
        fb_ffn1<<<F_ / 128, 128, 0, cudaStreamPerThread>>>(in[0], in[7], in[8]);
        fb_ffn2<<<D_ / 64, 64, 0, cudaStreamPerThread>>>(in[9]);
        fb_seq<<<S_, D_, 0, cudaStreamPerThread>>>(in[0], in[1], in[2], (bf16*)d_out);
        return;
    }
    Params p;
    p.dre = (const bf16*)d_in[3];
    p.dim = (const bf16*)d_in[4];
    p.w_r = (const bf16*)d_in[6];
    p.gate_w = (const bf16*)d_in[10];
    make_map_chunks(enc, &p.mX2, d_in[0], S_);
    make_map(enc, &p.mX, d_in[0], D_, S_, 64);
    make_map(enc, &p.mCre, d_in[1], S_, S_, 128);
    make_map(enc, &p.mCim, d_in[2], S_, S_, 128);
    make_map_perm(enc, &p.mDre, d_in[3]);
    make_map_perm(enc, &p.mDim, d_in[4]);
    make_map(enc, &p.mF, scr, 64, NCTA * 256, 64, CU_TENSOR_MAP_SWIZZLE_NONE);
    make_map(enc, &p.mWg, d_in[7], F_, D_, 64, CU_TENSOR_MAP_SWIZZLE_NONE, 32);
    make_map(enc, &p.mWu, d_in[8], F_, D_, 64, CU_TENSOR_MAP_SWIZZLE_NONE, 32);
    make_map(enc, &p.mWd, d_in[9], D_, F_, 8, CU_TENSOR_MAP_SWIZZLE_NONE, 256);
    fused_kernel<<<132, NTHREADS, SMEM_BYTES, cudaStreamPerThread>>>((const char*)d_in[1], (const char*)d_in[2], (const char*)d_in[0], (char*)d_out, (Scratch*)scr, p);
}
```

```cpp
#include <cuda_runtime.h>
#include <cuda.h>
#include <cuda_bf16.h>
#include <stdint.h>

typedef __nv_bfloat16 bf16;

constexpr int S_ = 2048, D_ = 512, F_ = 1792;
constexpr int NCTA = 128;
constexpr int NTHREADS = 512;
constexpr int NST = 6;
constexpr int SP0 = 27;
constexpr int FFN_CTAS = F_ / 16;
constexpr uint32_t SPIN_LIMIT = 1u << 16;

#define P_1 450
#define T_1 500
#define T_2 1050
#define PACE 420
#define ROUTER_T0 3000
#define ROUTER_DT 280
#define FFN_T0 5200
#define FFN_DT 640
#define XLD 14
#define XN 8
#define XD 1
#define PFD_T0 11900
#define PFD_DT 250
#define SUM_T0 15500
#define ET1 600
#define STP 170
#define ESEND 6
#define LT0 450
#define LTP 170
#define LSEND 3
#define SDEL 280
#define E_RD0 1330
#define E_RD1 2180
#define L_RD0 3300
#define L_RD1 3930
#define SG 130
#define T_D5 1500
#define T_D6 1700
#define T_D7 2400
#define XPOS 7
#define RC 168
#define RS_ 112
#define RU 64
#define KEY_T0 9800
#define NOFFN_MASK 0x00c8800f00000000ull
#define XW 4
#define SIDE_T0 2800
#define STR2(x) #x
#define STR(x) STR2(x)

__host__ __device__ constexpr int a_addr(int s) { return s % NST * 16384; }
__host__ __device__ constexpr int b_addr(int s) { return (NST + s % NST) * 16384; }
constexpr int R6 = 2 * NST * 16384;
__host__ __device__ constexpr int d_addr(int p) { return p / 2 == 1 ? R6 + (p & 1) * 16384 : (p & 1) ? b_addr(26 + p / 3) : a_addr(26 + p / 3); }
static_assert(d_addr(0) == a_addr(26) && d_addr(4) == a_addr(27) && d_addr(6) == a_addr(28), "");
constexpr int OFF_MISC = R6 + 32768;
constexpr int B_FULL = OFF_MISC;
constexpr int B_EMPTY = B_FULL + 48;
constexpr int B_EMPR = B_EMPTY + 48;
constexpr int B_VD = B_EMPR + 48;
constexpr int B_X = B_VD + 8;
constexpr int B_HX = B_X + 16;
constexpr int B_XF = B_HX + 8;
constexpr int B_S0 = B_XF + 8;
constexpr int B_S1 = B_S0 + 8;
constexpr int B_EA = B_S1 + 8;
constexpr int B_S2 = B_EA + 8;
constexpr int B_S3 = B_S2 + 8;
constexpr int B_D6 = B_S3 + 8;
constexpr int B_DL = B_D6 + 8;
constexpr int B_GATE = B_DL + 32;
constexpr int B_SIDE = B_GATE + 8;
constexpr int B_FFN = B_SIDE + 8;
constexpr int B_R6 = B_FFN + 32;
constexpr int B_LAND = B_R6 + 8;
constexpr int B_VAL = B_LAND + 48;
constexpr int B_TH = B_VAL + 96;
constexpr int M_TH = B_TH + 24;
constexpr int NBAR = (M_TH - B_EMPTY) / 8;
constexpr int M_KEY = M_TH + 12;
constexpr int M_PAR = M_KEY + 4;
constexpr int M_ROLE = M_PAR + 4;
constexpr int M_HX = OFF_MISC + 544;
constexpr int M_G = M_HX + 256;
constexpr int M_UPD = M_G + 512;
constexpr int M_RED = M_UPD + 512;
constexpr int SMEM_BYTES = 232448;
static_assert(M_RED + 512 <= SMEM_BYTES && M_ROLE + 4 <= M_HX, "smem");

struct Params {
    const bf16 *gate_w, *w_r, *dre, *dim;
    CUtensorMap mCre, mCim, mX2, mX, mDre, mDim, mF, mWg, mWu, mWd;
};

struct Scratch {
    uint32_t frag[NCTA * 2 * 4096];
    uint32_t stamp[NCTA * 32];
    uint32_t gate[S_];
    uint32_t keys[8 * NCTA];
    uint32_t part[FFN_CTAS / 2 * D_];
    uint32_t phint[4 * 8 * 8];
    uint32_t upd[D_];
    uint32_t epoch[NCTA + 4];
};
__device__ __align__(1024) Scratch g_scr;

__device__ __forceinline__ uint32_t smem_u32(const void* p) { return (uint32_t)__cvta_generic_to_shared(p); }
__device__ __forceinline__ void mbar_init(uint32_t bar, uint32_t cnt) {
    asm volatile("mbarrier.init.shared::cta.b64 [%0], %1;" ::"r"(bar), "r"(cnt) : "memory");
}
__device__ __forceinline__ void mbar_expect_tx(uint32_t bar, uint32_t bytes) {
    asm volatile("mbarrier.arrive.expect_tx.shared::cta.b64 _, [%0], %1;" ::"r"(bar), "r"(bytes) : "memory");
}
__device__ __forceinline__ void mbar_arrive(uint32_t bar) {
    asm volatile("mbarrier.arrive.shared::cta.b64 _, [%0];" ::"r"(bar) : "memory");
}
template <int N>
__device__ __forceinline__ void mbar_arrive_n_if(uint32_t bar, bool pred) {
    asm volatile("{.reg .pred p; setp.ne.b32 p, %1, 0; @p mbarrier.arrive.shared::cta.b64 _, [%0], %2;}" ::"r"(bar), "r"((int)pred), "n"(N) : "memory");
}
__device__ __forceinline__ void mbar_arrive_if(uint32_t bar, bool pred) {
    asm volatile("{.reg .pred p; setp.ne.b32 p, %1, 0; @p mbarrier.arrive.shared::cta.b64 _, [%0];}" ::"r"(bar), "r"((int)pred) : "memory");
}
__device__ __forceinline__ void mbar_arrive_warp(uint32_t bar) {
    __syncwarp();
    mbar_arrive_if(bar, (threadIdx.x & 31) == 0);
}
__device__ __forceinline__ void mbar_arrive_cluster_if(uint32_t bar, bool pred) {
    asm volatile("{.reg .pred p; setp.ne.b32 p, %1, 0; @p mbarrier.arrive.shared::cluster.b64 _, [%0], 1;}"
                 ::"r"(bar), "r"((int)pred) : "memory");
}
__device__ __forceinline__ uint32_t mapa(uint32_t a, uint32_t cta) {
    uint32_t r;
    asm volatile("mapa.shared::cluster.u32 %0, %1, %2;" : "=r"(r) : "r"(a), "r"(cta));
    return r;
}
__device__ __forceinline__ bool mbar_try(uint32_t bar, uint32_t parity) {
    uint32_t ok;
    asm volatile("{.reg .pred p; mbarrier.try_wait.parity.shared::cta.b64 p, [%1], %2; selp.u32 %0,1,0,p;}"
                 : "=r"(ok) : "r"(bar), "r"(parity) : "memory");
    return ok;
}
__device__ __forceinline__ bool mbar_test(uint32_t bar, uint32_t parity) {
    uint32_t ok;
    asm volatile("{.reg .pred p; mbarrier.test_wait.parity.shared::cta.b64 p, [%1], %2; selp.u32 %0,1,0,p;}"
                 : "=r"(ok) : "r"(bar), "r"(parity) : "memory");
    return ok;
}
__device__ __forceinline__ void mbar_wait(uint32_t bar, uint32_t parity) {
    uint32_t n = 0;
#pragma unroll 1
    while (!mbar_try(bar, parity)) { if (++n > SPIN_LIMIT) break; }
}
__device__ __forceinline__ void tma2d(uint32_t dst, const CUtensorMap* m, int c0, int c1, uint32_t bar) {
    asm volatile("cp.async.bulk.tensor.2d.shared::cluster.global.mbarrier::complete_tx::bytes [%0], [%1, {%3,%4}], [%2];"
                 ::"r"(dst), "l"(m), "r"(bar), "r"(c0), "r"(c1) : "memory");
}
__device__ __forceinline__ void tma3d(uint32_t dst, const CUtensorMap* m, int row, int chunk, uint32_t bar) {
    asm volatile("cp.async.bulk.tensor.3d.shared::cluster.global.mbarrier::complete_tx::bytes [%0], [%1, {%3,%4,%5}], [%2];"
                 ::"r"(dst), "l"(m), "r"(bar), "r"(0), "r"(row), "r"(chunk) : "memory");
}
__device__ __forceinline__ void tma2d_elect(uint32_t dst, const CUtensorMap* m, int c0, int c1, uint32_t bar) {
    asm volatile("{.reg .pred p; elect.sync _|p, 0xffffffff;"
                 " @p cp.async.bulk.tensor.2d.shared::cluster.global.mbarrier::complete_tx::bytes [%0], [%1, {%3,%4}], [%2];}"
                 ::"r"(dst), "l"(m), "r"(bar), "r"(c0), "r"(c1) : "memory");
}
__device__ __forceinline__ void tma2d_pair_elect(uint32_t dst, const CUtensorMap* m, int c0, int c1, uint32_t bar) {
    asm volatile("{.reg .pred p; elect.sync _|p, 0xffffffff;"
                 " @p cp.async.bulk.tensor.2d.shared::cluster.global.mbarrier::complete_tx::bytes.multicast::cluster"
                 " [%0], [%1, {%3,%4}], [%2], %5;}" ::"r"(dst), "l"(m), "r"(bar), "r"(c0), "r"(c1), "h"((uint16_t)3) : "memory");
}
__device__ __forceinline__ void tma3d_elect(uint32_t dst, const CUtensorMap* m, int row, int chunk, uint32_t bar) {
    asm volatile("{.reg .pred p; elect.sync _|p, 0xffffffff;"
                 " @p cp.async.bulk.tensor.3d.shared::cluster.global.mbarrier::complete_tx::bytes [%0], [%1, {%3,%4,%5}], [%2];}"
                 ::"r"(dst), "l"(m), "r"(bar), "r"(0), "r"(row), "r"(chunk) : "memory");
}
__device__ __forceinline__ void tma5d_elect(uint32_t dst, const CUtensorMap* m, int c0, int c4, uint32_t bar) {
    asm volatile("{.reg .pred p; elect.sync _|p, 0xffffffff;"
                 " @p cp.async.bulk.tensor.5d.shared::cluster.global.mbarrier::complete_tx::bytes [%0], [%1, {%3,%5,%5,%5,%4}], [%2];}"
                 ::"r"(dst), "l"(m), "r"(bar), "r"(c0), "r"(c4), "r"(0) : "memory");
}
__device__ __forceinline__ void mbar_expect_tx_elect(uint32_t bar, uint32_t bytes) {
    asm volatile("{.reg .pred p; elect.sync _|p, 0xffffffff; @p mbarrier.arrive.expect_tx.shared::cta.b64 _, [%0], %1;}"
                 ::"r"(bar), "r"(bytes) : "memory");
}
__device__ __forceinline__ void fence_proxy_async_smem() { asm volatile("fence.proxy.async.shared::cta;" ::: "memory"); }
__device__ __forceinline__ void prefetch_l2(const void* p) { asm volatile("prefetch.global.L2 [%0];" ::"l"(p)); }
__device__ __forceinline__ uint32_t ld_relaxed(const void* p) {
    uint32_t v;
    asm volatile("ld.relaxed.gpu.global.u32 %0, [%1];" : "=r"(v) : "l"(p) : "memory");
    return v;
}
__device__ __forceinline__ uint4 ld_relaxed4(const void* p) {
    uint4 v;
    asm volatile("ld.relaxed.gpu.global.v4.u32 {%0,%1,%2,%3}, [%4];" : "=r"(v.x), "=r"(v.y), "=r"(v.z), "=r"(v.w) : "l"(p) : "memory");
    return v;
}
__device__ __forceinline__ void st_relaxed(unsigned int* p, uint32_t v) {
    asm volatile("st.relaxed.gpu.global.u32 [%0], %1;" ::"l"(p), "r"(v) : "memory");
}
__device__ __forceinline__ uint32_t tagf(float v, uint32_t par) { return (__float_as_uint(v) & ~1u) | par; }
template <int BIT = 0>
__device__ __forceinline__ uint4 wait_tags(const unsigned int* p, uint32_t par) {
    uint32_t n = 0;
#pragma unroll 1
    while (true) {
        const uint4 v = ld_relaxed4(p);
        const uint32_t m = par ? (v.x & v.y & v.z & v.w) : ~(v.x | v.y | v.z | v.w);
        if (__all_sync(0xffffffffu, (m >> BIT) & 1u)) return v;
        __nanosleep(100);
        if (++n > SPIN_LIMIT) return v;
    }
}
__device__ __forceinline__ uint32_t best_key(const uint32_t* keys, uint32_t par) {
    const uint4 k = wait_tags<15>(keys + (threadIdx.x & 31) * 4, par);
    return __reduce_max_sync(0xffffffffu, max(max(k.x, k.y), max(k.z, k.w)));
}
__device__ __forceinline__ void named_bar(int id, int n) { asm volatile("bar.sync %0, %1;" ::"r"(id), "r"(n) : "memory"); }
template <int OFF>
__device__ __forceinline__ uint4 ldg_nc_off(const void* p) {
    uint4 v;
    asm volatile("ld.global.nc.v4.u32 {%0,%1,%2,%3}, [%4+%5];" : "=r"(v.x), "=r"(v.y), "=r"(v.z), "=r"(v.w) : "l"(p), "n"(OFF));
    return v;
}
__device__ __forceinline__ void ldg_nc_if(uint4& v, const void* a, bool pred) {
    asm volatile("{.reg .pred p; setp.ne.b32 p, %5, 0; @p ld.global.nc.v4.u32 {%0,%1,%2,%3}, [%4];}"
                 : "+r"(v.x), "+r"(v.y), "+r"(v.z), "+r"(v.w) : "l"(a), "r"((int)pred) : "memory");
}
template <int OFF>
__device__ __forceinline__ void stg_off(void* p, const uint4& v) {
    asm volatile("st.global.v4.u32 [%0+%5], {%1,%2,%3,%4};" ::"l"(p), "r"(v.x), "r"(v.y), "r"(v.z), "r"(v.w), "n"(OFF) : "memory");
}
__device__ __forceinline__ void sts128(uint32_t a, const uint4& v) {
    asm volatile("st.shared.v4.u32 [%0], {%1,%2,%3,%4};" ::"r"(a), "r"(v.x), "r"(v.y), "r"(v.z), "r"(v.w) : "memory");
}
__device__ __forceinline__ uint4 lds128(uint32_t a) {
    uint4 v;
    asm volatile("ld.shared.v4.u32 {%0,%1,%2,%3}, [%4];" : "=r"(v.x), "=r"(v.y), "=r"(v.z), "=r"(v.w) : "r"(a) : "memory");
    return v;
}
__device__ __forceinline__ void lds128_if(uint4& v, uint32_t a, bool pred) {
    asm volatile("{.reg .pred p; setp.ne.b32 p, %5, 0; @p ld.shared.v4.u32 {%0,%1,%2,%3}, [%4];}"
                 : "+r"(v.x), "+r"(v.y), "+r"(v.z), "+r"(v.w) : "r"(a), "r"((int)pred) : "memory");
}
__device__ __forceinline__ uint32_t lds32(uint32_t a) {
    uint32_t v;
    asm volatile("ld.shared.u32 %0, [%1];" : "=r"(v) : "r"(a) : "memory");
    return v;
}
__device__ __forceinline__ void st_async16(uint32_t dst, uint32_t x, uint32_t y, uint32_t z, uint32_t w, uint32_t bar) {
    asm volatile("st.async.weak.shared::cluster.mbarrier::complete_tx::bytes.v4.b32 [%0], {%1,%2,%3,%4}, [%5];"
                 ::"r"(dst), "r"(x), "r"(y), "r"(z), "r"(w), "r"(bar) : "memory");
}
__device__ __forceinline__ int sel(int a, int b, bool p) {
    int r;
    asm("{.reg .pred q; setp.ne.b32 q, %3, 0; selp.b32 %0, %1, %2, q;}" : "=r"(r) : "r"(a), "r"(b), "r"((int)p));
    return r;
}
__device__ __forceinline__ float selpf(float a, float b, bool p) {
    float r;
    asm("{.reg .pred q; setp.ne.b32 q, %3, 0; selp.f32 %0, %1, %2, q;}" : "=f"(r) : "f"(a), "f"(b), "r"((int)p));
    return r;
}
template <int N, int MASK, int SZ>
__device__ __forceinline__ void halve(float (&a)[SZ]) {
    const bool up = threadIdx.x & MASK;
#pragma unroll
    for (int j = 0; j < N; j++) a[j] = selpf(a[N + j], a[j], up) + __shfl_xor_sync(0xffffffffu, selpf(a[j], a[N + j], up), MASK);
}
__device__ __forceinline__ float bflo(uint32_t u) { return __uint_as_float(u << 16); }
__device__ __forceinline__ float bfhi(uint32_t u) { return __uint_as_float(u & 0xffff0000u); }
__device__ __forceinline__ uint32_t pack_bf16(float lo, float hi) {
    uint32_t r;
    asm("cvt.rn.bf16x2.f32 %0, %1, %2;" : "=r"(r) : "f"(hi), "f"(lo));
    return r;
}
__device__ __forceinline__ uint32_t hmul2_bf16(uint32_t a, uint32_t b) {
    uint32_t r;
    asm("mul.rn.bf16x2 %0, %1, %2;" : "=r"(r) : "r"(a), "r"(b));
    return r;
}
__device__ __forceinline__ float sigmoidf_(float v) { return 1.0f / (1.0f + __expf(-v)); }
__device__ __forceinline__ void wg_fence() { asm volatile("wgmma.fence.sync.aligned;" ::: "memory"); }
__device__ __forceinline__ void wg_commit() { asm volatile("wgmma.commit_group.sync.aligned;" ::: "memory"); }
template <int N> __device__ __forceinline__ void wg_wait() { asm volatile("wgmma.wait_group.sync.aligned %0;" ::"n"(N) : "memory"); }
__device__ __forceinline__ uint64_t desc_lo(uint32_t lo) { return (uint64_t)lo | (0x40000040ull << 32); }
template <int LO, int HI, int N>
__device__ __forceinline__ void fence_regs(float (&d)[N]) {
#pragma unroll
    for (int i = LO; i < HI; i++) asm volatile("" : "+f"(d[i])::"memory");
}
template <int LO, int HI, int N>
__device__ __forceinline__ void keep_regs(uint4 (&f)[N]) {
#pragma unroll
    for (int i = LO; i < HI; i++) asm volatile("" ::"r"(f[i].x), "r"(f[i].y), "r"(f[i].z), "r"(f[i].w) : "memory");
}
template <int TB = 1>
__device__ __forceinline__ void wgmma128(float (&d)[64], uint64_t da, uint64_t db, int scaleD) {
    asm volatile(
        "{ .reg .pred p; setp.ne.b32 p, %66, 0;\n"
        "wgmma.mma_async.sync.aligned.m64n128k16.f32.bf16.bf16 "
        "{%0,%1,%2,%3,%4,%5,%6,%7,%8,%9,%10,%11,%12,%13,%14,%15,%16,%17,%18,%19,%20,%21,%22,%23,%24,%25,%26,%27,%28,%29,%30,%31,"
        "%32,%33,%34,%35,%36,%37,%38,%39,%40,%41,%42,%43,%44,%45,%46,%47,%48,%49,%50,%51,%52,%53,%54,%55,%56,%57,%58,%59,%60,%61,%62,%63}, "
        "%64, %65, p, 1, 1, 0, %67;\n}"
        : "+f"(d[0]), "+f"(d[1]), "+f"(d[2]), "+f"(d[3]), "+f"(d[4]), "+f"(d[5]), "+f"(d[6]), "+f"(d[7]),
          "+f"(d[8]), "+f"(d[9]), "+f"(d[10]), "+f"(d[11]), "+f"(d[12]), "+f"(d[13]), "+f"(d[14]), "+f"(d[15]),
          "+f"(d[16]), "+f"(d[17]), "+f"(d[18]), "+f"(d[19]), "+f"(d[20]), "+f"(d[21]), "+f"(d[22]), "+f"(d[23]),
          "+f"(d[24]), "+f"(d[25]), "+f"(d[26]), "+f"(d[27]), "+f"(d[28]), "+f"(d[29]), "+f"(d[30]), "+f"(d[31]),
          "+f"(d[32]), "+f"(d[33]), "+f"(d[34]), "+f"(d[35]), "+f"(d[36]), "+f"(d[37]), "+f"(d[38]), "+f"(d[39]),
          "+f"(d[40]), "+f"(d[41]), "+f"(d[42]), "+f"(d[43]), "+f"(d[44]), "+f"(d[45]), "+f"(d[46]), "+f"(d[47]),
          "+f"(d[48]), "+f"(d[49]), "+f"(d[50]), "+f"(d[51]), "+f"(d[52]), "+f"(d[53]), "+f"(d[54]), "+f"(d[55]),
          "+f"(d[56]), "+f"(d[57]), "+f"(d[58]), "+f"(d[59]), "+f"(d[60]), "+f"(d[61]), "+f"(d[62]), "+f"(d[63])
        : "l"(da), "l"(db), "r"(scaleD), "n"(TB));
}
__device__ __forceinline__ void wgmma128rs(float (&d)[64], const uint4& a, uint64_t db, int scaleD) {
    asm volatile(
        "{ .reg .pred p; setp.ne.b32 p, %69, 0;\n"
        "wgmma.mma_async.sync.aligned.m64n128k16.f32.bf16.bf16 "
        "{%0,%1,%2,%3,%4,%5,%6,%7,%8,%9,%10,%11,%12,%13,%14,%15,%16,%17,%18,%19,%20,%21,%22,%23,%24,%25,%26,%27,%28,%29,%30,%31,"
        "%32,%33,%34,%35,%36,%37,%38,%39,%40,%41,%42,%43,%44,%45,%46,%47,%48,%49,%50,%51,%52,%53,%54,%55,%56,%57,%58,%59,%60,%61,%62,%63}, "
        "{%64,%65,%66,%67}, %68, p, 1, 1, 0;\n}"
        : "+f"(d[0]), "+f"(d[1]), "+f"(d[2]), "+f"(d[3]), "+f"(d[4]), "+f"(d[5]), "+f"(d[6]), "+f"(d[7]),
          "+f"(d[8]), "+f"(d[9]), "+f"(d[10]), "+f"(d[11]), "+f"(d[12]), "+f"(d[13]), "+f"(d[14]), "+f"(d[15]),
          "+f"(d[16]), "+f"(d[17]), "+f"(d[18]), "+f"(d[19]), "+f"(d[20]), "+f"(d[21]), "+f"(d[22]), "+f"(d[23]),
          "+f"(d[24]), "+f"(d[25]), "+f"(d[26]), "+f"(d[27]), "+f"(d[28]), "+f"(d[29]), "+f"(d[30]), "+f"(d[31]),
          "+f"(d[32]), "+f"(d[33]), "+f"(d[34]), "+f"(d[35]), "+f"(d[36]), "+f"(d[37]), "+f"(d[38]), "+f"(d[39]),
          "+f"(d[40]), "+f"(d[41]), "+f"(d[42]), "+f"(d[43]), "+f"(d[44]), "+f"(d[45]), "+f"(d[46]), "+f"(d[47]),
          "+f"(d[48]), "+f"(d[49]), "+f"(d[50]), "+f"(d[51]), "+f"(d[52]), "+f"(d[53]), "+f"(d[54]), "+f"(d[55]),
          "+f"(d[56]), "+f"(d[57]), "+f"(d[58]), "+f"(d[59]), "+f"(d[60]), "+f"(d[61]), "+f"(d[62]), "+f"(d[63])
        : "r"(a.x), "r"(a.y), "r"(a.z), "r"(a.w), "l"(db), "r"(scaleD));
}
__device__ __forceinline__ uint32_t clk() { uint64_t c; asm volatile("mov.u64 %0, %%clock64;" : "=l"(c)::"memory"); return (uint32_t)c; }
__device__ __forceinline__ uint32_t gtime() { uint64_t t; asm volatile("mov.u64 %0, %%globaltimer;" : "=l"(t)::"memory"); return (uint32_t)t; }
__device__ __forceinline__ void until(uint32_t t) { while (t - clk() < 0x8000u) {} }
__device__ __forceinline__ void nap_until(uint32_t t) { while (t - clk() < 0x8000u) __nanosleep(20); }
__device__ __forceinline__ uint4 scale_add(float s, const float (&a)[64], int o, const uint4& w) {
    return make_uint4(pack_bf16(fmaf(s, a[o], bflo(w.x)), fmaf(s, a[o + 1], bfhi(w.x))), pack_bf16(fmaf(s, a[o + 4], bflo(w.y)), fmaf(s, a[o + 5], bfhi(w.y))),
                      pack_bf16(fmaf(s, a[o + 8], bflo(w.z)), fmaf(s, a[o + 9], bfhi(w.z))), pack_bf16(fmaf(s, a[o + 12], bflo(w.w)), fmaf(s, a[o + 13], bfhi(w.w))));
}

__device__ __forceinline__ uint32_t router_key(float score, int row) {
    const float r = score + 0.0f;
    uint32_t u = pack_bf16(r, 0.f) & 0xffffu;
    u = (u & 0x8000u) ? (~u & 0xffffu) : (u | 0x8000u);
    if (r != r) u = 0;
    return (u << 16) | (uint32_t)(0x7fff - row);
}

#define g_ab g_scr.frag
#define g_fb_h ((float*)g_scr.part)
#define g_fb_upd (g_fb_h + 2048)
#define g_fb_gate (g_fb_h + 4096)
#define g_fb_keys (g_scr.part + 8192)
__global__ void fb_hidden(const bf16* x, const bf16* dre, const bf16* dim, const bf16* gw, const bf16* wr) {
    __shared__ float xs[D_];
    const int s = blockIdx.x, t = threadIdx.x;
    xs[t] = __bfloat162float(x[s * D_ + t]);
    __syncthreads();
    float a = 0.f, b = 0.f;
    for (int d = 0; d < D_; d++) { a = fmaf(xs[d], __bfloat162float(dre[t * D_ + d]), a); b = fmaf(xs[d], __bfloat162float(dim[t * D_ + d]), b); }
    ((bf16*)g_ab)[s * 1024 + t] = __float2bfloat16(a);
    ((bf16*)g_ab)[s * 1024 + 512 + t] = __float2bfloat16(b);
    if (t == 0) {
        float u = 0.f, v = 0.f;
        for (int d = 0; d < D_; d++) { u = fmaf(xs[d], __bfloat162float(gw[d]), u); v = fmaf(xs[d], __bfloat162float(wr[d]), v); }
        g_fb_gate[s] = sigmoidf_(u);
        g_fb_keys[s] = router_key(v, s);
    }
}
__device__ uint32_t fb_best() {
    uint32_t k = 0;
    for (int i = 0; i < S_; i++) k = max(k, g_fb_keys[i]);
    return k;
}
__global__ void fb_ffn1(const bf16* x, const bf16* wg, const bf16* wu) {
    const int f = blockIdx.x * blockDim.x + threadIdx.x, idx = 0x7fff - (int)(fb_best() & 0x7fffu);
    float a = 0.f, b = 0.f;
    for (int d = 0; d < D_; d++) {
        const float xv = __bfloat162float(x[idx * D_ + d]);
        a = fmaf(xv, __bfloat162float(wg[d * F_ + f]), a); b = fmaf(xv, __bfloat162float(wu[d * F_ + f]), b);
    }
    g_fb_h[f] = a * sigmoidf_(a) * b;
}
__global__ void fb_ffn2(const bf16* wd) {
    const int e = blockIdx.x * blockDim.x + threadIdx.x;
    const uint32_t u = fb_best() >> 16, rb = (u & 0x8000u) ? (u & 0x7fffu) : (~u & 0xffffu);
    float a = 0.f;
    for (int f = 0; f < F_; f++) a = fmaf(g_fb_h[f], __bfloat162float(wd[f * D_ + e]), a);
    g_fb_upd[e] = a * sigmoidf_(__uint_as_float(rb << 16));
}
__global__ void fb_seq(const bf16* x, const bf16* cre, const bf16* cim, bf16* out) {
    __shared__ float c[2][S_];
    __shared__ int idx;
    const int t = blockIdx.x, e = threadIdx.x;
    for (int i = e; i < S_; i += D_) { c[0][i] = __bfloat162float(cre[t * S_ + i]); c[1][i] = __bfloat162float(cim[t * S_ + i]); }
    if (e == 0) idx = 0x7fff - (int)(fb_best() & 0x7fffu);
    __syncthreads();
    float y = 0.f;
    for (int s = 0; s < S_; s++)
        y += c[0][s] * __bfloat162float(((const bf16*)g_ab)[s * 1024 + e]) - c[1][s] * __bfloat162float(((const bf16*)g_ab)[s * 1024 + 512 + e]);
    const float g = g_fb_gate[t];
    out[t * D_ + e] = __float2bfloat16(g * y + (1.f - g) * (__bfloat162float(x[t * D_ + e]) + (t == idx ? g_fb_upd[e] : 0.f)));
}

__device__ __forceinline__ void spare_job(const Params& p, Scratch* g, unsigned char* smem, int sp, uint32_t tstart) {
    const int tid = threadIdx.x, warp = tid >> 5, lane = tid & 31;
    if (warp >= 8) {
#pragma unroll 1
        for (int i = 0; i < 16; i++) {
            nap_until(tstart + PFD_T0 + i * (PFD_DT / 2));
            prefetch_l2((const char*)((sp & 2) ? p.dim : p.dre) + (sp & 1) * 262144 + i * 16384 + (tid - 256) * 128);
        }
        return;
    }
    nap_until(tstart + SUM_T0 - 2000);
    const uint32_t e1 = ld_relaxed(g->epoch + NCTA + sp) + 1u, par = e1 & 1u;
    const uint32_t u = best_key(g->keys + warp * NCTA, par) >> 16;
    const float rs = sigmoidf_(__uint_as_float(((u & 0x8000u) ? (u & 0x7fffu) : (~u & 0xffffu)) << 16));
    nap_until(tstart + SUM_T0);
    uint32_t n = 0;
#pragma unroll 1
    while ((int)(ld_relaxed(g->phint + (sp * 8 + warp) * 8) - e1 * 14u) < 0) {
        __nanosleep(40);
        if (++n > SPIN_LIMIT) break;
    }
    const unsigned int* src = g->part + warp * 7 * D_ + sp * 128 + lane * 4;
    uint4 v[7];
#pragma unroll 1
    while (true) {
        uint32_t bad = 0;
#pragma unroll
        for (int i = 0; i < 7; i++) v[i] = ld_relaxed4(src + i * D_);
#pragma unroll
        for (int i = 0; i < 7; i++) bad |= (v[i].x ^ par) | (v[i].y ^ par) | (v[i].z ^ par) | (v[i].w ^ par);
        if (!__any_sync(0xffffffffu, bad & 1u)) break;
        if (++n > SPIN_LIMIT) break;
    }
    float4 s = make_float4(0.f, 0.f, 0.f, 0.f);
#pragma unroll
    for (int i = 0; i < 7; i++) {
        s.x += __uint_as_float(v[i].x); s.y += __uint_as_float(v[i].y);
        s.z += __uint_as_float(v[i].z); s.w += __uint_as_float(v[i].w);
    }
    float* acc = (float*)smem;
    *(float4*)&acc[warp * 128 + lane * 4] = s;
    named_bar(1, 256);
    if (tid < 128) {
        float t = 0.f;
#pragma unroll
        for (int i = 0; i < 8; i++) t += acc[i * 128 + tid];
        st_relaxed(&g->upd[sp * 128 + tid], tagf(t * rs, par));
        if (tid == 0) st_relaxed(g->epoch + NCTA + sp, e1);
    }
}

__device__ __forceinline__ int ffn_pair(int role) { return role - __popcll(NOFFN_MASK & ((1ull << role) - 1)); }
__device__ __forceinline__ int other(int i, int tn) { return i + (i >= tn); }
__device__ __forceinline__ int dcol(int p, int tn) { return p < 2 ? tn * 128 + p * 64 : other((p - 2) % 3, tn) * 128 + (p >= 5 ? 64 : 0); }

template <int H>
__device__ __forceinline__ void fetch_job(const Params& p, Scratch* g, unsigned char* smem, uint32_t sb, int cta, int i, uint32_t par) {
    const int lane = threadIdx.x & 31, comp = cta & 1;
    const int j = other(i, (cta >> 1) & 3), src = (cta & ~6) + 2 * j;
    const int slot = i == 0 ? 29 % NST : i - 1;
    const uint32_t land = sb + B_LAND + 8 * (3 * H + i);
    uint32_t ph = 0, th;
    mbar_expect_tx_elect(land, 8192);
    if (H == 0) {
        mbar_wait(sb + B_S0, 0);
        const uint32_t t0 = clk();
        if (i == 0) {
            mbar_wait(sb + B_FULL + 8 * (31 % NST), (31 / NST) & 1);
            const uint32_t t1 = t0 + max(clk() - t0, 180u) - 180u;
            asm volatile("{.reg .pred p; .reg .b64 t; setp.eq.b32 p, %3, 0; mov.b64 t, {%1, %2}; @p st.relaxed.gpu.global.b64 [%0], t;}"
                         ::"l"(g->stamp + cta * 32), "r"((t1 & ~1u) | par), "r"(gtime()), "r"(lane) : "memory");
        }
        until(t0 + SDEL);
        uint32_t gt;
#pragma unroll 1
        for (uint32_t n = 0; n < SPIN_LIMIT; n++) {
            asm volatile("{.reg .b64 t; ld.relaxed.gpu.global.b64 t, [%2]; mov.b64 {%0,%1}, t;}" : "=r"(th), "=r"(gt) : "l"(g->stamp + src * 32) : "memory");
            if (!__any_sync(0xffffffffu, (th ^ par) & 1u)) break;
        }
        const uint32_t ns = min(gtime() - gt, 4096u), now = clk();
        if (now - th >= 8192u) th = now - (ns + (ns >> 1) + (ns >> 4));
        th += SG * j;
        if (lane == 0) { *(volatile uint32_t*)(smem + M_TH + 4 * i) = th; mbar_arrive(sb + B_TH + 8 * i); }
        __syncwarp();
    } else {
        mbar_wait(sb + B_TH + 8 * i, 0);
        th = lds32(sb + M_TH + 4 * i);
    }
    mbar_wait(sb + B_EA, 0);
#pragma unroll 1
    for (int c = 0; c < 2; c++) {
        const uint32_t dst = sb + slot * 16384 + (c ? NST * 16384 + H * 8192 : (comp ^ H) * 8192);
        if (c != H) mbar_wait(sb + B_EMPTY + 8 * slot, i != 0);
        until(th + (c ? (H ? L_RD1 : L_RD0) : (H ? E_RD1 : E_RD0)));
#pragma unroll 1
        for (uint32_t r = 0; r < SPIN_LIMIT; r++) {
            tma2d_elect(dst, &p.mF, 0, (src * 2 + (comp ^ c)) * 128 + H * 64, land);
            mbar_wait(land, ph);
            ph ^= 1;
            const uint32_t a = dst + (lane >> 2) * 132 + (lane & 3) * 32;
            uint32_t v[8], m0 = 0, m1 = ~0u;
#pragma unroll
            for (int k = 0; k < 8; k++) v[k] = lds32(a + k * 1024);
#pragma unroll
            for (int k = 0; k < 8; k++) { m0 |= v[k]; m1 &= v[k]; }
            if (__all_sync(0xffffffffu, (par ? m1 : ~m0) & 1u)) break;
            mbar_expect_tx_elect(land, 8192);
        }
        mbar_arrive_if(sb + B_VAL + 8 * (6 * c + 3 * H + i), lane == 0);
        if (c == 0) mbar_expect_tx_elect(land, 8192);
    }
}

__global__ void __cluster_dims__(2, 1, 1) __launch_bounds__(NTHREADS, 1)
fused_kernel(const char* pc0, const char* pc1, const char* px, char* pout, Scratch* g, const __grid_constant__ Params p) {
    extern __shared__ __align__(1024) unsigned char smem[];
    const uint32_t sb = smem_u32(smem);
    const int tid = threadIdx.x, warp = tid >> 5, lane = tid & 31;
    const int rank = blockIdx.x & 1;
    {
        const uint32_t b = blockIdx.x & 127;
        const char* u0 = (rank ? pc1 : pc0) + (b >> 1) * (32 * S_ * 2);
        const char* u1 = px + b * 512 - 4096;
        asm volatile("{.reg .pred p, q; .reg .b64 a; .reg .b32 t; setp.lt.u32 p, %2, 32; mad.wide.u32 a, %2, 4096, %0; @p prefetch.global.L2 [a];"
                     " sub.u32 t, %2, 32; setp.lt.u32 q, t, 4; mad.wide.u32 a, %2, 128, %1; @q prefetch.global.L2 [a];}" ::"l"(u0), "l"(u1), "r"(tid));
    }
    const uint32_t tstart = clk();
    uint32_t smid;
    asm volatile("mov.u32 %0, %%smid;" : "=r"(smid));
    const int u = smid >> 1, v7 = ((u - 32) * 37) >> 8;
    const int tn = sel(u >> 3, sel(v7, u - 62, u < 60), u < 32);
    const int tm = sel(u & 7, sel(u - 23 - 7 * v7, 8, u < 60), u < 32);
    const bool spare = tn < 0;
    const int role = tm * 4 + tn, cta = role * 2 + rank;
    const int comp = rank;
    const CUtensorMap* mC = comp ? &p.mCim : &p.mCre;
#define ARM(j) do { mbar_init(sb + B_FULL + 8 * (j), 1); mbar_expect_tx(sb + B_FULL + 8 * (j), 32768); } while (0)
#define FIRST(j) do { tma2d(sb + a_addr(j), mC, (j) * 64, tm * 128, sb + B_FULL + 8 * (j));                        \
                      tma3d(sb + b_addr(j), &p.mX2, (j) * 64, tn * 2, sb + B_FULL + 8 * (j)); } while (0)
    if (tid == 384) {
        ARM(0);
        if (!spare) FIRST(0);
    }
    const int wu = __shfl_sync(0xffffffffu, warp, 0);
    if (wu < 12) {
        if (lane == 0) {
            mbar_init(sb + B_EMPTY + 8 * wu, 2);
            mbar_init(sb + B_VD + 8 * wu, wu ? 1 : 4);
#pragma unroll
            for (int i = 24; i < NBAR; i += 12) if (i + 12 <= NBAR || wu < NBAR - i) mbar_init(sb + B_EMPTY + 8 * (i + wu), 1);
            if (wu >= 1 && wu < 4) mbar_expect_tx(sb + B_VD + 8 * wu, wu < 3 ? 8192 : 256);
        }
        asm volatile("fence.mbarrier_init.release.cluster;" ::: "memory");
        __syncwarp();
        asm volatile("barrier.cluster.arrive.relaxed.aligned;" ::: "memory");
        if (spare) {
            spare_job(p, g, smem, smid & 3, tstart);
        } else if (wu >= 8) {
            asm volatile("setmaxnreg.dec.sync.aligned.u32 " STR(RS_) ";");
            asm volatile("barrier.cluster.wait.acquire.aligned;" ::: "memory");
            const int t = tid - 256, w = wu - 8, fr = ffn_pair(role);
            const bool ffn = !((NOFFN_MASK >> role) & 1);
            nap_until(tstart + SIDE_T0);
            const uint4 gw0 = ldg_nc_off<0>(p.gate_w + lane * 8), gw1 = ldg_nc_off<512>(p.gate_w + lane * 8);
            const uint4 rw0 = ldg_nc_off<0>(p.w_r + lane * 8), rw1 = ldg_nc_off<512>(p.w_r + lane * 8);
            const uint32_t par = ~ld_relaxed(g->epoch + cta) & 1u;
            nap_until(tstart + ROUTER_T0 + (2 * w + rank) * ROUTER_DT);
            {
                const int row0 = cta * 16 + w * 4;
                const char* xp = px + (uint32_t)row0 * (D_ * 2) + lane * 16;
                uint4 xa[4], xb[4];
                xa[0] = ldg_nc_off<0>(xp);    xb[0] = ldg_nc_off<512>(xp);  xa[1] = ldg_nc_off<1024>(xp); xb[1] = ldg_nc_off<1536>(xp);
                xa[2] = ldg_nc_off<2048>(xp); xb[2] = ldg_nc_off<2560>(xp); xa[3] = ldg_nc_off<3072>(xp); xb[3] = ldg_nc_off<3584>(xp);
                float a[8];
#pragma unroll
                for (int i = 0; i < 4; i++) {
                    const uint32_t xv[8] = {xa[i].x, xa[i].y, xa[i].z, xa[i].w, xb[i].x, xb[i].y, xb[i].z, xb[i].w};
                    const uint32_t gv[8] = {gw0.x, gw0.y, gw0.z, gw0.w, gw1.x, gw1.y, gw1.z, gw1.w};
                    const uint32_t rv[8] = {rw0.x, rw0.y, rw0.z, rw0.w, rw1.x, rw1.y, rw1.z, rw1.w};
                    float uu = 0.f, vv = 0.f;
#pragma unroll
                    for (int j = 0; j < 8; j++) {
                        uu = fmaf(bflo(xv[j]), bflo(gv[j]), uu); uu = fmaf(bfhi(xv[j]), bfhi(gv[j]), uu);
                        vv = fmaf(bflo(xv[j]), bflo(rv[j]), vv); vv = fmaf(bfhi(xv[j]), bfhi(rv[j]), vv);
                    }
                    a[i] = uu; a[4 + i] = vv;
                }
                halve<4, 16>(a); halve<2, 8>(a); halve<1, 4>(a);
                {
                    const float b1 = __shfl_xor_sync(0xffffffffu, a[0], 1), b2 = __shfl_xor_sync(0xffffffffu, a[0], 2),
                                b3 = __shfl_xor_sync(0xffffffffu, a[0], 3);
                    a[0] = (a[0] + b1) + (b2 + b3);
                }
                const int row = row0 + ((lane >> 2) & 3);
                const uint32_t best = __reduce_max_sync(0xffffffffu, lane >= 16 && (lane & 3) == 0 ? router_key(a[0], row) : 0u);
                if (lane <= 16 && (lane & 3) == 0)
                    *(volatile uint32_t*)(smem + M_RED + (lane < 16 ? w * 16 + lane : 64 + w * 4)) = lane < 16 ? tagf(sigmoidf_(a[0]), par) : best;
                named_bar(1, 128);
                if (t < 8) {
                    const uint4 k = lds128(sb + M_RED + 64);
                    asm volatile("{.reg .b32 old; atom.relaxed.gpu.global.exch.b32 old, [%0], %1;}"
                                 ::"l"(g->keys + t * NCTA + cta), "r"(max(max(k.x, k.y), max(k.z, k.w)) | (par << 15)) : "memory");
                }
                if (w == 1 && lane < 16) st_relaxed(g->gate + cta * 16 + lane, lds32(sb + M_RED + lane * 4));
            }
            uint32_t vd[32];
            if (ffn) {
                mbar_wait(sb + B_FFN + 24, 0);
#pragma unroll
                for (int j = 0; j < 32; j++) vd[j] = lds32(sb + R6 + ((j >> 3) & 1) * 16384 + (2 + (j >> 4)) * 4096 + (j & 7) * 512 + t * 4);
                mbar_arrive_warp(sb + B_VD);
            }
            mbar_wait(sb + B_GATE, 0);
            const int idx = 0x7fff - (int)(*(volatile uint32_t*)(smem + M_KEY) & 0x7fffu);
            if (ffn) {
                float a[16];
#pragma unroll
                for (int i = 0; i < 16; i++) a[i] = 0.f;
#pragma unroll 1
                for (int qu = 0; qu < 4; qu++) {
                    mbar_wait(sb + B_FFN + 8 * qu, qu == 3);
#pragma unroll
                    for (int i = 2 * qu; i < 2 * qu + 2; i++) {
                        const float xs = __bfloat162float(((const bf16*)(smem + M_UPD))[32 * i + (t >> 2)]);
                        const uint4 vg = lds128(sb + R6 + i * 2048 + t * 16);
                        const uint4 vu = lds128(sb + R6 + 16384 + i * 2048 + t * 16);
                        const uint32_t g4[4] = {vg.x, vg.y, vg.z, vg.w};
                        const uint32_t u4[4] = {vu.x, vu.y, vu.z, vu.w};
#pragma unroll
                        for (int j = 0; j < 4; j++) {
                            a[2 * j] = fmaf(xs, bflo(g4[j]), a[2 * j]);         a[2 * j + 1] = fmaf(xs, bfhi(g4[j]), a[2 * j + 1]);
                            a[8 + 2 * j] = fmaf(xs, bflo(u4[j]), a[8 + 2 * j]); a[9 + 2 * j] = fmaf(xs, bfhi(u4[j]), a[9 + 2 * j]);
                        }
                    }
                }
                named_bar(1, 128);
                mbar_arrive_if(sb + B_R6, t == 0);
                halve<8, 16>(a); halve<4, 8>(a); halve<2, 4>(a);
                float* red = (float*)(smem + M_UPD);
                *(float2*)&red[w * 64 + (lane >> 4) * 32 + (lane & 3) * 8 + ((lane >> 2) & 3) * 2] = make_float2(a[0], a[1]);
                named_bar(1, 128);
                const float sg = red[lane] + red[64 + lane] + red[128 + lane] + red[192 + lane];
                const float su = red[32 + lane] + red[96 + lane] + red[160 + lane] + red[224 + lane];
                if (w < 2) {
                    asm volatile("st.async.weak.shared::cluster.mbarrier::complete_tx::bytes.f32 [%0], %1, [%2];"
                                 ::"r"(mapa(sb + M_HX + t * 4, rank ^ 1)), "f"(w ? su : sg), "r"(mapa(sb + B_HX, rank ^ 1)) : "memory");
                }
                named_bar(1, 128);
                mbar_wait(sb + B_HX, 0);
                const float pg = ((const float*)(smem + M_HX))[lane], pu = ((const float*)(smem + M_HX))[32 + lane];
                const float gs = sg + pg, us = su + pu;
                float* hrow = red + w * 32;
                hrow[lane] = gs * sigmoidf_(gs) * us;
                __syncwarp();
                float o0 = 0.f, o1 = 0.f;
#pragma unroll
                for (int j4 = 0; j4 < 8; j4++) {
                    const float4 hv = *(const float4*)&hrow[j4 * 4];
                    o0 = fmaf(hv.x, bflo(vd[4 * j4]), o0);     o1 = fmaf(hv.x, bfhi(vd[4 * j4]), o1);
                    o0 = fmaf(hv.y, bflo(vd[4 * j4 + 1]), o0); o1 = fmaf(hv.y, bfhi(vd[4 * j4 + 1]), o1);
                    o0 = fmaf(hv.z, bflo(vd[4 * j4 + 2]), o0); o1 = fmaf(hv.z, bfhi(vd[4 * j4 + 2]), o1);
                    o0 = fmaf(hv.w, bflo(vd[4 * j4 + 3]), o0); o1 = fmaf(hv.w, bfhi(vd[4 * j4 + 3]), o1);
                }
                asm volatile("st.relaxed.gpu.global.v2.u32 [%0], {%1,%2};" ::"l"(&g->part[fr * D_ + rank * 256 + t * 2]),
                             "r"(tagf(o0, par)), "r"(tagf(o1, par)) : "memory");
                if (lane == 0) asm volatile("red.relaxed.gpu.global.add.u32 [%0], 1;" ::"l"(g->phint + ((rank * 2 + (w >> 1)) * 8 + fr / 7) * 8) : "memory");
            }
            if (!ffn) mbar_arrive_if(sb + B_R6, t == 0);
            if (w < 3) {
                fetch_job<1>(p, g, smem, sb, cta, w, par);
            } else {
                if (lds32(sb + M_ROLE) != (uint32_t)role) __trap();
                if ((idx >> 6) == 2 * tm + comp) {
                    const uint4 u4 = wait_tags(g->upd + tn * 128 + lane * 4, par);
                    const float og = 1.f - ((const float*)(smem + M_G))[idx & 127];
                    *(float4*)(smem + M_RED + lane * 16) = make_float4(og * __uint_as_float(u4.x), og * __uint_as_float(u4.y),
                                                                       og * __uint_as_float(u4.z), og * __uint_as_float(u4.w));
                    mbar_arrive_warp(sb + B_SIDE);
                }
            }
        } else {
            const int wg = wu >> 2;
            const uint32_t sbd = (sb & 0x3FFFF) >> 4;
            const bool lead = (tid & 127) == 0;
            const bool early = wg == comp;
            const int q = lane & 3;
            const int r0 = (warp & 3) * 16 + (lane >> 2);
            float acc[64];
            const uint32_t da0 = sbd + 0x10000 + wg * 512, db0 = sbd + 0x2000000, dd0 = sbd + 0x10000;
            const uint32_t rE = mapa(sb + B_EMPR, rank ^ 1);
#define WAITFULL(s) mbar_wait(sb + B_FULL + 8 * ((s) % NST), ((s) / NST) & 1)
#define TESTFULL(s) mbar_test(sb + B_FULL + 8 * ((s) % NST), ((s) / NST) & 1)
#define WAITD(pos) do { if ((pos) >= 4) mbar_wait(sb + B_DL + 8 * ((pos) & 3), 0); else if ((pos) >= 2) mbar_wait(sb + B_D6, 0); else WAITFULL(32); } while (0)
#define MMA_A(s, kk) wgmma128(acc, desc_lo(da0 + a_addr(s) / 16 + (kk) * 2), desc_lo(db0 + b_addr(s) / 16 + (kk) * 128), 1)
            asm volatile("setmaxnreg.inc.sync.aligned.u32 " STR(RC) ";");
            asm volatile("barrier.cluster.wait.acquire.aligned;" ::: "memory");
            WAITFULL(0);
            wg_fence();
#pragma unroll
            for (int kk = 0; kk < 4; kk++) wgmma128(acc, desc_lo(da0 + kk * 2), desc_lo(db0 + b_addr(0) / 16 + kk * 128), kk != 0);
            wg_commit();
            int slot = 1, ph = 0, pslot = 0;
            const uint32_t ooff = (uint32_t)((tm * 128 + wg * 64 + r0) * D_ + tn * 128 + q * 8) * 2u;
            uint32_t* fout = g->frag + (cta * 2 + wg) * 4096 + (warp & 3) * 128 + lane;
            uint32_t tagm[4];
#pragma unroll
            for (int c = 0; c < 4; c++) tagm[c] = (lane & 7) == (warp & 1) * 4 + c;
            const char* xp = px + ooff;
            asm volatile("" : "+r"(tagm[0]), "+r"(tagm[1]), "+r"(tagm[2]), "+r"(tagm[3]), "+l"(xp), "+l"(fout));
            uint4 w[8];
#pragma unroll
            for (int i = 0; i < 8; i++) w[i] = make_uint4(0, 0, 0, 0);
#pragma unroll
            for (int part = 0; part <= XN; part++) {
                if (part) {
#pragma unroll
                    for (int i = (part - 1) * 8 / XN; i < part * 8 / XN; i++) ldg_nc_if(w[i], xp + (i & 1) * 8192 + (i >> 1) * 64, early);
                }
#pragma unroll 1
                for (int step = part ? XLD + (part - 1) * XD : 1; step < (part < XN ? XLD + part * XD : SP0); step++) {
                    mbar_wait(sb + B_FULL + 8 * slot, ph);
                    const uint32_t a = da0 + slot * 1024, b = db0 + b_addr(0) / 16 + slot * 1024;
                    wg_fence();
                    wgmma128(acc, desc_lo(a), desc_lo(b), 1);
                    wg_commit();
                    wg_wait<1>();
                    mbar_arrive_if(sb + B_EMPTY + 8 * pslot, lead);
                    mbar_arrive_cluster_if(rE + 8 * pslot, lead);
                    pslot = slot;
                    if (++slot == NST) { slot = 0; ph ^= 1; }
                    wg_fence();
#pragma unroll
                    for (int kk = 1; kk < 4; kk++) wgmma128(acc, desc_lo(a + kk * 2), desc_lo(b + kk * 128), 1);
                    wg_commit();
                }
            }
            uint32_t par;
            float g0, g1;
#define GATES() do { par = lds32(sb + M_PAR); g0 = __uint_as_float(lds32(sb + M_G + (wg * 64 + r0) * 4)); g1 = __uint_as_float(lds32(sb + M_G + (wg * 64 + r0 + 8) * 4)); } while (0)
            if (early) {
                WAITFULL(SP0);
                wg_fence();
                MMA_A(SP0, 0); MMA_A(SP0, 1);
                wg_commit();
                wg_wait<1>();
                mbar_arrive_if(sb + B_EMPTY + 8 * ((SP0 - 1) % NST), lead);
                bool ok = TESTFULL(SP0 + 1);
                MMA_A(SP0, 2); MMA_A(SP0, 3);
                wg_commit();
#pragma unroll
                for (int s = SP0 + 1; s < 32; s++) {
                    if (!ok) { WAITFULL(s); if (s == 29) mbar_wait(sb + B_GATE, 0); }
                    wg_fence();
                    MMA_A(s, 0); MMA_A(s, 1);
                    if (s == 29) GATES();
                    if (s >= 30) { wg_commit(); wg_wait<1>(); mbar_arrive_if(sb + (s == 30 ? B_S0 : B_S1), lead); wg_fence(); }
                    if (s < 31) ok = TESTFULL(s + 1) & (s != 28 || mbar_test(sb + B_GATE, 0));
                    MMA_A(s, 2); MMA_A(s, 3);
                    wg_commit();
                }
                wg_wait<0>();
                mbar_arrive_if(sb + B_EA, lead);
            } else {
                wg_wait<0>();
                mbar_arrive_if(sb + B_EMPTY + 8 * ((SP0 - 1) % NST), lead);
#pragma unroll
                for (int s = SP0; s < 32; s++) WAITFULL(s);
                mbar_wait(sb + B_GATE, 0);
                GATES();
                mbar_wait(sb + B_S1, 0);
                wg_fence();
#pragma unroll
                for (int s = SP0; s < 32; s++) {
                    MMA_A(s, 0); MMA_A(s, 1);
                    if (s > SP0) {
                        wg_commit();
                        wg_wait<1>();
                        mbar_arrive_n_if<2>(sb + B_EMPTY + 8 * ((s - 1) % NST), lead);
                        if (s == 31) mbar_arrive_if(sb + B_S3, lead);
                        if (s == 30) WAITD(0);
                        wg_fence();
                    }
                    MMA_A(s, 2); MMA_A(s, 3);
                    wg_commit();
                }
                wg_wait<0>();
                mbar_arrive_n_if<2>(sb + B_EMPTY + 8 * (31 % NST), lead);
            }
            fence_regs<0, 64>(acc);
            uint4 f[8];
#define TAG(v, c) (((v) & ~tagm[c]) | (par & tagm[c]))
#define PACK(k) f[k] = make_uint4(TAG(pack_bf16(acc[8 * (k)], acc[8 * (k) + 1]), 0), TAG(pack_bf16(acc[8 * (k) + 2], acc[8 * (k) + 3]), 2), \
                                  TAG(pack_bf16(acc[8 * (k) + 4], acc[8 * (k) + 5]), 1), TAG(pack_bf16(acc[8 * (k) + 6], acc[8 * (k) + 7]), 3))
#define SEND(k) do { st_relaxed(fout + 512 * (k), f[k].x); st_relaxed(fout + 512 * (k) + 32, f[k].z);                        \
                     st_relaxed(fout + 512 * (k) + 64, f[k].y); st_relaxed(fout + 512 * (k) + 96, f[k].w); } while (0)
#define OWN(k) wgmma128rs(acc, f[k], desc_lo(dd0 + d_addr((k) >> 2) / 16 + ((k) & 3) * 2), (k) != 0)
            const uint32_t dfa = sbd + 0x80000 + (early ? comp * 512 : NST * 1024), dfb = sbd + 0x80000 + (early ? (1 - comp) * 512 : NST * 1024 + 512);
#define MMA_F(pos, kk) wgmma128<0>(acc, (uint64_t)(((pos) < 5 ? dfa : dfb) + a_addr(29 + ((pos) - 2) % 3) / 16 + (kk) * 128) | (0x10ull << 32), \
                                   desc_lo(dd0 + d_addr(pos) / 16 + (kk) * 2), 1)
#define WAITF(pos) mbar_wait(vb + 8 * ((pos) - 2), 0)
            const uint32_t vb = sb + B_VAL + (early ? 0 : 48);
            const uint32_t ts = clk();
            if (early) {
                PACK(0); SEND(0); PACK(1); SEND(1); PACK(2); SEND(2); PACK(3); SEND(3);
                until(ts);
                PACK(4); PACK(5); PACK(6); PACK(7);
                const float s0 = comp ? -g0 : g0, s1 = comp ? -g1 : g1;
                const uint32_t og0 = pack_bf16(1.f - g0, 1.f - g0), og1 = pack_bf16(1.f - g1, 1.f - g1);
                const int rr = 0x7fff - (int)(lds32(sb + M_KEY) & 0x7fffu) - (tm * 128 + wg * 64 + r0);
#pragma unroll
                for (int k = 4; k < 8; k++) {
                    if (k < ESEND) { until(ts + ET1 + (k - 4) * STP); SEND(k); }
#pragma unroll
                    for (int i = 2 * k - 8; i < 2 * k - 6; i++) {
                        const uint32_t og = (i & 1) ? og1 : og0;
                        w[i] = make_uint4(hmul2_bf16(og, w[i].x), hmul2_bf16(og, w[i].y), hmul2_bf16(og, w[i].z), hmul2_bf16(og, w[i].w));
                        asm volatile("" : "+r"(w[i].x), "+r"(w[i].y), "+r"(w[i].z), "+r"(w[i].w));
                    }
                }
                WAITD(0);
                mbar_wait(sb + B_S3, 0);
                wg_fence();
#pragma unroll
                for (int k = 0; k < 8; k++) {
                    OWN(k);
                    if (k >= 1 && k + ESEND - 1 < 8) { wg_commit(); until(ts + ET1 + (k + ESEND - 5) * STP); SEND(k + ESEND - 1); wg_fence(); }
                }
                wg_commit();
                WAITD(2);
                bool ok = false;
#pragma unroll
                for (int pos = 2; pos < 8; pos++) {
                    if (!ok) {
                        if (pos >= 4) WAITD(pos);
                        WAITF(pos);
                    }
                    wg_fence();
                    MMA_F(pos, 0); MMA_F(pos, 1);
                    if (pos == 6) { wg_commit(); wg_wait<1>(); mbar_arrive_cluster_if(mapa(sb + B_XF, rank ^ 1), lead); wg_fence(); }
                    if (pos == 7) mbar_arrive_if(sb + B_S2, lead);
                    if (pos < 7) ok = mbar_test(vb + 8 * (pos - 1), 0) & (pos < 3 || mbar_test(sb + B_DL + 8 * (pos - 3), 0));
                    MMA_F(pos, 2); MMA_F(pos, 3);
                    wg_commit();
                }
                const uint32_t xd = mapa(sb + a_addr(29) + (tid & 127) * 16, rank ^ 1), xb = mapa(sb + B_X, rank ^ 1);
                if (rr == 0 || rr == 8) {
                    mbar_wait(sb + B_SIDE, 0);
#pragma unroll
                    for (int j = 0; j < 4; j++) {
                        const float4 ua = *(const float4*)(smem + M_RED + j * 128 + q * 32), ub = *(const float4*)(smem + M_RED + j * 128 + q * 32 + 16);
                        uint4 v = rr ? w[2 * j + 1] : w[2 * j];
                        v = make_uint4(pack_bf16(ua.x + bflo(v.x), ua.y + bfhi(v.x)), pack_bf16(ua.z + bflo(v.y), ua.w + bfhi(v.y)),
                                       pack_bf16(ub.x + bflo(v.z), ub.y + bfhi(v.z)), pack_bf16(ub.z + bflo(v.w), ub.w + bfhi(v.w)));
                        if (rr) w[2 * j + 1] = v; else w[2 * j] = v;
                    }
                }
                __syncwarp();
                mbar_wait(sb + B_XF, 0);
                wg_wait<0>();
                fence_regs<0, 64>(acc);
                keep_regs<0, 8>(f);
#pragma unroll
                for (int i = 0; i < 8; i++) {
                    const uint4 z = scale_add((i & 1) ? s1 : s0, acc, 16 * (i >> 1) + 2 * (i & 1), w[i]);
                    st_async16(xd + i * 2048, z.x, z.y, z.z, z.w, xb + 2 * (i & 4));
                    if (i & 1) until(ts);
                }
            } else {
                PACK(0); PACK(1); PACK(2); PACK(3); PACK(4); PACK(5); PACK(6); PACK(7);
                wg_fence();
#pragma unroll
                for (int k = 0; k < 8; k++) {
                    OWN(k);
                    if ((k & 1) && k / 2 < LSEND) { wg_commit(); until(ts + LT0 + k / 2 * LTP); SEND(k / 2); wg_fence(); }
                }
                wg_commit();
#pragma unroll
                for (int k = LSEND; k < 8; k++) { until(ts + LT0 + k * LTP); SEND(k); }
                float s0 = comp ? -g0 : g0, s1 = comp ? -g1 : g1;
                uint32_t xs = sb + a_addr(29) + (tid & 127) * 16;
                char* op = pout + ooff;
                asm volatile("" : "+f"(s0), "+f"(s1), "+r"(xs), "+l"(op));
                wg_wait<0>();
                keep_regs<0, 8>(f);
                WAITF(2);
                mbar_wait(sb + B_S2, 0);
                bool there = false, there1 = false, ok = true;
#pragma unroll
                for (int pos = 2; pos < 8; pos++) {
                    if (!ok) WAITF(pos);
                    wg_fence();
                    MMA_F(pos, 0);
                    if (pos == XPOS) there = mbar_test(sb + B_X, 0);
                    MMA_F(pos, 1);
                    if (pos == XPOS) {
#pragma unroll
                        for (int i = 0; i < 4; i++) lds128_if(w[i], xs + i * 2048, there);
                    }
                    if (pos < 7) ok = mbar_test(vb + 8 * (pos - 1), 0);
                    MMA_F(pos, 2); MMA_F(pos, 3);
                    wg_commit();
                }
                if (!there) {
                    mbar_wait(sb + B_X, 0);
#pragma unroll
                    for (int i = 0; i < 4; i++) w[i] = lds128(xs + i * 2048);
                }
                there1 = mbar_test(sb + B_X + 8, 0);
                float z[32];
#pragma unroll
                for (int i = 0; i < 4; i++) {
                    z[8 * i] = bflo(w[i].x); z[8 * i + 1] = bfhi(w[i].x); z[8 * i + 2] = bflo(w[i].y); z[8 * i + 3] = bfhi(w[i].y);
                    z[8 * i + 4] = bflo(w[i].z); z[8 * i + 5] = bfhi(w[i].z); z[8 * i + 6] = bflo(w[i].w); z[8 * i + 7] = bfhi(w[i].w);
                }
                fence_regs<0, 32>(z);
#pragma unroll 1
                for (int n = there1; n > 0; n--) {
#pragma unroll
                    for (int i = 4; i < 8; i++) w[i] = lds128(xs + i * 2048);
                }
                wg_wait<0>();
                fence_regs<0, 64>(acc);
#pragma unroll
                for (int i = 0; i < 8; i++) {
                    const int o = 16 * (i >> 1) + 2 * (i & 1);
                    const float s = (i & 1) ? s1 : s0;
                    if (i == XW && !there1) {
                        mbar_wait(sb + B_X + 8, 0);
#pragma unroll
                        for (int k = 4; k < 8; k++) w[k] = lds128(xs + k * 2048);
                    }
                    stg_off<0>(op + (i & 1) * 8192 + (i >> 1) * 64,
                               i >= 4 ? scale_add(s, acc, o, w[i])
                                      : make_uint4(pack_bf16(fmaf(s, acc[o], z[8 * (i & 3)]), fmaf(s, acc[o + 1], z[8 * (i & 3) + 1])),
                                                   pack_bf16(fmaf(s, acc[o + 4], z[8 * (i & 3) + 2]), fmaf(s, acc[o + 5], z[8 * (i & 3) + 3])),
                                                   pack_bf16(fmaf(s, acc[o + 8], z[8 * (i & 3) + 4]), fmaf(s, acc[o + 9], z[8 * (i & 3) + 5])),
                                                   pack_bf16(fmaf(s, acc[o + 12], z[8 * (i & 3) + 6]), fmaf(s, acc[o + 13], z[8 * (i & 3) + 7]))));
                    __syncwarp();
                }
            }
        }
    } else {
#define STEP0(j) do { tma2d_elect(sb + (j) * 16384, mC, (j) * 64, tm * 128, sb + B_FULL + 8 * (j));                            \
                      tma3d_elect(sb + (NST + (j)) * 16384, &p.mX2, (j) * 64, tn * 2, sb + B_FULL + 8 * (j)); } while (0)
        if (wu >= 14) {
            const uint32_t b = blockIdx.x;
            const char* q = wu == 14 ? (rank ? pc1 : pc0) + (uint32_t)((b >> 1) * 32 + lane) * (S_ * 2) + 128 : px + (uint32_t)(b * 4 + lane) * 128 + 65536;
            until(tstart + P_1);
            if (b < 128 && (wu == 14 || lane < 4)) prefetch_l2(q);
        } else if (wu == 13 && !spare) {
            if (lane == 0) ARM(1);
            __syncwarp();
            until(tstart + T_1);
            STEP0(1);
        }
        if (lane == 0) ARM(wu - 10);
        asm volatile("fence.mbarrier_init.release.cluster;" ::: "memory");
        __syncwarp();
        asm volatile("barrier.cluster.arrive.relaxed.aligned;" ::: "memory");
        if (spare) return;
        asm volatile("setmaxnreg.dec.sync.aligned.u32 " STR(RU) ";");
        if (wu < 14) {
            until(tstart + T_2 + (wu - 12) * PACE);
            STEP0(wu - 10);
        }
        asm volatile("barrier.cluster.wait.acquire.aligned;" ::: "memory");
        if (wu == 13) {
            const CUtensorMap* mD = comp ? &p.mDim : &p.mDre;
#pragma unroll
            for (int step = 4; step < NST; step++) {
                until(tstart + T_2 + (step - 2) * PACE);
                tma3d_elect(sb + b_addr(step), &p.mX2, step * 64, tn * 2, sb + B_FULL + 8 * step);
            }
#pragma unroll 1
            for (int step = NST, slot = 0, ph = 0; step < 32; step++) {
                mbar_wait(sb + B_EMPTY + 8 * slot, ph);
                mbar_wait(sb + B_EMPR + 8 * slot, ph);
                tma2d_pair_elect(sb + b_addr(0) + slot * 16384 + rank * 8192, &p.mX, tn * 128 + rank * 64, step * 64, sb + B_FULL + 8 * slot);
                if (++slot == NST) { slot = 0; ph ^= 1; }
            }
#pragma unroll
            for (int c = 0; c < 4; c += 2) {
                const uint32_t bar = sb + (c ? B_D6 : B_FULL + 8 * (32 % NST));
                if (c) mbar_wait(sb + B_R6, 0);
                else mbar_wait(sb + B_EMPTY + 8 * (26 % NST), (26 / NST) & 1);
                tma5d_elect(sb + d_addr(c), mD, dcol(c, tn), tn * 4, bar);
                tma5d_elect(sb + d_addr(c + 1), mD, dcol(c + 1, tn), tn * 4, bar);
                mbar_expect_tx_elect(bar, 32768);
            }
#pragma unroll
            for (int c = 0; c < 4; c++) mbar_expect_tx_elect(sb + B_DL + 8 * c, 16384);
            mbar_wait(sb + B_S1, 0);
            const uint32_t tq = clk();
#pragma unroll
            for (int c = 0; c < 4; c++) {
                if (!(c & 1)) mbar_wait(sb + B_EMPTY + 8 * ((27 + c / 2) % NST), ((27 + c / 2) / NST) & 1);
                if (c) until(tq + (c == 1 ? T_D5 : c == 2 ? T_D6 : T_D7));
                tma5d_elect(sb + d_addr(4 + c), mD, dcol(4 + c, tn), tn * 4, sb + B_DL + 8 * c);
            }
        } else {
            if (wu == 12) {
#pragma unroll
                for (int step = 4; step < NST; step++) {
                    until(tstart + T_2 + (step - 2) * PACE);
                    tma2d_elect(sb + a_addr(step), mC, step * 64, tm * 128, sb + B_FULL + 8 * step);
                }
#pragma unroll 1
                for (int step = NST, slot = 0, ph = 0; step < 32; step++) {
                    mbar_wait(sb + B_EMPTY + 8 * slot, ph);
                    tma2d_elect(sb + slot * 16384, mC, step * 64, tm * 128, sb + B_FULL + 8 * slot);
                    mbar_expect_tx_elect(sb + B_FULL + 8 * slot, 32768);
                    if (++slot == NST) { slot = 0; ph ^= 1; }
                }
            } else if (wu == 14) {
                if (lane == 0) {
                    asm volatile("prefetch.tensormap [%0];" ::"l"(&p.mX) : "memory");
                    asm volatile("prefetch.tensormap [%0];" ::"l"(&p.mF) : "memory");
                    asm volatile("prefetch.tensormap [%0];" ::"l"(comp ? &p.mDim : &p.mDre) : "memory");
                    asm volatile("st.shared::cluster.u32 [%0], %1;" ::"r"(mapa(sb + M_ROLE, rank ^ 1)), "r"(role) : "memory");
                }
                nap_until(tstart + KEY_T0 - 1000);
                const uint32_t epoch = ld_relaxed(g->epoch + cta) + 1u, par = epoch & 1u;
                if (lane < 8) stg_off<0>(g->stamp + cta * 32 + lane * 4, make_uint4(par ^ 1u, 0, 0, 0));
                nap_until(tstart + KEY_T0);
                const uint32_t k = best_key(g->keys + (tm & 7) * NCTA, par);
                const uint4 xr = ldg_nc_off<0>(px + (0x7fff - (k & 0x7fffu)) * (D_ * 2) + rank * 512 + lane * 16);
                const uint4 g4 = wait_tags(g->gate + tm * 128 + lane * 4, par);
                sts128(sb + M_G + lane * 16, make_uint4(g4.x & ~1u, g4.y & ~1u, g4.z & ~1u, g4.w & ~1u));
                sts128(sb + M_UPD + lane * 16, xr);
                if (lane == 0) {
                    *(volatile uint32_t*)(smem + M_KEY) = k;
                    *(volatile uint32_t*)(smem + M_PAR) = par;
                    st_relaxed(g->epoch + cta, epoch);
                }
                mbar_arrive_warp(sb + B_GATE);
            } else {
                const int fr = ffn_pair(role);
                const uint32_t t1 = tstart + FFN_T0 + (rank + ((fr >> 2) & 6)) * (FFN_DT / 8);
                if (!((NOFFN_MASK >> role) & 1)) {
#pragma unroll 1
                    for (int i = 0; i < 12; i++) {
                        const int qu = i < 4 ? 2 + (i >> 1) : (i - 4) >> 1;
                        const uint32_t bar = sb + B_FFN + 8 * (i < 4 ? 3 : qu), dst = sb + R6 + (i & 1) * 16384 + qu * 4096;
                        if (i == 8) mbar_wait(sb + B_VD, 0);
                        if (i == 0 || (i >= 4 && !(i & 1))) mbar_expect_tx_elect(bar, i ? 8192 : 16384);
                        nap_until(t1 + i * FFN_DT);
                        tma2d_elect(dst, i < 4 ? &p.mWd : (i & 1) ? &p.mWu : &p.mWg, i < 4 ? rank * 256 : fr * 32, i < 4 ? fr * 32 + i * 8 : rank * 256 + qu * 64, bar);
                    }
                }
            }
            __syncwarp();
            mbar_wait(sb + B_GATE, 0);
            fetch_job<0>(p, g, smem, sb, cta, wu == 12 ? 2 : wu - 14, lds32(sb + M_PAR));
        }
    }
}

typedef CUresult (*EncodeTiledFn)(CUtensorMap*, CUtensorMapDataType, cuuint32_t, void*, const cuuint64_t*, const cuuint64_t*,
                                  const cuuint32_t*, const cuuint32_t*, CUtensorMapInterleave, CUtensorMapSwizzle,
                                  CUtensorMapL2promotion, CUtensorMapFloatOOBfill);

static void make_map(EncodeTiledFn enc, CUtensorMap* m, const void* base, uint64_t cols, uint64_t rows, uint32_t box_rows,
                     CUtensorMapSwizzle sw = CU_TENSOR_MAP_SWIZZLE_128B, uint32_t box_cols = 64) {
    cuuint64_t dims[2] = {cols, rows};
    cuuint64_t str[1] = {cols * 2};
    cuuint32_t box[2] = {box_cols, box_rows};
    cuuint32_t es[2] = {1, 1};
    enc(m, CU_TENSOR_MAP_DATA_TYPE_BFLOAT16, 2, (void*)base, dims, str, box, es, CU_TENSOR_MAP_INTERLEAVE_NONE,
        sw, CU_TENSOR_MAP_L2_PROMOTION_L2_128B, CU_TENSOR_MAP_FLOAT_OOB_FILL_NONE);
}

static void make_map_chunks(EncodeTiledFn enc, CUtensorMap* m, const void* base, uint64_t rows) {
    cuuint64_t dims[3] = {64, rows, D_ / 64};
    cuuint64_t str[2] = {D_ * 2, 128};
    cuuint32_t box[3] = {64, 64, 2};
    cuuint32_t es[3] = {1, 1, 1};
    enc(m, CU_TENSOR_MAP_DATA_TYPE_BFLOAT16, 3, (void*)base, dims, str, box, es, CU_TENSOR_MAP_INTERLEAVE_NONE,
        CU_TENSOR_MAP_SWIZZLE_128B, CU_TENSOR_MAP_L2_PROMOTION_L2_128B, CU_TENSOR_MAP_FLOAT_OOB_FILL_NONE);
}

static void make_map_perm(EncodeTiledFn enc, CUtensorMap* m, const void* base) {
    cuuint64_t dims[5] = {D_, 2, 4, 4, D_ / 32};
    cuuint64_t str[4] = {D_ * 2, 8 * D_ * 2, 2 * D_ * 2, 32 * D_ * 2};
    cuuint32_t box[5] = {64, 2, 4, 4, 4};
    cuuint32_t es[5] = {1, 1, 1, 1, 1};
    enc(m, CU_TENSOR_MAP_DATA_TYPE_BFLOAT16, 5, (void*)base, dims, str, box, es, CU_TENSOR_MAP_INTERLEAVE_NONE,
        CU_TENSOR_MAP_SWIZZLE_128B, CU_TENSOR_MAP_L2_PROMOTION_L2_128B, CU_TENSOR_MAP_FLOAT_OOB_FILL_NONE);
}

extern "C" void kernel_launch(void* const* d_in, const int* in_sizes, int n_in, void* d_out, int out_size) {
    (void)in_sizes; (void)n_in; (void)out_size;
    static EncodeTiledFn enc = nullptr;
    static bool fused_ok = false;
    static void* scr = nullptr;
    if (!enc) {
        void* fn = nullptr;
        cudaDriverEntryPointQueryResult q;
        cudaGetDriverEntryPoint("cuTensorMapEncodeTiled", &fn, cudaEnableDefault, &q);
        enc = (EncodeTiledFn)fn;
        cudaGetSymbolAddress(&scr, g_scr);
        cudaFuncSetAttribute(fused_kernel, cudaFuncAttributeMaxDynamicSharedMemorySize, SMEM_BYTES);
        int dev = 0, nsm = 0, ncl = 0;
        cudaGetDevice(&dev);
        cudaDeviceGetAttribute(&nsm, cudaDevAttrMultiProcessorCount, dev);
        cudaLaunchConfig_t cfg = {};
        cfg.gridDim = dim3(132); cfg.blockDim = dim3(NTHREADS); cfg.dynamicSmemBytes = SMEM_BYTES;
        cudaLaunchAttribute at;
        at.id = cudaLaunchAttributeClusterDimension;
        at.val.clusterDim.x = 2; at.val.clusterDim.y = 1; at.val.clusterDim.z = 1;
        cfg.attrs = &at; cfg.numAttrs = 1;
        fused_ok = cudaOccupancyMaxActiveClusters(&ncl, fused_kernel, &cfg) == cudaSuccess && nsm == 132 && ncl == 66;
        (void)cudaGetLastError();
    }
    if (!fused_ok) {
        const bf16* const* in = (const bf16* const*)d_in;
        fb_hidden<<<S_, D_, 0, cudaStreamPerThread>>>(in[0], in[3], in[4], in[10], in[6]);
        fb_ffn1<<<F_ / 128, 128, 0, cudaStreamPerThread>>>(in[0], in[7], in[8]);
        fb_ffn2<<<D_ / 64, 64, 0, cudaStreamPerThread>>>(in[9]);
        fb_seq<<<S_, D_, 0, cudaStreamPerThread>>>(in[0], in[1], in[2], (bf16*)d_out);
        return;
    }
    Params p;
    p.dre = (const bf16*)d_in[3];
    p.dim = (const bf16*)d_in[4];
    p.w_r = (const bf16*)d_in[6];
    p.gate_w = (const bf16*)d_in[10];
    make_map_chunks(enc, &p.mX2, d_in[0], S_);
    make_map(enc, &p.mX, d_in[0], D_, S_, 64);
    make_map(enc, &p.mCre, d_in[1], S_, S_, 128);
    make_map(enc, &p.mCim, d_in[2], S_, S_, 128);
    make_map_perm(enc, &p.mDre, d_in[3]);
    make_map_perm(enc, &p.mDim, d_in[4]);
    make_map(enc, &p.mF, scr, 64, NCTA * 256, 64, CU_TENSOR_MAP_SWIZZLE_NONE);
    make_map(enc, &p.mWg, d_in[7], F_, D_, 64, CU_TENSOR_MAP_SWIZZLE_NONE, 32);
    make_map(enc, &p.mWu, d_in[8], F_, D_, 64, CU_TENSOR_MAP_SWIZZLE_NONE, 32);
    make_map(enc, &p.mWd, d_in[9], D_, F_, 8, CU_TENSOR_MAP_SWIZZLE_NONE, 256);
    fused_kernel<<<132, NTHREADS, SMEM_BYTES, cudaStreamPerThread>>>((const char*)d_in[1], (const char*)d_in[2], (const char*)d_in[0], (char*)d_out, (Scratch*)scr, p);
}
```

```cpp
#include <cuda_runtime.h>
#include <cuda.h>
#include <cuda_bf16.h>
#include <stdint.h>

typedef __nv_bfloat16 bf16;

constexpr int S_ = 2048, D_ = 512, F_ = 1792;
constexpr int NCTA = 128;
constexpr int NTHREADS = 512;
constexpr int NST = 6;
constexpr int SP0 = 27;
constexpr int FFN_CTAS = F_ / 16;
constexpr uint32_t SPIN_LIMIT = 1u << 16;

#define P_1 450
#define T_1 500
#define T_2 1050
#define PACE 420
#define ROUTER_T0 3000
#define ROUTER_DT 280
#define FFN_T0 5200
#define FFN_DT 640
#define XLD 14
#define XN 8
#define XD 1
#define PFD_T0 11900
#define PFD_DT 250
#define SUM_T0 15500
#define ET1 600
#define STP 170
#define ESEND 6
#define LT0 450
#define LTP 170
#define LSEND 3
#define SDEL 280
#define E_RD0 1330
#define E_RD1 2180
#define L_RD0 3300
#define L_RD1 3930
#define SG 130
#define T_D5 1500
#define T_D6 1700
#define T_D7 2400
#define XPOS 7
#define RC 168
#define RS_ 112
#define RU 64
#define KEY_T0 9800
#define NOFFN_MASK 0xf00c880000000000ull
#define XW 4
#define SIDE_T0 2800
#define STR2(x) #x
#define STR(x) STR2(x)

__host__ __device__ constexpr int a_addr(int s) { return s % NST * 16384; }
__host__ __device__ constexpr int b_addr(int s) { return (NST + s % NST) * 16384; }
constexpr int R6 = 2 * NST * 16384;
__host__ __device__ constexpr int d_addr(int p) { return p / 2 == 1 ? R6 + (p & 1) * 16384 : (p & 1) ? b_addr(26 + p / 3) : a_addr(26 + p / 3); }
static_assert(d_addr(0) == a_addr(26) && d_addr(4) == a_addr(27) && d_addr(6) == a_addr(28), "");
constexpr int OFF_MISC = R6 + 32768;
constexpr int B_FULL = OFF_MISC;
constexpr int B_EMPTY = B_FULL + 48;
constexpr int B_EMPR = B_EMPTY + 48;
constexpr int B_VD = B_EMPR + 48;
constexpr int B_X = B_VD + 8;
constexpr int B_HX = B_X + 16;
constexpr int B_XF = B_HX + 8;
constexpr int B_S0 = B_XF + 8;
constexpr int B_S1 = B_S0 + 8;
constexpr int B_EA = B_S1 + 8;
constexpr int B_S2 = B_EA + 8;
constexpr int B_S3 = B_S2 + 8;
constexpr int B_D6 = B_S3 + 8;
constexpr int B_DL = B_D6 + 8;
constexpr int B_GATE = B_DL + 32;
constexpr int B_SIDE = B_GATE + 8;
constexpr int B_FFN = B_SIDE + 8;
constexpr int B_R6 = B_FFN + 32;
constexpr int B_LAND = B_R6 + 8;
constexpr int B_VAL = B_LAND + 48;
constexpr int B_TH = B_VAL + 96;
constexpr int M_TH = B_TH + 24;
constexpr int NBAR = (M_TH - B_EMPTY) / 8;
constexpr int M_KEY = M_TH + 12;
constexpr int M_PAR = M_KEY + 4;
constexpr int M_ROLE = M_PAR + 4;
constexpr int M_HX = OFF_MISC + 544;
constexpr int M_G = M_HX + 256;
constexpr int M_UPD = M_G + 512;
constexpr int M_RED = M_UPD + 512;
constexpr int SMEM_BYTES = 232448;
static_assert(M_RED + 512 <= SMEM_BYTES && M_ROLE + 4 <= M_HX, "smem");

struct Params {
    const bf16 *gate_w, *w_r, *dre, *dim;
    CUtensorMap mCre, mCim, mX2, mX, mDre, mDim, mF, mWg, mWu, mWd;
};

struct CPtr { const char* c[2]; };

struct Scratch {
    uint32_t frag[NCTA * 2 * 4096];
    uint32_t stamp[NCTA * 32];
    uint32_t gate[S_];
    uint32_t keys[8 * NCTA];
    uint32_t part[FFN_CTAS / 2 * D_];
    uint32_t phint[4 * 8 * 8];
    uint32_t upd[D_];
    uint32_t epoch[NCTA + 4];
};
__device__ __align__(1024) Scratch g_scr;

__device__ __forceinline__ uint32_t smem_u32(const void* p) { return (uint32_t)__cvta_generic_to_shared(p); }
__device__ __forceinline__ void mbar_init(uint32_t bar, uint32_t cnt) {
    asm volatile("mbarrier.init.shared::cta.b64 [%0], %1;" ::"r"(bar), "r"(cnt) : "memory");
}
__device__ __forceinline__ void mbar_expect_tx(uint32_t bar, uint32_t bytes) {
    asm volatile("mbarrier.arrive.expect_tx.shared::cta.b64 _, [%0], %1;" ::"r"(bar), "r"(bytes) : "memory");
}
__device__ __forceinline__ void mbar_arrive(uint32_t bar) {
    asm volatile("mbarrier.arrive.shared::cta.b64 _, [%0];" ::"r"(bar) : "memory");
}
template <int N>
__device__ __forceinline__ void mbar_arrive_n_if(uint32_t bar, bool pred) {
    asm volatile("{.reg .pred p; setp.ne.b32 p, %1, 0; @p mbarrier.arrive.shared::cta.b64 _, [%0], %2;}" ::"r"(bar), "r"((int)pred), "n"(N) : "memory");
}
__device__ __forceinline__ void mbar_arrive_if(uint32_t bar, bool pred) {
    asm volatile("{.reg .pred p; setp.ne.b32 p, %1, 0; @p mbarrier.arrive.shared::cta.b64 _, [%0];}" ::"r"(bar), "r"((int)pred) : "memory");
}
__device__ __forceinline__ void mbar_arrive_warp(uint32_t bar) {
    __syncwarp();
    mbar_arrive_if(bar, (threadIdx.x & 31) == 0);
}
__device__ __forceinline__ void mbar_arrive_cluster_if(uint32_t bar, bool pred) {
    asm volatile("{.reg .pred p; setp.ne.b32 p, %1, 0; @p mbarrier.arrive.shared::cluster.b64 _, [%0], 1;}"
                 ::"r"(bar), "r"((int)pred) : "memory");
}
__device__ __forceinline__ uint32_t mapa(uint32_t a, uint32_t cta) {
    uint32_t r;
    asm volatile("mapa.shared::cluster.u32 %0, %1, %2;" : "=r"(r) : "r"(a), "r"(cta));
    return r;
}
__device__ __forceinline__ bool mbar_try(uint32_t bar, uint32_t parity) {
    uint32_t ok;
    asm volatile("{.reg .pred p; mbarrier.try_wait.parity.shared::cta.b64 p, [%1], %2; selp.u32 %0,1,0,p;}"
                 : "=r"(ok) : "r"(bar), "r"(parity) : "memory");
    return ok;
}
__device__ __forceinline__ bool mbar_test(uint32_t bar, uint32_t parity) {
    uint32_t ok;
    asm volatile("{.reg .pred p; mbarrier.test_wait.parity.shared::cta.b64 p, [%1], %2; selp.u32 %0,1,0,p;}"
                 : "=r"(ok) : "r"(bar), "r"(parity) : "memory");
    return ok;
}
__device__ __forceinline__ void mbar_wait(uint32_t bar, uint32_t parity) {
    uint32_t n = 0;
#pragma unroll 1
    while (!mbar_try(bar, parity)) { if (++n > SPIN_LIMIT) break; }
}
__device__ __forceinline__ void tma2d_elect(uint32_t dst, const CUtensorMap* m, int c0, int c1, uint32_t bar) {
    asm volatile("{.reg .pred p; elect.sync _|p, 0xffffffff;"
                 " @p cp.async.bulk.tensor.2d.shared::cluster.global.mbarrier::complete_tx::bytes [%0], [%1, {%3,%4}], [%2];}"
                 ::"r"(dst), "l"(m), "r"(bar), "r"(c0), "r"(c1) : "memory");
}
__device__ __forceinline__ void tma2d_pair_elect(uint32_t dst, const CUtensorMap* m, int c0, int c1, uint32_t bar) {
    asm volatile("{.reg .pred p; elect.sync _|p, 0xffffffff;"
                 " @p cp.async.bulk.tensor.2d.shared::cluster.global.mbarrier::complete_tx::bytes.multicast::cluster"
                 " [%0], [%1, {%3,%4}], [%2], %5;}" ::"r"(dst), "l"(m), "r"(bar), "r"(c0), "r"(c1), "h"((uint16_t)3) : "memory");
}
__device__ __forceinline__ void tma3d_elect(uint32_t dst, const CUtensorMap* m, int row, int chunk, uint32_t bar) {
    asm volatile("{.reg .pred p; elect.sync _|p, 0xffffffff;"
                 " @p cp.async.bulk.tensor.3d.shared::cluster.global.mbarrier::complete_tx::bytes [%0], [%1, {%3,%4,%5}], [%2];}"
                 ::"r"(dst), "l"(m), "r"(bar), "r"(0), "r"(row), "r"(chunk) : "memory");
}
__device__ __forceinline__ void tma5d_elect(uint32_t dst, const CUtensorMap* m, int c0, int c4, uint32_t bar) {
    asm volatile("{.reg .pred p; elect.sync _|p, 0xffffffff;"
                 " @p cp.async.bulk.tensor.5d.shared::cluster.global.mbarrier::complete_tx::bytes [%0], [%1, {%3,%5,%5,%5,%4}], [%2];}"
                 ::"r"(dst), "l"(m), "r"(bar), "r"(c0), "r"(c4), "r"(0) : "memory");
}
__device__ __forceinline__ void mbar_expect_tx_elect(uint32_t bar, uint32_t bytes) {
    asm volatile("{.reg .pred p; elect.sync _|p, 0xffffffff; @p mbarrier.arrive.expect_tx.shared::cta.b64 _, [%0], %1;}"
                 ::"r"(bar), "r"(bytes) : "memory");
}
__device__ __forceinline__ void prefetch_l2(const void* p) { asm volatile("prefetch.global.L2 [%0];" ::"l"(p)); }
__device__ __forceinline__ uint32_t ld_relaxed(const void* p) {
    uint32_t v;
    asm volatile("ld.relaxed.gpu.global.u32 %0, [%1];" : "=r"(v) : "l"(p) : "memory");
    return v;
}
__device__ __forceinline__ uint4 ld_relaxed4(const void* p) {
    uint4 v;
    asm volatile("ld.relaxed.gpu.global.v4.u32 {%0,%1,%2,%3}, [%4];" : "=r"(v.x), "=r"(v.y), "=r"(v.z), "=r"(v.w) : "l"(p) : "memory");
    return v;
}
__device__ __forceinline__ void st_relaxed(unsigned int* p, uint32_t v) {
    asm volatile("st.relaxed.gpu.global.u32 [%0], %1;" ::"l"(p), "r"(v) : "memory");
}
__device__ __forceinline__ uint32_t tagf(float v, uint32_t par) { return (__float_as_uint(v) & ~1u) | par; }
template <int BIT = 0>
__device__ __forceinline__ uint4 wait_tags(const unsigned int* p, uint32_t par) {
    uint32_t n = 0;
#pragma unroll 1
    while (true) {
        const uint4 v = ld_relaxed4(p);
        const uint32_t m = par ? (v.x & v.y & v.z & v.w) : ~(v.x | v.y | v.z | v.w);
        if (__all_sync(0xffffffffu, (m >> BIT) & 1u)) return v;
        __nanosleep(100);
        if (++n > SPIN_LIMIT) return v;
    }
}
__device__ __forceinline__ uint32_t best_key(const uint32_t* keys, uint32_t par) {
    const uint4 k = wait_tags<15>(keys + (threadIdx.x & 31) * 4, par);
    return __reduce_max_sync(0xffffffffu, max(max(k.x, k.y), max(k.z, k.w)));
}
__device__ __forceinline__ void named_bar(int id, int n) { asm volatile("bar.sync %0, %1;" ::"r"(id), "r"(n) : "memory"); }
template <int OFF>
__device__ __forceinline__ uint4 ldg_nc_off(const void* p) {
    uint4 v;
    asm volatile("ld.global.nc.v4.u32 {%0,%1,%2,%3}, [%4+%5];" : "=r"(v.x), "=r"(v.y), "=r"(v.z), "=r"(v.w) : "l"(p), "n"(OFF));
    return v;
}
__device__ __forceinline__ void ldg_nc_if(uint4& v, const void* a, bool pred) {
    asm volatile("{.reg .pred p; setp.ne.b32 p, %5, 0; @p ld.global.nc.v4.u32 {%0,%1,%2,%3}, [%4];}"
                 : "+r"(v.x), "+r"(v.y), "+r"(v.z), "+r"(v.w) : "l"(a), "r"((int)pred) : "memory");
}
template <int OFF>
__device__ __forceinline__ void stg_off(void* p, const uint4& v) {
    asm volatile("st.global.v4.u32 [%0+%5], {%1,%2,%3,%4};" ::"l"(p), "r"(v.x), "r"(v.y), "r"(v.z), "r"(v.w), "n"(OFF) : "memory");
}
__device__ __forceinline__ void sts128(uint32_t a, const uint4& v) {
    asm volatile("st.shared.v4.u32 [%0], {%1,%2,%3,%4};" ::"r"(a), "r"(v.x), "r"(v.y), "r"(v.z), "r"(v.w) : "memory");
}
__device__ __forceinline__ uint4 lds128(uint32_t a) {
    uint4 v;
    asm volatile("ld.shared.v4.u32 {%0,%1,%2,%3}, [%4];" : "=r"(v.x), "=r"(v.y), "=r"(v.z), "=r"(v.w) : "r"(a) : "memory");
    return v;
}
__device__ __forceinline__ void lds128_if(uint4& v, uint32_t a, bool pred) {
    asm volatile("{.reg .pred p; setp.ne.b32 p, %5, 0; @p ld.shared.v4.u32 {%0,%1,%2,%3}, [%4];}"
                 : "+r"(v.x), "+r"(v.y), "+r"(v.z), "+r"(v.w) : "r"(a), "r"((int)pred) : "memory");
}
__device__ __forceinline__ uint32_t lds32(uint32_t a) {
    uint32_t v;
    asm volatile("ld.shared.u32 %0, [%1];" : "=r"(v) : "r"(a) : "memory");
    return v;
}
__device__ __forceinline__ void st_async16(uint32_t dst, uint32_t x, uint32_t y, uint32_t z, uint32_t w, uint32_t bar) {
    asm volatile("st.async.weak.shared::cluster.mbarrier::complete_tx::bytes.v4.b32 [%0], {%1,%2,%3,%4}, [%5];"
                 ::"r"(dst), "r"(x), "r"(y), "r"(z), "r"(w), "r"(bar) : "memory");
}
__device__ __forceinline__ int sel(int a, int b, bool p) {
    int r;
    asm("{.reg .pred q; setp.ne.b32 q, %3, 0; selp.b32 %0, %1, %2, q;}" : "=r"(r) : "r"(a), "r"(b), "r"((int)p));
    return r;
}
__device__ __forceinline__ float selpf(float a, float b, bool p) {
    float r;
    asm("{.reg .pred q; setp.ne.b32 q, %3, 0; selp.f32 %0, %1, %2, q;}" : "=f"(r) : "f"(a), "f"(b), "r"((int)p));
    return r;
}
template <int N, int MASK, int SZ>
__device__ __forceinline__ void halve(float (&a)[SZ]) {
    const bool up = threadIdx.x & MASK;
#pragma unroll
    for (int j = 0; j < N; j++) a[j] = selpf(a[N + j], a[j], up) + __shfl_xor_sync(0xffffffffu, selpf(a[j], a[N + j], up), MASK);
}
__device__ __forceinline__ float bflo(uint32_t u) { return __uint_as_float(u << 16); }
__device__ __forceinline__ float bfhi(uint32_t u) { return __uint_as_float(u & 0xffff0000u); }
__device__ __forceinline__ uint32_t pack_bf16(float lo, float hi) {
    uint32_t r;
    asm("cvt.rn.bf16x2.f32 %0, %1, %2;" : "=r"(r) : "f"(hi), "f"(lo));
    return r;
}
__device__ __forceinline__ uint32_t hmul2_bf16(uint32_t a, uint32_t b) {
    uint32_t r;
    asm("mul.rn.bf16x2 %0, %1, %2;" : "=r"(r) : "r"(a), "r"(b));
    return r;
}
__device__ __forceinline__ float sigmoidf_(float v) { return 1.0f / (1.0f + __expf(-v)); }
__device__ __forceinline__ void wg_fence() { asm volatile("wgmma.fence.sync.aligned;" ::: "memory"); }
__device__ __forceinline__ void wg_commit() { asm volatile("wgmma.commit_group.sync.aligned;" ::: "memory"); }
template <int N> __device__ __forceinline__ void wg_wait() { asm volatile("wgmma.wait_group.sync.aligned %0;" ::"n"(N) : "memory"); }
__device__ __forceinline__ uint64_t desc_lo(uint32_t lo) { return (uint64_t)lo | (0x40000040ull << 32); }
template <int LO, int HI, int N>
__device__ __forceinline__ void fence_regs(float (&d)[N]) {
#pragma unroll
    for (int i = LO; i < HI; i++) asm volatile("" : "+f"(d[i])::"memory");
}
template <int LO, int HI, int N>
__device__ __forceinline__ void keep_regs(uint4 (&f)[N]) {
#pragma unroll
    for (int i = LO; i < HI; i++) asm volatile("" ::"r"(f[i].x), "r"(f[i].y), "r"(f[i].z), "r"(f[i].w) : "memory");
}
template <int TB = 1>
__device__ __forceinline__ void wgmma128(float (&d)[64], uint64_t da, uint64_t db, int scaleD) {
    asm volatile(
        "{ .reg .pred p; setp.ne.b32 p, %66, 0;\n"
        "wgmma.mma_async.sync.aligned.m64n128k16.f32.bf16.bf16 "
        "{%0,%1,%2,%3,%4,%5,%6,%7,%8,%9,%10,%11,%12,%13,%14,%15,%16,%17,%18,%19,%20,%21,%22,%23,%24,%25,%26,%27,%28,%29,%30,%31,"
        "%32,%33,%34,%35,%36,%37,%38,%39,%40,%41,%42,%43,%44,%45,%46,%47,%48,%49,%50,%51,%52,%53,%54,%55,%56,%57,%58,%59,%60,%61,%62,%63}, "
        "%64, %65, p, 1, 1, 0, %67;\n}"
        : "+f"(d[0]), "+f"(d[1]), "+f"(d[2]), "+f"(d[3]), "+f"(d[4]), "+f"(d[5]), "+f"(d[6]), "+f"(d[7]),
          "+f"(d[8]), "+f"(d[9]), "+f"(d[10]), "+f"(d[11]), "+f"(d[12]), "+f"(d[13]), "+f"(d[14]), "+f"(d[15]),
          "+f"(d[16]), "+f"(d[17]), "+f"(d[18]), "+f"(d[19]), "+f"(d[20]), "+f"(d[21]), "+f"(d[22]), "+f"(d[23]),
          "+f"(d[24]), "+f"(d[25]), "+f"(d[26]), "+f"(d[27]), "+f"(d[28]), "+f"(d[29]), "+f"(d[30]), "+f"(d[31]),
          "+f"(d[32]), "+f"(d[33]), "+f"(d[34]), "+f"(d[35]), "+f"(d[36]), "+f"(d[37]), "+f"(d[38]), "+f"(d[39]),
          "+f"(d[40]), "+f"(d[41]), "+f"(d[42]), "+f"(d[43]), "+f"(d[44]), "+f"(d[45]), "+f"(d[46]), "+f"(d[47]),
          "+f"(d[48]), "+f"(d[49]), "+f"(d[50]), "+f"(d[51]), "+f"(d[52]), "+f"(d[53]), "+f"(d[54]), "+f"(d[55]),
          "+f"(d[56]), "+f"(d[57]), "+f"(d[58]), "+f"(d[59]), "+f"(d[60]), "+f"(d[61]), "+f"(d[62]), "+f"(d[63])
        : "l"(da), "l"(db), "r"(scaleD), "n"(TB));
}
__device__ __forceinline__ void wgmma128rs(float (&d)[64], const uint4& a, uint64_t db, int scaleD) {
    asm volatile(
        "{ .reg .pred p; setp.ne.b32 p, %69, 0;\n"
        "wgmma.mma_async.sync.aligned.m64n128k16.f32.bf16.bf16 "
        "{%0,%1,%2,%3,%4,%5,%6,%7,%8,%9,%10,%11,%12,%13,%14,%15,%16,%17,%18,%19,%20,%21,%22,%23,%24,%25,%26,%27,%28,%29,%30,%31,"
        "%32,%33,%34,%35,%36,%37,%38,%39,%40,%41,%42,%43,%44,%45,%46,%47,%48,%49,%50,%51,%52,%53,%54,%55,%56,%57,%58,%59,%60,%61,%62,%63}, "
        "{%64,%65,%66,%67}, %68, p, 1, 1, 0;\n}"
        : "+f"(d[0]), "+f"(d[1]), "+f"(d[2]), "+f"(d[3]), "+f"(d[4]), "+f"(d[5]), "+f"(d[6]), "+f"(d[7]),
          "+f"(d[8]), "+f"(d[9]), "+f"(d[10]), "+f"(d[11]), "+f"(d[12]), "+f"(d[13]), "+f"(d[14]), "+f"(d[15]),
          "+f"(d[16]), "+f"(d[17]), "+f"(d[18]), "+f"(d[19]), "+f"(d[20]), "+f"(d[21]), "+f"(d[22]), "+f"(d[23]),
          "+f"(d[24]), "+f"(d[25]), "+f"(d[26]), "+f"(d[27]), "+f"(d[28]), "+f"(d[29]), "+f"(d[30]), "+f"(d[31]),
          "+f"(d[32]), "+f"(d[33]), "+f"(d[34]), "+f"(d[35]), "+f"(d[36]), "+f"(d[37]), "+f"(d[38]), "+f"(d[39]),
          "+f"(d[40]), "+f"(d[41]), "+f"(d[42]), "+f"(d[43]), "+f"(d[44]), "+f"(d[45]), "+f"(d[46]), "+f"(d[47]),
          "+f"(d[48]), "+f"(d[49]), "+f"(d[50]), "+f"(d[51]), "+f"(d[52]), "+f"(d[53]), "+f"(d[54]), "+f"(d[55]),
          "+f"(d[56]), "+f"(d[57]), "+f"(d[58]), "+f"(d[59]), "+f"(d[60]), "+f"(d[61]), "+f"(d[62]), "+f"(d[63])
        : "r"(a.x), "r"(a.y), "r"(a.z), "r"(a.w), "l"(db), "r"(scaleD));
}
__device__ __forceinline__ uint32_t clk() { uint64_t c; asm volatile("mov.u64 %0, %%clock64;" : "=l"(c)::"memory"); return (uint32_t)c; }
__device__ __forceinline__ uint32_t gtime() { uint64_t t; asm volatile("mov.u64 %0, %%globaltimer;" : "=l"(t)::"memory"); return (uint32_t)t; }
__device__ __forceinline__ void until(uint32_t t) { while (t - clk() < 0x8000u) {} }
__device__ __forceinline__ void nap_until(uint32_t t) { while (t - clk() < 0x8000u) __nanosleep(20); }
__device__ __forceinline__ uint4 scale_add(float s, const float (&a)[64], int o, const uint4& w) {
    return make_uint4(pack_bf16(fmaf(s, a[o], bflo(w.x)), fmaf(s, a[o + 1], bfhi(w.x))), pack_bf16(fmaf(s, a[o + 4], bflo(w.y)), fmaf(s, a[o + 5], bfhi(w.y))),
                      pack_bf16(fmaf(s, a[o + 8], bflo(w.z)), fmaf(s, a[o + 9], bfhi(w.z))), pack_bf16(fmaf(s, a[o + 12], bflo(w.w)), fmaf(s, a[o + 13], bfhi(w.w))));
}

__device__ __forceinline__ uint32_t router_key(float score, int row) {
    const float r = score + 0.0f;
    uint32_t u = pack_bf16(r, 0.f) & 0xffffu;
    u = (u & 0x8000u) ? (~u & 0xffffu) : (u | 0x8000u);
    if (r != r) u = 0;
    return (u << 16) | (uint32_t)(0x7fff - row);
}

#define g_ab g_scr.frag
#define g_fb_h ((float*)g_scr.part)
#define g_fb_upd (g_fb_h + 2048)
#define g_fb_gate (g_fb_h + 4096)
#define g_fb_keys (g_scr.part + 8192)
__global__ void fb_hidden(const bf16* x, const bf16* dre, const bf16* dim, const bf16* gw, const bf16* wr) {
    __shared__ float xs[D_];
    const int s = blockIdx.x, t = threadIdx.x;
    xs[t] = __bfloat162float(x[s * D_ + t]);
    __syncthreads();
    float a = 0.f, b = 0.f;
    for (int d = 0; d < D_; d++) { a = fmaf(xs[d], __bfloat162float(dre[t * D_ + d]), a); b = fmaf(xs[d], __bfloat162float(dim[t * D_ + d]), b); }
    ((bf16*)g_ab)[s * 1024 + t] = __float2bfloat16(a);
    ((bf16*)g_ab)[s * 1024 + 512 + t] = __float2bfloat16(b);
    if (t == 0) {
        float u = 0.f, v = 0.f;
        for (int d = 0; d < D_; d++) { u = fmaf(xs[d], __bfloat162float(gw[d]), u); v = fmaf(xs[d], __bfloat162float(wr[d]), v); }
        g_fb_gate[s] = sigmoidf_(u);
        g_fb_keys[s] = router_key(v, s);
    }
}
__device__ uint32_t fb_best() {
    uint32_t k = 0;
    for (int i = 0; i < S_; i++) k = max(k, g_fb_keys[i]);
    return k;
}
__global__ void fb_ffn1(const bf16* x, const bf16* wg, const bf16* wu) {
    const int f = blockIdx.x * blockDim.x + threadIdx.x, idx = 0x7fff - (int)(fb_best() & 0x7fffu);
    float a = 0.f, b = 0.f;
    for (int d = 0; d < D_; d++) {
        const float xv = __bfloat162float(x[idx * D_ + d]);
        a = fmaf(xv, __bfloat162float(wg[d * F_ + f]), a); b = fmaf(xv, __bfloat162float(wu[d * F_ + f]), b);
    }
    g_fb_h[f] = a * sigmoidf_(a) * b;
}
__global__ void fb_ffn2(const bf16* wd) {
    const int e = blockIdx.x * blockDim.x + threadIdx.x;
    const uint32_t u = fb_best() >> 16, rb = (u & 0x8000u) ? (u & 0x7fffu) : (~u & 0xffffu);
    float a = 0.f;
    for (int f = 0; f < F_; f++) a = fmaf(g_fb_h[f], __bfloat162float(wd[f * D_ + e]), a);
    g_fb_upd[e] = a * sigmoidf_(__uint_as_float(rb << 16));
}
__global__ void fb_seq(const bf16* x, const bf16* cre, const bf16* cim, bf16* out) {
    __shared__ float c[2][S_];
    __shared__ int idx;
    const int t = blockIdx.x, e = threadIdx.x;
    for (int i = e; i < S_; i += D_) { c[0][i] = __bfloat162float(cre[t * S_ + i]); c[1][i] = __bfloat162float(cim[t * S_ + i]); }
    if (e == 0) idx = 0x7fff - (int)(fb_best() & 0x7fffu);
    __syncthreads();
    float y = 0.f;
    for (int s = 0; s < S_; s++)
        y += c[0][s] * __bfloat162float(((const bf16*)g_ab)[s * 1024 + e]) - c[1][s] * __bfloat162float(((const bf16*)g_ab)[s * 1024 + 512 + e]);
    const float g = g_fb_gate[t];
    out[t * D_ + e] = __float2bfloat16(g * y + (1.f - g) * (__bfloat162float(x[t * D_ + e]) + (t == idx ? g_fb_upd[e] : 0.f)));
}

__device__ __forceinline__ void spare_job(const Params& p, Scratch* g, unsigned char* smem, int sp, uint32_t tstart) {
    const int tid = threadIdx.x, warp = tid >> 5, lane = tid & 31;
    if (warp >= 8) {
        asm volatile("barrier.cluster.wait.acquire.aligned;" ::: "memory");
        mbar_wait(smem_u32(smem) + B_FULL, 0);
#pragma unroll 1
        for (int i = 0; i < 16; i++) {
            nap_until(tstart + PFD_T0 + i * (PFD_DT / 2));
            prefetch_l2((const char*)((sp & 2) ? p.dim : p.dre) + (sp & 1) * 262144 + i * 16384 + (tid - 256) * 128);
        }
        return;
    }
    nap_until(tstart + SUM_T0 - 2000);
    const uint32_t e1 = ld_relaxed(g->epoch + NCTA + sp) + 1u, par = e1 & 1u;
    const uint32_t u = best_key(g->keys + warp * NCTA, par) >> 16;
    const float rs = sigmoidf_(__uint_as_float(((u & 0x8000u) ? (u & 0x7fffu) : (~u & 0xffffu)) << 16));
    nap_until(tstart + SUM_T0);
    uint32_t n = 0;
#pragma unroll 1
    while ((int)(ld_relaxed(g->phint + (sp * 8 + warp) * 8) - e1 * 14u) < 0) {
        __nanosleep(40);
        if (++n > SPIN_LIMIT) break;
    }
    const unsigned int* src = g->part + warp * 7 * D_ + sp * 128 + lane * 4;
    uint4 v[7];
#pragma unroll 1
    while (true) {
        uint32_t bad = 0;
#pragma unroll
        for (int i = 0; i < 7; i++) v[i] = ld_relaxed4(src + i * D_);
#pragma unroll
        for (int i = 0; i < 7; i++) bad |= (v[i].x ^ par) | (v[i].y ^ par) | (v[i].z ^ par) | (v[i].w ^ par);
        if (!__any_sync(0xffffffffu, bad & 1u)) break;
        if (++n > SPIN_LIMIT) break;
    }
    float4 s = make_float4(0.f, 0.f, 0.f, 0.f);
#pragma unroll
    for (int i = 0; i < 7; i++) {
        s.x += __uint_as_float(v[i].x); s.y += __uint_as_float(v[i].y);
        s.z += __uint_as_float(v[i].z); s.w += __uint_as_float(v[i].w);
    }
    float* acc = (float*)(smem + R6);
    *(float4*)&acc[warp * 128 + lane * 4] = s;
    named_bar(1, 256);
    if (tid < 128) {
        float t = 0.f;
#pragma unroll
        for (int i = 0; i < 8; i++) t += acc[i * 128 + tid];
        st_relaxed(&g->upd[sp * 128 + tid], tagf(t * rs, par));
        if (tid == 0) st_relaxed(g->epoch + NCTA + sp, e1);
    }
}

__device__ __forceinline__ int ffn_pair(int role) { return role - __popcll(NOFFN_MASK & ((1ull << role) - 1)); }
__device__ __forceinline__ int other(int i, int tn) { return i + (i >= tn); }
__device__ __forceinline__ int dcol(int p, int tn) { return p < 2 ? tn * 128 + p * 64 : other((p - 2) % 3, tn) * 128 + (p >= 5 ? 64 : 0); }

template <int H>
__device__ __forceinline__ void fetch_job(const Params& p, Scratch* g, unsigned char* smem, uint32_t sb, int cta, int i, uint32_t par) {
    const int lane = threadIdx.x & 31, comp = cta & 1;
    const int j = other(i, (cta >> 1) & 3), src = (cta & ~6) + 2 * j;
    const int slot = i == 0 ? 29 % NST : i - 1;
    const uint32_t land = sb + B_LAND + 8 * (3 * H + i);
    uint32_t ph = 0, th;
    mbar_expect_tx_elect(land, 8192);
    if (H == 0) {
        mbar_wait(sb + B_S0, 0);
        const uint32_t t0 = clk();
        if (i == 0) {
            mbar_wait(sb + B_FULL + 8 * (31 % NST), (31 / NST) & 1);
            const uint32_t t1 = t0 + max(clk() - t0, 180u) - 180u;
            asm volatile("{.reg .pred p; .reg .b64 t; setp.eq.b32 p, %3, 0; mov.b64 t, {%1, %2}; @p st.relaxed.gpu.global.b64 [%0], t;}"
                         ::"l"(g->stamp + cta * 32), "r"((t1 & ~1u) | par), "r"(gtime()), "r"(lane) : "memory");
        }
        until(t0 + SDEL);
        uint32_t gt;
#pragma unroll 1
        for (uint32_t n = 0; n < SPIN_LIMIT; n++) {
            asm volatile("{.reg .b64 t; ld.relaxed.gpu.global.b64 t, [%2]; mov.b64 {%0,%1}, t;}" : "=r"(th), "=r"(gt) : "l"(g->stamp + src * 32) : "memory");
            if (!__any_sync(0xffffffffu, (th ^ par) & 1u)) break;
        }
        const uint32_t ns = min(gtime() - gt, 4096u), now = clk();
        if (now - th >= 8192u) th = now - (ns + (ns >> 1) + (ns >> 4));
        th += SG * j;
        if (lane == 0) { *(volatile uint32_t*)(smem + M_TH + 4 * i) = th; mbar_arrive(sb + B_TH + 8 * i); }
        __syncwarp();
    } else {
        mbar_wait(sb + B_TH + 8 * i, 0);
        th = lds32(sb + M_TH + 4 * i);
    }
    mbar_wait(sb + B_EA, 0);
#pragma unroll 1
    for (int c = 0; c < 2; c++) {
        const uint32_t dst = sb + slot * 16384 + (c ? NST * 16384 + H * 8192 : (comp ^ H) * 8192);
        if (c != H) mbar_wait(sb + B_EMPTY + 8 * slot, i != 0);
        until(th + (c ? (H ? L_RD1 : L_RD0) : (H ? E_RD1 : E_RD0)));
#pragma unroll 1
        for (uint32_t r = 0; r < SPIN_LIMIT; r++) {
            tma2d_elect(dst, &p.mF, 0, (src * 2 + (comp ^ c)) * 128 + H * 64, land);
            mbar_wait(land, ph);
            ph ^= 1;
            const uint32_t a = dst + (lane >> 2) * 132 + (lane & 3) * 32;
            uint32_t v[8], m0 = 0, m1 = ~0u;
#pragma unroll
            for (int k = 0; k < 8; k++) v[k] = lds32(a + k * 1024);
#pragma unroll
            for (int k = 0; k < 8; k++) { m0 |= v[k]; m1 &= v[k]; }
            if (__all_sync(0xffffffffu, (par ? m1 : ~m0) & 1u)) break;
            mbar_expect_tx_elect(land, 8192);
        }
        mbar_arrive_if(sb + B_VAL + 8 * (6 * c + 3 * H + i), lane == 0);
        if (c == 0) mbar_expect_tx_elect(land, 8192);
    }
}

__global__ void __cluster_dims__(2, 1, 1) __launch_bounds__(NTHREADS, 1)
fused_kernel(const __grid_constant__ CPtr pc, const char* px, char* pout, Scratch* g, const __grid_constant__ Params p) {
    extern __shared__ __align__(1024) unsigned char smem[];
    const uint32_t sb = smem_u32(smem);
    const int tid = threadIdx.x, warp = tid >> 5, lane = tid & 31;
    const int rank = blockIdx.x & 1;
    const char* pcr = pc.c[rank];
    asm volatile("{.reg .pred p; setp.lt.u32 p, %1, 32; @p prefetch.global.L2 [%0];}"
                 ::"l"(pcr + (uint32_t)(((blockIdx.x << 16) & 0x7e0000) + (tid << 12))), "r"(tid));
    const uint32_t tstart = clk();
    asm volatile("{.reg .pred p; setp.lt.u32 p, %1, 4; @p prefetch.global.L2 [%0];}"
                 ::"l"(px + (uint32_t)(((blockIdx.x << 9) & 0xfe00) + (tid << 7))), "r"(tid));
    uint32_t smid;
    asm volatile("mov.u32 %0, %%smid;" : "=r"(smid));
    const int u = smid >> 1;
    const int code = sel(u, sel(((u - 32) * 293) >> 8, 8 * u - 489, u < 60), u < 32);
    const int tn = code >> 3, tm = (code & 7) + sel(0, 8, u < 32);
    const int comp = rank;
    const CUtensorMap* mC = &p.mCre + comp;
#define ARM(j) do { mbar_init(sb + B_FULL + 8 * (j), 1); mbar_expect_tx(sb + B_FULL + 8 * (j), 32768); } while (0)
#define STEP0(j) do { tma2d_elect(sb + (j) * 16384, mC, (j) * 64, tm * 128, sb + B_FULL + 8 * (j));                            \
                      tma3d_elect(sb + (NST + (j)) * 16384, &p.mX2, (j) * 64, tn * 2, sb + B_FULL + 8 * (j)); } while (0)
    if (__all_sync(0xffffffffu, warp == 12)) {
        asm volatile("{.reg .pred p; elect.sync _|p, 0xffffffff; @p mbarrier.init.shared::cta.b64 [%0], 1;}" ::"r"(sb + B_FULL) : "memory");
        STEP0(0);
        mbar_expect_tx_elect(sb + B_FULL, 32768);
    }
    const bool spare = tn < 0;
    const int role = tm * 4 + tn, cta = role * 2 + rank;
    const int wu = __shfl_sync(0xffffffffu, warp, 0);
    if (wu < 12) {
        if (lane == 0) {
            mbar_init(sb + B_EMPTY + 8 * wu, 2);
            mbar_init(sb + B_VD + 8 * wu, wu ? 1 : 4);
#pragma unroll
            for (int i = 24; i < NBAR; i += 12) if (i + 12 <= NBAR || wu < NBAR - i) mbar_init(sb + B_EMPTY + 8 * (i + wu), 1);
            if (wu >= 1 && wu < 4) mbar_expect_tx(sb + B_VD + 8 * wu, wu < 3 ? 8192 : 256);
        }
        asm volatile("fence.mbarrier_init.release.cluster;" ::: "memory");
        __syncwarp();
        asm volatile("barrier.cluster.arrive.relaxed.aligned;" ::: "memory");
        if (spare) {
            spare_job(p, g, smem, smid & 3, tstart);
        } else if (wu >= 8) {
            asm volatile("setmaxnreg.dec.sync.aligned.u32 " STR(RS_) ";");
            asm volatile("barrier.cluster.wait.acquire.aligned;" ::: "memory");
            const int t = tid - 256, w = wu - 8, fr = ffn_pair(role);
            const bool ffn = !((NOFFN_MASK >> role) & 1);
            nap_until(tstart + SIDE_T0);
            const uint4 gw0 = ldg_nc_off<0>(p.gate_w + lane * 8), gw1 = ldg_nc_off<512>(p.gate_w + lane * 8);
            const uint4 rw0 = ldg_nc_off<0>(p.w_r + lane * 8), rw1 = ldg_nc_off<512>(p.w_r + lane * 8);
            const uint32_t par = ~ld_relaxed(g->epoch + cta) & 1u;
            nap_until(tstart + ROUTER_T0 + (2 * w + rank) * ROUTER_DT);
            {
                const int row0 = cta * 16 + w * 4;
                const char* xp = px + (uint32_t)row0 * (D_ * 2) + lane * 16;
                uint4 xa[4], xb[4];
                xa[0] = ldg_nc_off<0>(xp);    xb[0] = ldg_nc_off<512>(xp);  xa[1] = ldg_nc_off<1024>(xp); xb[1] = ldg_nc_off<1536>(xp);
                xa[2] = ldg_nc_off<2048>(xp); xb[2] = ldg_nc_off<2560>(xp); xa[3] = ldg_nc_off<3072>(xp); xb[3] = ldg_nc_off<3584>(xp);
                float a[8];
#pragma unroll
                for (int i = 0; i < 4; i++) {
                    const uint32_t xv[8] = {xa[i].x, xa[i].y, xa[i].z, xa[i].w, xb[i].x, xb[i].y, xb[i].z, xb[i].w};
                    const uint32_t gv[8] = {gw0.x, gw0.y, gw0.z, gw0.w, gw1.x, gw1.y, gw1.z, gw1.w};
                    const uint32_t rv[8] = {rw0.x, rw0.y, rw0.z, rw0.w, rw1.x, rw1.y, rw1.z, rw1.w};
                    float uu = 0.f, vv = 0.f;
#pragma unroll
                    for (int j = 0; j < 8; j++) {
                        uu = fmaf(bflo(xv[j]), bflo(gv[j]), uu); uu = fmaf(bfhi(xv[j]), bfhi(gv[j]), uu);
                        vv = fmaf(bflo(xv[j]), bflo(rv[j]), vv); vv = fmaf(bfhi(xv[j]), bfhi(rv[j]), vv);
                    }
                    a[i] = uu; a[4 + i] = vv;
                }
                halve<4, 16>(a); halve<2, 8>(a); halve<1, 4>(a);
                {
                    const float b1 = __shfl_xor_sync(0xffffffffu, a[0], 1), b2 = __shfl_xor_sync(0xffffffffu, a[0], 2),
                                b3 = __shfl_xor_sync(0xffffffffu, a[0], 3);
                    a[0] = (a[0] + b1) + (b2 + b3);
                }
                const int row = row0 + ((lane >> 2) & 3);
                const uint32_t best = __reduce_max_sync(0xffffffffu, lane >= 16 && (lane & 3) == 0 ? router_key(a[0], row) : 0u);
                if (lane <= 16 && (lane & 3) == 0)
                    *(volatile uint32_t*)(smem + M_RED + (lane < 16 ? w * 16 + lane : 64 + w * 4)) = lane < 16 ? tagf(sigmoidf_(a[0]), par) : best;
                named_bar(1, 128);
                if (t < 8) {
                    const uint4 k = lds128(sb + M_RED + 64);
                    asm volatile("{.reg .b32 old; atom.relaxed.gpu.global.exch.b32 old, [%0], %1;}"
                                 ::"l"(g->keys + t * NCTA + cta), "r"(max(max(k.x, k.y), max(k.z, k.w)) | (par << 15)) : "memory");
                }
                if (w == 1 && lane < 16) st_relaxed(g->gate + cta * 16 + lane, lds32(sb + M_RED + lane * 4));
            }
            uint32_t vd[32];
            if (ffn) {
                mbar_wait(sb + B_FFN + 24, 0);
#pragma unroll
                for (int j = 0; j < 32; j++) vd[j] = lds32(sb + R6 + ((j >> 3) & 1) * 16384 + (2 + (j >> 4)) * 4096 + (j & 7) * 512 + t * 4);
                mbar_arrive_warp(sb + B_VD);
            }
            mbar_wait(sb + B_GATE, 0);
            const int idx = 0x7fff - (int)(*(volatile uint32_t*)(smem + M_KEY) & 0x7fffu);
            if (ffn) {
                float a[16];
#pragma unroll
                for (int i = 0; i < 16; i++) a[i] = 0.f;
#pragma unroll 1
                for (int qu = 0; qu < 4; qu++) {
                    mbar_wait(sb + B_FFN + 8 * qu, qu == 3);
#pragma unroll
                    for (int i = 2 * qu; i < 2 * qu + 2; i++) {
                        const float xs = __bfloat162float(((const bf16*)(smem + M_UPD))[32 * i + (t >> 2)]);
                        const uint4 vg = lds128(sb + R6 + i * 2048 + t * 16);
                        const uint4 vu = lds128(sb + R6 + 16384 + i * 2048 + t * 16);
                        const uint32_t g4[4] = {vg.x, vg.y, vg.z, vg.w};
                        const uint32_t u4[4] = {vu.x, vu.y, vu.z, vu.w};
#pragma unroll
                        for (int j = 0; j < 4; j++) {
                            a[2 * j] = fmaf(xs, bflo(g4[j]), a[2 * j]);         a[2 * j + 1] = fmaf(xs, bfhi(g4[j]), a[2 * j + 1]);
                            a[8 + 2 * j] = fmaf(xs, bflo(u4[j]), a[8 + 2 * j]); a[9 + 2 * j] = fmaf(xs, bfhi(u4[j]), a[9 + 2 * j]);
                        }
                    }
                }
                named_bar(1, 128);
                mbar_arrive_if(sb + B_R6, t == 0);
                halve<8, 16>(a); halve<4, 8>(a); halve<2, 4>(a);
                float* red = (float*)(smem + M_UPD);
                *(float2*)&red[w * 64 + (lane >> 4) * 32 + (lane & 3) * 8 + ((lane >> 2) & 3) * 2] = make_float2(a[0], a[1]);
                named_bar(1, 128);
                const float sg = red[lane] + red[64 + lane] + red[128 + lane] + red[192 + lane];
                const float su = red[32 + lane] + red[96 + lane] + red[160 + lane] + red[224 + lane];
                if (w < 2) {
                    asm volatile("st.async.weak.shared::cluster.mbarrier::complete_tx::bytes.f32 [%0], %1, [%2];"
                                 ::"r"(mapa(sb + M_HX + t * 4, rank ^ 1)), "f"(w ? su : sg), "r"(mapa(sb + B_HX, rank ^ 1)) : "memory");
                }
                named_bar(1, 128);
                mbar_wait(sb + B_HX, 0);
                const float pg = ((const float*)(smem + M_HX))[lane], pu = ((const float*)(smem + M_HX))[32 + lane];
                const float gs = sg + pg, us = su + pu;
                float* hrow = red + w * 32;
                hrow[lane] = gs * sigmoidf_(gs) * us;
                __syncwarp();
                float o0 = 0.f, o1 = 0.f;
#pragma unroll
                for (int j4 = 0; j4 < 8; j4++) {
                    const float4 hv = *(const float4*)&hrow[j4 * 4];
                    o0 = fmaf(hv.x, bflo(vd[4 * j4]), o0);     o1 = fmaf(hv.x, bfhi(vd[4 * j4]), o1);
                    o0 = fmaf(hv.y, bflo(vd[4 * j4 + 1]), o0); o1 = fmaf(hv.y, bfhi(vd[4 * j4 + 1]), o1);
                    o0 = fmaf(hv.z, bflo(vd[4 * j4 + 2]), o0); o1 = fmaf(hv.z, bfhi(vd[4 * j4 + 2]), o1);
                    o0 = fmaf(hv.w, bflo(vd[4 * j4 + 3]), o0); o1 = fmaf(hv.w, bfhi(vd[4 * j4 + 3]), o1);
                }
                asm volatile("st.relaxed.gpu.global.v2.u32 [%0], {%1,%2};" ::"l"(&g->part[fr * D_ + rank * 256 + t * 2]),
                             "r"(tagf(o0, par)), "r"(tagf(o1, par)) : "memory");
                if (lane == 0) asm volatile("red.relaxed.gpu.global.add.u32 [%0], 1;" ::"l"(g->phint + ((rank * 2 + (w >> 1)) * 8 + fr / 7) * 8) : "memory");
            }
            if (!ffn) mbar_arrive_if(sb + B_R6, t == 0);
            if (w < 3) {
                fetch_job<1>(p, g, smem, sb, cta, w, par);
            } else {
                if (lds32(sb + M_ROLE) != (uint32_t)role) __trap();
                if ((idx >> 6) == 2 * tm + comp) {
                    const uint4 u4 = wait_tags(g->upd + tn * 128 + lane * 4, par);
                    const float og = 1.f - ((const float*)(smem + M_G))[idx & 127];
                    *(float4*)(smem + M_RED + lane * 16) = make_float4(og * __uint_as_float(u4.x), og * __uint_as_float(u4.y),
                                                                       og * __uint_as_float(u4.z), og * __uint_as_float(u4.w));
                    mbar_arrive_warp(sb + B_SIDE);
                }
            }
        } else {
            const int wg = wu >> 2;
            const uint32_t sbd = (sb & 0x3FFFF) >> 4;
            const bool lead = (tid & 127) == 0;
            const bool early = wg == comp;
            const int q = lane & 3;
            const int r0 = (warp & 3) * 16 + (lane >> 2);
            float acc[64];
            const uint32_t da0 = sbd + 0x10000 + wg * 512, db0 = sbd + 0x2000000, dd0 = sbd + 0x10000;
            const uint32_t rE = mapa(sb + B_EMPR, rank ^ 1);
#define WAITFULL(s) mbar_wait(sb + B_FULL + 8 * ((s) % NST), ((s) / NST) & 1)
#define TESTFULL(s) mbar_test(sb + B_FULL + 8 * ((s) % NST), ((s) / NST) & 1)
#define WAITD(pos) do { if ((pos) >= 4) mbar_wait(sb + B_DL + 8 * ((pos) & 3), 0); else if ((pos) >= 2) mbar_wait(sb + B_D6, 0); else WAITFULL(32); } while (0)
#define MMA_A(s, kk) wgmma128(acc, desc_lo(da0 + a_addr(s) / 16 + (kk) * 2), desc_lo(db0 + b_addr(s) / 16 + (kk) * 128), 1)
            asm volatile("setmaxnreg.inc.sync.aligned.u32 " STR(RC) ";");
            asm volatile("barrier.cluster.wait.acquire.aligned;" ::: "memory");
            WAITFULL(0);
            wg_fence();
#pragma unroll
            for (int kk = 0; kk < 4; kk++) wgmma128(acc, desc_lo(da0 + kk * 2), desc_lo(db0 + b_addr(0) / 16 + kk * 128), kk != 0);
            wg_commit();
            int slot = 1, ph = 0, pslot = 0;
            const uint32_t ooff = (uint32_t)((tm * 128 + wg * 64 + r0) * D_ + tn * 128 + q * 8) * 2u;
            uint32_t* fout = g->frag + (cta * 2 + wg) * 4096 + (warp & 3) * 128 + lane;
            uint32_t tagm[4];
#pragma unroll
            for (int c = 0; c < 4; c++) tagm[c] = (lane & 7) == (warp & 1) * 4 + c;
            const char* xp = px + ooff;
            asm volatile("" : "+r"(tagm[0]), "+r"(tagm[1]), "+r"(tagm[2]), "+r"(tagm[3]), "+l"(xp), "+l"(fout));
            uint4 w[8];
#pragma unroll
            for (int i = 0; i < 8; i++) w[i] = make_uint4(0, 0, 0, 0);
#pragma unroll
            for (int part = 0; part <= XN; part++) {
                if (part) {
#pragma unroll
                    for (int i = (part - 1) * 8 / XN; i < part * 8 / XN; i++) ldg_nc_if(w[i], xp + (i & 1) * 8192 + (i >> 1) * 64, early);
                }
#pragma unroll 1
                for (int step = part ? XLD + (part - 1) * XD : 1; step < (part < XN ? XLD + part * XD : SP0); step++) {
                    mbar_wait(sb + B_FULL + 8 * slot, ph);
                    const uint32_t a = da0 + slot * 1024, b = db0 + b_addr(0) / 16 + slot * 1024;
                    wg_fence();
                    wgmma128(acc, desc_lo(a), desc_lo(b), 1);
                    wg_commit();
                    wg_wait<1>();
                    mbar_arrive_if(sb + B_EMPTY + 8 * pslot, lead);
                    mbar_arrive_cluster_if(rE + 8 * pslot, lead);
                    pslot = slot;
                    if (++slot == NST) { slot = 0; ph ^= 1; }
                    wg_fence();
#pragma unroll
                    for (int kk = 1; kk < 4; kk++) wgmma128(acc, desc_lo(a + kk * 2), desc_lo(b + kk * 128), 1);
                    wg_commit();
                }
            }
            uint32_t par;
            float g0, g1;
#define GATES() do { par = lds32(sb + M_PAR); g0 = __uint_as_float(lds32(sb + M_G + (wg * 64 + r0) * 4)); g1 = __uint_as_float(lds32(sb + M_G + (wg * 64 + r0 + 8) * 4)); } while (0)
            if (early) {
                WAITFULL(SP0);
                wg_fence();
                MMA_A(SP0, 0); MMA_A(SP0, 1);
                wg_commit();
                wg_wait<1>();
                mbar_arrive_if(sb + B_EMPTY + 8 * ((SP0 - 1) % NST), lead);
                bool ok = TESTFULL(SP0 + 1);
                MMA_A(SP0, 2); MMA_A(SP0, 3);
                wg_commit();
#pragma unroll
                for (int s = SP0 + 1; s < 32; s++) {
                    if (!ok) { WAITFULL(s); if (s == 29) mbar_wait(sb + B_GATE, 0); }
                    wg_fence();
                    MMA_A(s, 0); MMA_A(s, 1);
                    if (s == 29) GATES();
                    if (s >= 30) { wg_commit(); wg_wait<1>(); mbar_arrive_if(sb + (s == 30 ? B_S0 : B_S1), lead); wg_fence(); }
                    if (s < 31) ok = TESTFULL(s + 1) & (s != 28 || mbar_test(sb + B_GATE, 0));
                    MMA_A(s, 2); MMA_A(s, 3);
                    wg_commit();
                }
                wg_wait<0>();
                mbar_arrive_if(sb + B_EA, lead);
            } else {
                wg_wait<0>();
                mbar_arrive_if(sb + B_EMPTY + 8 * ((SP0 - 1) % NST), lead);
#pragma unroll
                for (int s = SP0; s < 32; s++) WAITFULL(s);
                mbar_wait(sb + B_GATE, 0);
                GATES();
                mbar_wait(sb + B_S1, 0);
                wg_fence();
#pragma unroll
                for (int s = SP0; s < 32; s++) {
                    MMA_A(s, 0); MMA_A(s, 1);
                    if (s > SP0) {
                        wg_commit();
                        wg_wait<1>();
                        mbar_arrive_n_if<2>(sb + B_EMPTY + 8 * ((s - 1) % NST), lead);
                        if (s == 31) mbar_arrive_if(sb + B_S3, lead);
                        if (s == 30) WAITD(0);
                        wg_fence();
                    }
                    MMA_A(s, 2); MMA_A(s, 3);
                    wg_commit();
                }
                wg_wait<0>();
                mbar_arrive_n_if<2>(sb + B_EMPTY + 8 * (31 % NST), lead);
            }
            fence_regs<0, 64>(acc);
            uint4 f[8];
#define TAG(v, c) (((v) & ~tagm[c]) | (par & tagm[c]))
#define PACK(k) f[k] = make_uint4(TAG(pack_bf16(acc[8 * (k)], acc[8 * (k) + 1]), 0), TAG(pack_bf16(acc[8 * (k) + 2], acc[8 * (k) + 3]), 2), \
                                  TAG(pack_bf16(acc[8 * (k) + 4], acc[8 * (k) + 5]), 1), TAG(pack_bf16(acc[8 * (k) + 6], acc[8 * (k) + 7]), 3))
#define SEND(k) do { st_relaxed(fout + 512 * (k), f[k].x); st_relaxed(fout + 512 * (k) + 32, f[k].z);                        \
                     st_relaxed(fout + 512 * (k) + 64, f[k].y); st_relaxed(fout + 512 * (k) + 96, f[k].w); } while (0)
#define OWN(k) wgmma128rs(acc, f[k], desc_lo(dd0 + d_addr((k) >> 2) / 16 + ((k) & 3) * 2), (k) != 0)
            const uint32_t dfa = sbd + 0x80000 + (early ? comp * 512 : NST * 1024), dfb = sbd + 0x80000 + (early ? (1 - comp) * 512 : NST * 1024 + 512);
#define MMA_F(pos, kk) wgmma128<0>(acc, (uint64_t)(((pos) < 5 ? dfa : dfb) + a_addr(29 + ((pos) - 2) % 3) / 16 + (kk) * 128) | (0x10ull << 32), \
                                   desc_lo(dd0 + d_addr(pos) / 16 + (kk) * 2), 1)
#define WAITF(pos) mbar_wait(vb + 8 * ((pos) - 2), 0)
            const uint32_t vb = sb + B_VAL + (early ? 0 : 48);
            const uint32_t ts = clk();
            if (early) {
                PACK(0); SEND(0); PACK(1); SEND(1); PACK(2); SEND(2); PACK(3); SEND(3);
                until(ts);
                PACK(4); PACK(5); PACK(6); PACK(7);
                const float s0 = comp ? -g0 : g0, s1 = comp ? -g1 : g1;
                const uint32_t og0 = pack_bf16(1.f - g0, 1.f - g0), og1 = pack_bf16(1.f - g1, 1.f - g1);
                const int rr = 0x7fff - (int)(lds32(sb + M_KEY) & 0x7fffu) - (tm * 128 + wg * 64 + r0);
#pragma unroll
                for (int k = 4; k < 8; k++) {
                    if (k < ESEND) { until(ts + ET1 + (k - 4) * STP); SEND(k); }
#pragma unroll
                    for (int i = 2 * k - 8; i < 2 * k - 6; i++) {
                        const uint32_t og = (i & 1) ? og1 : og0;
                        w[i] = make_uint4(hmul2_bf16(og, w[i].x), hmul2_bf16(og, w[i].y), hmul2_bf16(og, w[i].z), hmul2_bf16(og, w[i].w));
                        asm volatile("" : "+r"(w[i].x), "+r"(w[i].y), "+r"(w[i].z), "+r"(w[i].w));
                    }
                }
                WAITD(0);
                mbar_wait(sb + B_S3, 0);
                wg_fence();
#pragma unroll
                for (int k = 0; k < 8; k++) {
                    OWN(k);
                    if (k >= 1 && k + ESEND - 1 < 8) { wg_commit(); until(ts + ET1 + (k + ESEND - 5) * STP); SEND(k + ESEND - 1); wg_fence(); }
                }
                wg_commit();
                WAITD(2);
                bool ok = false;
#pragma unroll
                for (int pos = 2; pos < 8; pos++) {
                    if (!ok) {
                        if (pos >= 4) WAITD(pos);
                        WAITF(pos);
                    }
                    wg_fence();
                    MMA_F(pos, 0); MMA_F(pos, 1);
                    if (pos == 6) { wg_commit(); wg_wait<1>(); mbar_arrive_cluster_if(mapa(sb + B_XF, rank ^ 1), lead); wg_fence(); }
                    if (pos == 7) mbar_arrive_if(sb + B_S2, lead);
                    if (pos < 7) ok = mbar_test(vb + 8 * (pos - 1), 0) & (pos < 3 || mbar_test(sb + B_DL + 8 * (pos - 3), 0));
                    MMA_F(pos, 2); MMA_F(pos, 3);
                    wg_commit();
                }
                const uint32_t xd = mapa(sb + a_addr(29) + (tid & 127) * 16, rank ^ 1), xb = mapa(sb + B_X, rank ^ 1);
                if (rr == 0 || rr == 8) {
                    mbar_wait(sb + B_SIDE, 0);
#pragma unroll
                    for (int j = 0; j < 4; j++) {
                        const float4 ua = *(const float4*)(smem + M_RED + j * 128 + q * 32), ub = *(const float4*)(smem + M_RED + j * 128 + q * 32 + 16);
                        uint4 v = rr ? w[2 * j + 1] : w[2 * j];
                        v = make_uint4(pack_bf16(ua.x + bflo(v.x), ua.y + bfhi(v.x)), pack_bf16(ua.z + bflo(v.y), ua.w + bfhi(v.y)),
                                       pack_bf16(ub.x + bflo(v.z), ub.y + bfhi(v.z)), pack_bf16(ub.z + bflo(v.w), ub.w + bfhi(v.w)));
                        if (rr) w[2 * j + 1] = v; else w[2 * j] = v;
                    }
                }
                __syncwarp();
                mbar_wait(sb + B_XF, 0);
                wg_wait<0>();
                fence_regs<0, 64>(acc);
                keep_regs<0, 8>(f);
#pragma unroll
                for (int i = 0; i < 8; i++) {
                    const uint4 z = scale_add((i & 1) ? s1 : s0, acc, 16 * (i >> 1) + 2 * (i & 1), w[i]);
                    st_async16(xd + i * 2048, z.x, z.y, z.z, z.w, xb + 2 * (i & 4));
                    if (i & 1) until(ts);
                }
            } else {
                PACK(0); PACK(1); PACK(2); PACK(3); PACK(4); PACK(5); PACK(6); PACK(7);
                wg_fence();
#pragma unroll
                for (int k = 0; k < 8; k++) {
                    OWN(k);
                    if ((k & 1) && k / 2 < LSEND) { wg_commit(); until(ts + LT0 + k / 2 * LTP); SEND(k / 2); wg_fence(); }
                }
                wg_commit();
#pragma unroll
                for (int k = LSEND; k < 8; k++) { until(ts + LT0 + k * LTP); SEND(k); }
                float s0 = comp ? -g0 : g0, s1 = comp ? -g1 : g1;
                uint32_t xs = sb + a_addr(29) + (tid & 127) * 16;
                char* op = pout + ooff;
                asm volatile("" : "+f"(s0), "+f"(s1), "+r"(xs), "+l"(op));
                wg_wait<0>();
                keep_regs<0, 8>(f);
                WAITF(2);
                mbar_wait(sb + B_S2, 0);
                bool there = false, there1 = false, ok = true;
#pragma unroll
                for (int pos = 2; pos < 8; pos++) {
                    if (!ok) WAITF(pos);
                    wg_fence();
                    MMA_F(pos, 0);
                    if (pos == XPOS) there = mbar_test(sb + B_X, 0);
                    MMA_F(pos, 1);
                    if (pos == XPOS) {
#pragma unroll
                        for (int i = 0; i < 4; i++) lds128_if(w[i], xs + i * 2048, there);
                    }
                    if (pos < 7) ok = mbar_test(vb + 8 * (pos - 1), 0);
                    MMA_F(pos, 2); MMA_F(pos, 3);
                    wg_commit();
                }
                if (!there) {
                    mbar_wait(sb + B_X, 0);
#pragma unroll
                    for (int i = 0; i < 4; i++) w[i] = lds128(xs + i * 2048);
                }
                there1 = mbar_test(sb + B_X + 8, 0);
                float z[32];
#pragma unroll
                for (int i = 0; i < 4; i++) {
                    z[8 * i] = bflo(w[i].x); z[8 * i + 1] = bfhi(w[i].x); z[8 * i + 2] = bflo(w[i].y); z[8 * i + 3] = bfhi(w[i].y);
                    z[8 * i + 4] = bflo(w[i].z); z[8 * i + 5] = bfhi(w[i].z); z[8 * i + 6] = bflo(w[i].w); z[8 * i + 7] = bfhi(w[i].w);
                }
                fence_regs<0, 32>(z);
#pragma unroll 1
                for (int n = there1; n > 0; n--) {
#pragma unroll
                    for (int i = 4; i < 8; i++) w[i] = lds128(xs + i * 2048);
                }
                wg_wait<0>();
                fence_regs<0, 64>(acc);
#pragma unroll
                for (int i = 0; i < 8; i++) {
                    const int o = 16 * (i >> 1) + 2 * (i & 1);
                    const float s = (i & 1) ? s1 : s0;
                    if (i == XW && !there1) {
                        mbar_wait(sb + B_X + 8, 0);
#pragma unroll
                        for (int k = 4; k < 8; k++) w[k] = lds128(xs + k * 2048);
                    }
                    stg_off<0>(op + (i & 1) * 8192 + (i >> 1) * 64,
                               i >= 4 ? scale_add(s, acc, o, w[i])
                                      : make_uint4(pack_bf16(fmaf(s, acc[o], z[8 * (i & 3)]), fmaf(s, acc[o + 1], z[8 * (i & 3) + 1])),
                                                   pack_bf16(fmaf(s, acc[o + 4], z[8 * (i & 3) + 2]), fmaf(s, acc[o + 5], z[8 * (i & 3) + 3])),
                                                   pack_bf16(fmaf(s, acc[o + 8], z[8 * (i & 3) + 4]), fmaf(s, acc[o + 9], z[8 * (i & 3) + 5])),
                                                   pack_bf16(fmaf(s, acc[o + 12], z[8 * (i & 3) + 6]), fmaf(s, acc[o + 13], z[8 * (i & 3) + 7]))));
                    __syncwarp();
                }
            }
        }
    } else {
        if (wu >= 14) {
            const uint32_t b = blockIdx.x;
            const char* q = wu == 14 ? pcr + (uint32_t)((b >> 1) * 32 + lane) * (S_ * 2) + 128 : px + (uint32_t)(b * 4 + lane) * 128 + 65536;
            until(tstart + P_1);
            if (b < 128 && (wu == 14 || lane < 4)) prefetch_l2(q);
        } else if (wu == 13 && !spare) {
            if (lane == 0) ARM(1);
            __syncwarp();
            until(tstart + T_1);
            STEP0(1);
        }
        if (lane == 0) ARM(wu - 10);
        asm volatile("fence.mbarrier_init.release.cluster;" ::: "memory");
        __syncwarp();
        asm volatile("barrier.cluster.arrive.relaxed.aligned;" ::: "memory");
        if (spare) return;
        asm volatile("setmaxnreg.dec.sync.aligned.u32 " STR(RU) ";");
        if (wu < 14) {
            until(tstart + T_2 + (wu - 12) * PACE);
            STEP0(wu - 10);
        }
        asm volatile("barrier.cluster.wait.acquire.aligned;" ::: "memory");
        if (wu == 13) {
            const CUtensorMap* mD = comp ? &p.mDim : &p.mDre;
#pragma unroll
            for (int step = 4; step < NST; step++) {
                until(tstart + T_2 + (step - 2) * PACE);
                tma3d_elect(sb + b_addr(step), &p.mX2, step * 64, tn * 2, sb + B_FULL + 8 * step);
            }
#pragma unroll 1
            for (int step = NST, slot = 0, ph = 0; step < 32; step++) {
                mbar_wait(sb + B_EMPTY + 8 * slot, ph);
                mbar_wait(sb + B_EMPR + 8 * slot, ph);
                tma2d_pair_elect(sb + b_addr(0) + slot * 16384 + rank * 8192, &p.mX, tn * 128 + rank * 64, step * 64, sb + B_FULL + 8 * slot);
                if (++slot == NST) { slot = 0; ph ^= 1; }
            }
#pragma unroll
            for (int c = 0; c < 4; c += 2) {
                const uint32_t bar = sb + (c ? B_D6 : B_FULL + 8 * (32 % NST));
                if (c) mbar_wait(sb + B_R6, 0);
                else mbar_wait(sb + B_EMPTY + 8 * (26 % NST), (26 / NST) & 1);
                tma5d_elect(sb + d_addr(c), mD, dcol(c, tn), tn * 4, bar);
                tma5d_elect(sb + d_addr(c + 1), mD, dcol(c + 1, tn), tn * 4, bar);
                mbar_expect_tx_elect(bar, 32768);
            }
#pragma unroll
            for (int c = 0; c < 4; c++) mbar_expect_tx_elect(sb + B_DL + 8 * c, 16384);
            mbar_wait(sb + B_S1, 0);
            const uint32_t tq = clk();
#pragma unroll
            for (int c = 0; c < 4; c++) {
                if (!(c & 1)) mbar_wait(sb + B_EMPTY + 8 * ((27 + c / 2) % NST), ((27 + c / 2) / NST) & 1);
                if (c) until(tq + (c == 1 ? T_D5 : c == 2 ? T_D6 : T_D7));
                tma5d_elect(sb + d_addr(4 + c), mD, dcol(4 + c, tn), tn * 4, sb + B_DL + 8 * c);
            }
        } else {
            if (wu == 12) {
#pragma unroll
                for (int step = 4; step < NST; step++) {
                    until(tstart + T_2 + (step - 2) * PACE);
                    tma2d_elect(sb + a_addr(step), mC, step * 64, tm * 128, sb + B_FULL + 8 * step);
                }
#pragma unroll 1
                for (int step = NST, slot = 0, ph = 0; step < 32; step++) {
                    mbar_wait(sb + B_EMPTY + 8 * slot, ph);
                    tma2d_elect(sb + slot * 16384, mC, step * 64, tm * 128, sb + B_FULL + 8 * slot);
                    mbar_expect_tx_elect(sb + B_FULL + 8 * slot, 32768);
                    if (++slot == NST) { slot = 0; ph ^= 1; }
                }
            } else if (wu == 14) {
                if (lane == 0) {
                    asm volatile("prefetch.tensormap [%0];" ::"l"(&p.mX) : "memory");
                    asm volatile("prefetch.tensormap [%0];" ::"l"(&p.mF) : "memory");
                    asm volatile("prefetch.tensormap [%0];" ::"l"(comp ? &p.mDim : &p.mDre) : "memory");
                    asm volatile("st.shared::cluster.u32 [%0], %1;" ::"r"(mapa(sb + M_ROLE, rank ^ 1)), "r"(role) : "memory");
                }
                nap_until(tstart + KEY_T0 - 1000);
                const uint32_t epoch = ld_relaxed(g->epoch + cta) + 1u, par = epoch & 1u;
                if (lane < 8) stg_off<0>(g->stamp + cta * 32 + lane * 4, make_uint4(par ^ 1u, 0, 0, 0));
                nap_until(tstart + KEY_T0);
                const uint32_t k = best_key(g->keys + ((tm + (tm >> 3)) & 7) * NCTA, par);
                const uint4 xr = ldg_nc_off<0>(px + (0x7fff - (k & 0x7fffu)) * (D_ * 2) + rank * 512 + lane * 16);
                const uint4 g4 = wait_tags(g->gate + tm * 128 + lane * 4, par);
                sts128(sb + M_G + lane * 16, make_uint4(g4.x & ~1u, g4.y & ~1u, g4.z & ~1u, g4.w & ~1u));
                sts128(sb + M_UPD + lane * 16, xr);
                if (lane == 0) {
                    *(volatile uint32_t*)(smem + M_KEY) = k;
                    *(volatile uint32_t*)(smem + M_PAR) = par;
                    st_relaxed(g->epoch + cta, epoch);
                }
                mbar_arrive_warp(sb + B_GATE);
            } else {
                const int fr = ffn_pair(role);
                const uint32_t t1 = tstart + FFN_T0 + (rank + ((fr >> 2) & 6)) * (FFN_DT / 8);
                if (!((NOFFN_MASK >> role) & 1)) {
#pragma unroll 1
                    for (int i = 0; i < 12; i++) {
                        const int qu = i < 4 ? 2 + (i >> 1) : (i - 4) >> 1;
                        const uint32_t bar = sb + B_FFN + 8 * (i < 4 ? 3 : qu), dst = sb + R6 + (i & 1) * 16384 + qu * 4096;
                        if (i == 8) mbar_wait(sb + B_VD, 0);
                        if (i == 0 || (i >= 4 && !(i & 1))) mbar_expect_tx_elect(bar, i ? 8192 : 16384);
                        nap_until(t1 + i * FFN_DT);
                        tma2d_elect(dst, i < 4 ? &p.mWd : (i & 1) ? &p.mWu : &p.mWg, i < 4 ? rank * 256 : fr * 32, i < 4 ? fr * 32 + i * 8 : rank * 256 + qu * 64, bar);
                    }
                }
            }
            __syncwarp();
            mbar_wait(sb + B_GATE, 0);
            fetch_job<0>(p, g, smem, sb, cta, wu == 12 ? 2 : wu - 14, lds32(sb + M_PAR));
        }
    }
}

typedef CUresult (*EncodeTiledFn)(CUtensorMap*, CUtensorMapDataType, cuuint32_t, void*, const cuuint64_t*, const cuuint64_t*,
                                  const cuuint32_t*, const cuuint32_t*, CUtensorMapInterleave, CUtensorMapSwizzle,
                                  CUtensorMapL2promotion, CUtensorMapFloatOOBfill);

static void make_map(EncodeTiledFn enc, CUtensorMap* m, const void* base, uint64_t cols, uint64_t rows, uint32_t box_rows,
                     CUtensorMapSwizzle sw = CU_TENSOR_MAP_SWIZZLE_128B, uint32_t box_cols = 64) {
    cuuint64_t dims[2] = {cols, rows};
    cuuint64_t str[1] = {cols * 2};
    cuuint32_t box[2] = {box_cols, box_rows};
    cuuint32_t es[2] = {1, 1};
    enc(m, CU_TENSOR_MAP_DATA_TYPE_BFLOAT16, 2, (void*)base, dims, str, box, es, CU_TENSOR_MAP_INTERLEAVE_NONE,
        sw, CU_TENSOR_MAP_L2_PROMOTION_L2_128B, CU_TENSOR_MAP_FLOAT_OOB_FILL_NONE);
}

static void make_map_chunks(EncodeTiledFn enc, CUtensorMap* m, const void* base, uint64_t rows) {
    cuuint64_t dims[3] = {64, rows, D_ / 64};
    cuuint64_t str[2] = {D_ * 2, 128};
    cuuint32_t box[3] = {64, 64, 2};
    cuuint32_t es[3] = {1, 1, 1};
    enc(m, CU_TENSOR_MAP_DATA_TYPE_BFLOAT16, 3, (void*)base, dims, str, box, es, CU_TENSOR_MAP_INTERLEAVE_NONE,
        CU_TENSOR_MAP_SWIZZLE_128B, CU_TENSOR_MAP_L2_PROMOTION_L2_128B, CU_TENSOR_MAP_FLOAT_OOB_FILL_NONE);
}

static void make_map_perm(EncodeTiledFn enc, CUtensorMap* m, const void* base) {
    cuuint64_t dims[5] = {D_, 2, 4, 4, D_ / 32};
    cuuint64_t str[4] = {D_ * 2, 8 * D_ * 2, 2 * D_ * 2, 32 * D_ * 2};
    cuuint32_t box[5] = {64, 2, 4, 4, 4};
    cuuint32_t es[5] = {1, 1, 1, 1, 1};
    enc(m, CU_TENSOR_MAP_DATA_TYPE_BFLOAT16, 5, (void*)base, dims, str, box, es, CU_TENSOR_MAP_INTERLEAVE_NONE,
        CU_TENSOR_MAP_SWIZZLE_128B, CU_TENSOR_MAP_L2_PROMOTION_L2_128B, CU_TENSOR_MAP_FLOAT_OOB_FILL_NONE);
}

extern "C" void kernel_launch(void* const* d_in, const int* in_sizes, int n_in, void* d_out, int out_size) {
    (void)in_sizes; (void)n_in; (void)out_size;
    static EncodeTiledFn enc = nullptr;
    static bool fused_ok = false;
    static void* scr = nullptr;
    if (!enc) {
        void* fn = nullptr;
        cudaDriverEntryPointQueryResult q;
        cudaGetDriverEntryPoint("cuTensorMapEncodeTiled", &fn, cudaEnableDefault, &q);
        enc = (EncodeTiledFn)fn;
        cudaGetSymbolAddress(&scr, g_scr);
        cudaFuncSetAttribute(fused_kernel, cudaFuncAttributeMaxDynamicSharedMemorySize, SMEM_BYTES);
        int dev = 0, nsm = 0, ncl = 0;
        cudaGetDevice(&dev);
        cudaDeviceGetAttribute(&nsm, cudaDevAttrMultiProcessorCount, dev);
        cudaLaunchConfig_t cfg = {};
        cfg.gridDim = dim3(132); cfg.blockDim = dim3(NTHREADS); cfg.dynamicSmemBytes = SMEM_BYTES;
        cudaLaunchAttribute at;
        at.id = cudaLaunchAttributeClusterDimension;
        at.val.clusterDim.x = 2; at.val.clusterDim.y = 1; at.val.clusterDim.z = 1;
        cfg.attrs = &at; cfg.numAttrs = 1;
        fused_ok = cudaOccupancyMaxActiveClusters(&ncl, fused_kernel, &cfg) == cudaSuccess && nsm == 132 && ncl == 66;
        (void)cudaGetLastError();
    }
    if (!fused_ok) {
        const bf16* const* in = (const bf16* const*)d_in;
        fb_hidden<<<S_, D_, 0, cudaStreamPerThread>>>(in[0], in[3], in[4], in[10], in[6]);
        fb_ffn1<<<F_ / 128, 128, 0, cudaStreamPerThread>>>(in[0], in[7], in[8]);
        fb_ffn2<<<D_ / 64, 64, 0, cudaStreamPerThread>>>(in[9]);
        fb_seq<<<S_, D_, 0, cudaStreamPerThread>>>(in[0], in[1], in[2], (bf16*)d_out);
        return;
    }
    Params p;
    p.dre = (const bf16*)d_in[3];
    p.dim = (const bf16*)d_in[4];
    p.w_r = (const bf16*)d_in[6];
    p.gate_w = (const bf16*)d_in[10];
    make_map_chunks(enc, &p.mX2, d_in[0], S_);
    make_map(enc, &p.mX, d_in[0], D_, S_, 64);
    make_map(enc, &p.mCre, d_in[1], S_, S_, 128);
    make_map(enc, &p.mCim, d_in[2], S_, S_, 128);
    make_map_perm(enc, &p.mDre, d_in[3]);
    make_map_perm(enc, &p.mDim, d_in[4]);
    make_map(enc, &p.mF, scr, 64, NCTA * 256, 64, CU_TENSOR_MAP_SWIZZLE_NONE);
    make_map(enc, &p.mWg, d_in[7], F_, D_, 64, CU_TENSOR_MAP_SWIZZLE_NONE, 32);
    make_map(enc, &p.mWu, d_in[8], F_, D_, 64, CU_TENSOR_MAP_SWIZZLE_NONE, 32);
    make_map(enc, &p.mWd, d_in[9], D_, F_, 8, CU_TENSOR_MAP_SWIZZLE_NONE, 256);
    fused_kernel<<<132, NTHREADS, SMEM_BYTES, cudaStreamPerThread>>>(CPtr{{(const char*)d_in[1], (const char*)d_in[2]}}, (const char*)d_in[0], (char*)d_out, (Scratch*)scr, p);
}
```

```cpp
#include <cuda_runtime.h>
#include <cuda.h>
#include <cuda_bf16.h>
#include <stdint.h>

typedef __nv_bfloat16 bf16;

constexpr int S_ = 2048, D_ = 512, F_ = 1792;
constexpr int NCTA = 128;
constexpr int NTHREADS = 512;
constexpr int NST = 6;
constexpr int SP0 = 27;
constexpr int FFN_CTAS = F_ / 16;
constexpr uint32_t SPIN_LIMIT = 1u << 16;

#define P_1 450
#define T_1 500
#define T_2 1050
#define PACE 420
#define SIDE_T0 2800
#define ROUTER_T0 3000
#define ROUTER_DT 280
#define KEY_T0 9800
#define FFN_T0 5200
#define FFN_DT 640
#define XLD 14
#define XN 8
#define XD 1
#define PFD_T0 11900
#define PFD_DT 250
#define SUM_T0 15500
#define ET1 600
#define STP 170
#define ESEND 6
#define LT0 200
#define LTP 170
#define LPRE 2
#define LSEND 3
#define SDEL 280
#define E_RD0 1350
#define E_RD1 2180
#define L_RD0 3200
#define L_RD1 3880
#define SG 130
#define T_D5 1500
#define T_D6 1700
#define T_D7 2400
#define XPOS 7
#define XW 4
#define RC 168
#define RS_ 112
#define RU 64
#define NOFFN_MASK 0xf00c880000000000ull
#define STR2(x) #x
#define STR(x) STR2(x)

__host__ __device__ constexpr int a_addr(int s) { return s % NST * 16384; }
__host__ __device__ constexpr int b_addr(int s) { return (NST + s % NST) * 16384; }
constexpr int R6 = 2 * NST * 16384;
__host__ __device__ constexpr int d_addr(int p) { return p / 2 == 1 ? R6 + (p & 1) * 16384 : (p & 1) ? b_addr(26 + p / 3) : a_addr(26 + p / 3); }
static_assert(d_addr(0) == a_addr(26) && d_addr(4) == a_addr(27) && d_addr(6) == a_addr(28), "");
constexpr int OFF_MISC = R6 + 32768;
constexpr int B_FULL = OFF_MISC;
constexpr int B_EMPTY = B_FULL + 48;
constexpr int B_EMPR = B_EMPTY + 48;
constexpr int B_VD = B_EMPR + 48;
constexpr int B_X = B_VD + 8;
constexpr int B_HX = B_X + 16;
constexpr int B_XF = B_HX + 8;
constexpr int B_S0 = B_XF + 8;
constexpr int B_S1 = B_S0 + 8;
constexpr int B_EA = B_S1 + 8;
constexpr int B_S2 = B_EA + 8;
constexpr int B_S3 = B_S2 + 8;
constexpr int B_D6 = B_S3 + 8;
constexpr int B_DL = B_D6 + 8;
constexpr int B_GATE = B_DL + 32;
constexpr int B_SIDE = B_GATE + 8;
constexpr int B_FFN = B_SIDE + 8;
constexpr int B_R6 = B_FFN + 32;
constexpr int B_LAND = B_R6 + 8;
constexpr int B_VAL = B_LAND + 48;
constexpr int B_TH = B_VAL + 96;
constexpr int M_TH = B_TH + 24;
constexpr int NBAR = (M_TH - B_EMPTY) / 8;
constexpr int M_KEY = M_TH + 12;
constexpr int M_PAR = M_KEY + 4;
constexpr int M_ROLE = M_PAR + 4;
constexpr int M_HX = OFF_MISC + 544;
constexpr int M_G = M_HX + 256;
constexpr int M_UPD = M_G + 512;
constexpr int M_RED = M_UPD + 512;
constexpr int SMEM_BYTES = 232448;
static_assert(M_RED + 512 <= SMEM_BYTES && M_ROLE + 4 <= M_HX, "smem");

struct Params {
    const bf16 *gate_w, *w_r, *dre, *dim;
    CUtensorMap mCre, mCim, mX2, mX, mDre, mDim, mF, mWg, mWu, mWd;
};

struct CPtr { const char* c[2]; };

struct Scratch {
    uint32_t frag[NCTA * 2 * 4096];
    uint32_t stamp[NCTA * 32];
    uint32_t gate[S_];
    uint32_t keys[8 * NCTA];
    uint32_t part[FFN_CTAS / 2 * D_];
    uint32_t phint[4 * 8 * 8];
    uint32_t upd[D_];
    uint32_t epoch[NCTA + 4];
};
__device__ __align__(1024) Scratch g_scr;

__device__ __forceinline__ uint32_t smem_u32(const void* p) { return (uint32_t)__cvta_generic_to_shared(p); }
__device__ __forceinline__ void mbar_init(uint32_t bar, uint32_t cnt) {
    asm volatile("mbarrier.init.shared::cta.b64 [%0], %1;" ::"r"(bar), "r"(cnt) : "memory");
}
__device__ __forceinline__ void mbar_expect_tx(uint32_t bar, uint32_t bytes) {
    asm volatile("mbarrier.arrive.expect_tx.shared::cta.b64 _, [%0], %1;" ::"r"(bar), "r"(bytes) : "memory");
}
__device__ __forceinline__ void mbar_arrive(uint32_t bar) {
    asm volatile("mbarrier.arrive.shared::cta.b64 _, [%0];" ::"r"(bar) : "memory");
}
template <int N>
__device__ __forceinline__ void mbar_arrive_n_if(uint32_t bar, bool pred) {
    asm volatile("{.reg .pred p; setp.ne.b32 p, %1, 0; @p mbarrier.arrive.shared::cta.b64 _, [%0], %2;}" ::"r"(bar), "r"((int)pred), "n"(N) : "memory");
}
__device__ __forceinline__ void mbar_arrive_if(uint32_t bar, bool pred) {
    asm volatile("{.reg .pred p; setp.ne.b32 p, %1, 0; @p mbarrier.arrive.shared::cta.b64 _, [%0];}" ::"r"(bar), "r"((int)pred) : "memory");
}
__device__ __forceinline__ void mbar_arrive_warp(uint32_t bar) {
    __syncwarp();
    mbar_arrive_if(bar, (threadIdx.x & 31) == 0);
}
__device__ __forceinline__ void mbar_arrive_cluster_if(uint32_t bar, bool pred) {
    asm volatile("{.reg .pred p; setp.ne.b32 p, %1, 0; @p mbarrier.arrive.shared::cluster.b64 _, [%0], 1;}"
                 ::"r"(bar), "r"((int)pred) : "memory");
}
__device__ __forceinline__ uint32_t mapa(uint32_t a, uint32_t cta) {
    uint32_t r;
    asm volatile("mapa.shared::cluster.u32 %0, %1, %2;" : "=r"(r) : "r"(a), "r"(cta));
    return r;
}
__device__ __forceinline__ bool mbar_try(uint32_t bar, uint32_t parity) {
    uint32_t ok;
    asm volatile("{.reg .pred p; mbarrier.try_wait.parity.shared::cta.b64 p, [%1], %2; selp.u32 %0,1,0,p;}"
                 : "=r"(ok) : "r"(bar), "r"(parity) : "memory");
    return ok;
}
__device__ __forceinline__ bool mbar_test(uint32_t bar, uint32_t parity) {
    uint32_t ok;
    asm volatile("{.reg .pred p; mbarrier.test_wait.parity.shared::cta.b64 p, [%1], %2; selp.u32 %0,1,0,p;}"
                 : "=r"(ok) : "r"(bar), "r"(parity) : "memory");
    return ok;
}
__device__ __forceinline__ void mbar_wait(uint32_t bar, uint32_t parity) {
    uint32_t n = 0;
#pragma unroll 1
    while (!mbar_try(bar, parity)) { if (++n > SPIN_LIMIT) break; }
}
__device__ __forceinline__ void tma2d_elect(uint32_t dst, const CUtensorMap* m, int c0, int c1, uint32_t bar) {
    asm volatile("{.reg .pred p; elect.sync _|p, 0xffffffff;"
                 " @p cp.async.bulk.tensor.2d.shared::cluster.global.mbarrier::complete_tx::bytes [%0], [%1, {%3,%4}], [%2];}"
                 ::"r"(dst), "l"(m), "r"(bar), "r"(c0), "r"(c1) : "memory");
}
__device__ __forceinline__ void tma2d_pair_elect(uint32_t dst, const CUtensorMap* m, int c0, int c1, uint32_t bar) {
    asm volatile("{.reg .pred p; elect.sync _|p, 0xffffffff;"
                 " @p cp.async.bulk.tensor.2d.shared::cluster.global.mbarrier::complete_tx::bytes.multicast::cluster"
                 " [%0], [%1, {%3,%4}], [%2], %5;}" ::"r"(dst), "l"(m), "r"(bar), "r"(c0), "r"(c1), "h"((uint16_t)3) : "memory");
}
__device__ __forceinline__ void tma3d_elect(uint32_t dst, const CUtensorMap* m, int row, int chunk, uint32_t bar) {
    asm volatile("{.reg .pred p; elect.sync _|p, 0xffffffff;"
                 " @p cp.async.bulk.tensor.3d.shared::cluster.global.mbarrier::complete_tx::bytes [%0], [%1, {%3,%4,%5}], [%2];}"
                 ::"r"(dst), "l"(m), "r"(bar), "r"(0), "r"(row), "r"(chunk) : "memory");
}
__device__ __forceinline__ void tma5d_elect(uint32_t dst, const CUtensorMap* m, int c0, int c4, uint32_t bar) {
    asm volatile("{.reg .pred p; elect.sync _|p, 0xffffffff;"
                 " @p cp.async.bulk.tensor.5d.shared::cluster.global.mbarrier::complete_tx::bytes [%0], [%1, {%3,%5,%5,%5,%4}], [%2];}"
                 ::"r"(dst), "l"(m), "r"(bar), "r"(c0), "r"(c4), "r"(0) : "memory");
}
__device__ __forceinline__ void mbar_expect_tx_elect(uint32_t bar, uint32_t bytes) {
    asm volatile("{.reg .pred p; elect.sync _|p, 0xffffffff; @p mbarrier.arrive.expect_tx.shared::cta.b64 _, [%0], %1;}"
                 ::"r"(bar), "r"(bytes) : "memory");
}
__device__ __forceinline__ void prefetch_l2(const void* p) { asm volatile("prefetch.global.L2 [%0];" ::"l"(p)); }
__device__ __forceinline__ uint32_t ld_relaxed(const void* p) {
    uint32_t v;
    asm volatile("ld.relaxed.gpu.global.u32 %0, [%1];" : "=r"(v) : "l"(p) : "memory");
    return v;
}
__device__ __forceinline__ uint4 ld_relaxed4(const void* p) {
    uint4 v;
    asm volatile("ld.relaxed.gpu.global.v4.u32 {%0,%1,%2,%3}, [%4];" : "=r"(v.x), "=r"(v.y), "=r"(v.z), "=r"(v.w) : "l"(p) : "memory");
    return v;
}
__device__ __forceinline__ void st_relaxed(unsigned int* p, uint32_t v) {
    asm volatile("st.relaxed.gpu.global.u32 [%0], %1;" ::"l"(p), "r"(v) : "memory");
}
__device__ __forceinline__ uint32_t tagf(float v, uint32_t par) { return (__float_as_uint(v) & ~1u) | par; }
template <int BIT = 0>
__device__ __forceinline__ uint4 wait_tags(const unsigned int* p, uint32_t par) {
    uint32_t n = 0;
#pragma unroll 1
    while (true) {
        const uint4 v = ld_relaxed4(p);
        const uint32_t m = par ? (v.x & v.y & v.z & v.w) : ~(v.x | v.y | v.z | v.w);
        if (__all_sync(0xffffffffu, (m >> BIT) & 1u)) return v;
        __nanosleep(100);
        if (++n > SPIN_LIMIT) return v;
    }
}
__device__ __forceinline__ uint32_t best_key(const uint32_t* keys, uint32_t par) {
    const uint4 k = wait_tags<15>(keys + (threadIdx.x & 31) * 4, par);
    return __reduce_max_sync(0xffffffffu, max(max(k.x, k.y), max(k.z, k.w)));
}
__device__ __forceinline__ void named_bar(int id, int n) { asm volatile("bar.sync %0, %1;" ::"r"(id), "r"(n) : "memory"); }
template <int OFF>
__device__ __forceinline__ uint4 ldg_nc_off(const void* p) {
    uint4 v;
    asm volatile("ld.global.nc.v4.u32 {%0,%1,%2,%3}, [%4+%5];" : "=r"(v.x), "=r"(v.y), "=r"(v.z), "=r"(v.w) : "l"(p), "n"(OFF));
    return v;
}
__device__ __forceinline__ void ldg_nc_if(uint4& v, const void* a, bool pred) {
    asm volatile("{.reg .pred p; setp.ne.b32 p, %5, 0; @p ld.global.nc.v4.u32 {%0,%1,%2,%3}, [%4];}"
                 : "+r"(v.x), "+r"(v.y), "+r"(v.z), "+r"(v.w) : "l"(a), "r"((int)pred) : "memory");
}
template <int OFF>
__device__ __forceinline__ void stg_off(void* p, const uint4& v) {
    asm volatile("st.global.v4.u32 [%0+%5], {%1,%2,%3,%4};" ::"l"(p), "r"(v.x), "r"(v.y), "r"(v.z), "r"(v.w), "n"(OFF) : "memory");
}
__device__ __forceinline__ void sts128(uint32_t a, const uint4& v) {
    asm volatile("st.shared.v4.u32 [%0], {%1,%2,%3,%4};" ::"r"(a), "r"(v.x), "r"(v.y), "r"(v.z), "r"(v.w) : "memory");
}
__device__ __forceinline__ uint4 lds128(uint32_t a) {
    uint4 v;
    asm volatile("ld.shared.v4.u32 {%0,%1,%2,%3}, [%4];" : "=r"(v.x), "=r"(v.y), "=r"(v.z), "=r"(v.w) : "r"(a) : "memory");
    return v;
}
__device__ __forceinline__ void lds128_if(uint4& v, uint32_t a, bool pred) {
    asm volatile("{.reg .pred p; setp.ne.b32 p, %5, 0; @p ld.shared.v4.u32 {%0,%1,%2,%3}, [%4];}"
                 : "+r"(v.x), "+r"(v.y), "+r"(v.z), "+r"(v.w) : "r"(a), "r"((int)pred) : "memory");
}
__device__ __forceinline__ uint32_t lds32(uint32_t a) {
    uint32_t v;
    asm volatile("ld.shared.u32 %0, [%1];" : "=r"(v) : "r"(a) : "memory");
    return v;
}
__device__ __forceinline__ void st_async16(uint32_t dst, uint32_t x, uint32_t y, uint32_t z, uint32_t w, uint32_t bar) {
    asm volatile("st.async.weak.shared::cluster.mbarrier::complete_tx::bytes.v4.b32 [%0], {%1,%2,%3,%4}, [%5];"
                 ::"r"(dst), "r"(x), "r"(y), "r"(z), "r"(w), "r"(bar) : "memory");
}
__device__ __forceinline__ int sel(int a, int b, bool p) {
    int r;
    asm("{.reg .pred q; setp.ne.b32 q, %3, 0; selp.b32 %0, %1, %2, q;}" : "=r"(r) : "r"(a), "r"(b), "r"((int)p));
    return r;
}
__device__ __forceinline__ float selpf(float a, float b, bool p) {
    float r;
    asm("{.reg .pred q; setp.ne.b32 q, %3, 0; selp.f32 %0, %1, %2, q;}" : "=f"(r) : "f"(a), "f"(b), "r"((int)p));
    return r;
}
template <int N, int MASK, int SZ>
__device__ __forceinline__ void halve(float (&a)[SZ]) {
    const bool up = threadIdx.x & MASK;
#pragma unroll
    for (int j = 0; j < N; j++) a[j] = selpf(a[N + j], a[j], up) + __shfl_xor_sync(0xffffffffu, selpf(a[j], a[N + j], up), MASK);
}
__device__ __forceinline__ float bflo(uint32_t u) { return __uint_as_float(u << 16); }
__device__ __forceinline__ float bfhi(uint32_t u) { return __uint_as_float(u & 0xffff0000u); }
__device__ __forceinline__ uint32_t pack_bf16(float lo, float hi) {
    uint32_t r;
    asm("cvt.rn.bf16x2.f32 %0, %1, %2;" : "=r"(r) : "f"(hi), "f"(lo));
    return r;
}
__device__ __forceinline__ uint32_t hmul2_bf16(uint32_t a, uint32_t b) {
    uint32_t r;
    asm("mul.rn.bf16x2 %0, %1, %2;" : "=r"(r) : "r"(a), "r"(b));
    return r;
}
__device__ __forceinline__ float sigmoidf_(float v) { return 1.0f / (1.0f + __expf(-v)); }
__device__ __forceinline__ void wg_fence() { asm volatile("wgmma.fence.sync.aligned;" ::: "memory"); }
__device__ __forceinline__ void wg_commit() { asm volatile("wgmma.commit_group.sync.aligned;" ::: "memory"); }
template <int N> __device__ __forceinline__ void wg_wait() { asm volatile("wgmma.wait_group.sync.aligned %0;" ::"n"(N) : "memory"); }
__device__ __forceinline__ uint64_t desc_lo(uint32_t lo) { return (uint64_t)lo | (0x40000040ull << 32); }
template <int LO, int HI, int N>
__device__ __forceinline__ void fence_regs(float (&d)[N]) {
#pragma unroll
    for (int i = LO; i < HI; i++) asm volatile("" : "+f"(d[i])::"memory");
}
template <int LO, int HI, int N>
__device__ __forceinline__ void keep_regs(uint4 (&f)[N]) {
#pragma unroll
    for (int i = LO; i < HI; i++) asm volatile("" ::"r"(f[i].x), "r"(f[i].y), "r"(f[i].z), "r"(f[i].w) : "memory");
}
template <int TB = 1>
__device__ __forceinline__ void wgmma128(float (&d)[64], uint64_t da, uint64_t db, int scaleD) {
    asm volatile(
        "{ .reg .pred p; setp.ne.b32 p, %66, 0;\n"
        "wgmma.mma_async.sync.aligned.m64n128k16.f32.bf16.bf16 "
        "{%0,%1,%2,%3,%4,%5,%6,%7,%8,%9,%10,%11,%12,%13,%14,%15,%16,%17,%18,%19,%20,%21,%22,%23,%24,%25,%26,%27,%28,%29,%30,%31,"
        "%32,%33,%34,%35,%36,%37,%38,%39,%40,%41,%42,%43,%44,%45,%46,%47,%48,%49,%50,%51,%52,%53,%54,%55,%56,%57,%58,%59,%60,%61,%62,%63}, "
        "%64, %65, p, 1, 1, 0, %67;\n}"
        : "+f"(d[0]), "+f"(d[1]), "+f"(d[2]), "+f"(d[3]), "+f"(d[4]), "+f"(d[5]), "+f"(d[6]), "+f"(d[7]),
          "+f"(d[8]), "+f"(d[9]), "+f"(d[10]), "+f"(d[11]), "+f"(d[12]), "+f"(d[13]), "+f"(d[14]), "+f"(d[15]),
          "+f"(d[16]), "+f"(d[17]), "+f"(d[18]), "+f"(d[19]), "+f"(d[20]), "+f"(d[21]), "+f"(d[22]), "+f"(d[23]),
          "+f"(d[24]), "+f"(d[25]), "+f"(d[26]), "+f"(d[27]), "+f"(d[28]), "+f"(d[29]), "+f"(d[30]), "+f"(d[31]),
          "+f"(d[32]), "+f"(d[33]), "+f"(d[34]), "+f"(d[35]), "+f"(d[36]), "+f"(d[37]), "+f"(d[38]), "+f"(d[39]),
          "+f"(d[40]), "+f"(d[41]), "+f"(d[42]), "+f"(d[43]), "+f"(d[44]), "+f"(d[45]), "+f"(d[46]), "+f"(d[47]),
          "+f"(d[48]), "+f"(d[49]), "+f"(d[50]), "+f"(d[51]), "+f"(d[52]), "+f"(d[53]), "+f"(d[54]), "+f"(d[55]),
          "+f"(d[56]), "+f"(d[57]), "+f"(d[58]), "+f"(d[59]), "+f"(d[60]), "+f"(d[61]), "+f"(d[62]), "+f"(d[63])
        : "l"(da), "l"(db), "r"(scaleD), "n"(TB));
}
__device__ __forceinline__ void wgmma128rs(float (&d)[64], const uint4& a, uint64_t db, int scaleD) {
    asm volatile(
        "{ .reg .pred p; setp.ne.b32 p, %69, 0;\n"
        "wgmma.mma_async.sync.aligned.m64n128k16.f32.bf16.bf16 "
        "{%0,%1,%2,%3,%4,%5,%6,%7,%8,%9,%10,%11,%12,%13,%14,%15,%16,%17,%18,%19,%20,%21,%22,%23,%24,%25,%26,%27,%28,%29,%30,%31,"
        "%32,%33,%34,%35,%36,%37,%38,%39,%40,%41,%42,%43,%44,%45,%46,%47,%48,%49,%50,%51,%52,%53,%54,%55,%56,%57,%58,%59,%60,%61,%62,%63}, "
        "{%64,%65,%66,%67}, %68, p, 1, 1, 0;\n}"
        : "+f"(d[0]), "+f"(d[1]), "+f"(d[2]), "+f"(d[3]), "+f"(d[4]), "+f"(d[5]), "+f"(d[6]), "+f"(d[7]),
          "+f"(d[8]), "+f"(d[9]), "+f"(d[10]), "+f"(d[11]), "+f"(d[12]), "+f"(d[13]), "+f"(d[14]), "+f"(d[15]),
          "+f"(d[16]), "+f"(d[17]), "+f"(d[18]), "+f"(d[19]), "+f"(d[20]), "+f"(d[21]), "+f"(d[22]), "+f"(d[23]),
          "+f"(d[24]), "+f"(d[25]), "+f"(d[26]), "+f"(d[27]), "+f"(d[28]), "+f"(d[29]), "+f"(d[30]), "+f"(d[31]),
          "+f"(d[32]), "+f"(d[33]), "+f"(d[34]), "+f"(d[35]), "+f"(d[36]), "+f"(d[37]), "+f"(d[38]), "+f"(d[39]),
          "+f"(d[40]), "+f"(d[41]), "+f"(d[42]), "+f"(d[43]), "+f"(d[44]), "+f"(d[45]), "+f"(d[46]), "+f"(d[47]),
          "+f"(d[48]), "+f"(d[49]), "+f"(d[50]), "+f"(d[51]), "+f"(d[52]), "+f"(d[53]), "+f"(d[54]), "+f"(d[55]),
          "+f"(d[56]), "+f"(d[57]), "+f"(d[58]), "+f"(d[59]), "+f"(d[60]), "+f"(d[61]), "+f"(d[62]), "+f"(d[63])
        : "r"(a.x), "r"(a.y), "r"(a.z), "r"(a.w), "l"(db), "r"(scaleD));
}
__device__ __forceinline__ uint32_t clk() { uint64_t c; asm volatile("mov.u64 %0, %%clock64;" : "=l"(c)::"memory"); return (uint32_t)c; }
__device__ __forceinline__ uint32_t gtime() { uint64_t t; asm volatile("mov.u64 %0, %%globaltimer;" : "=l"(t)::"memory"); return (uint32_t)t; }
__device__ __forceinline__ void until(uint32_t t) { while (t - clk() < 0x8000u) {} }
__device__ __forceinline__ void nap_until(uint32_t t) { while (t - clk() < 0x8000u) __nanosleep(20); }
__device__ __forceinline__ uint4 scale_add(float s, const float (&a)[64], int o, const uint4& w) {
    return make_uint4(pack_bf16(fmaf(s, a[o], bflo(w.x)), fmaf(s, a[o + 1], bfhi(w.x))), pack_bf16(fmaf(s, a[o + 4], bflo(w.y)), fmaf(s, a[o + 5], bfhi(w.y))),
                      pack_bf16(fmaf(s, a[o + 8], bflo(w.z)), fmaf(s, a[o + 9], bfhi(w.z))), pack_bf16(fmaf(s, a[o + 12], bflo(w.w)), fmaf(s, a[o + 13], bfhi(w.w))));
}

__device__ __forceinline__ uint32_t router_key(float score, int row) {
    const float r = score + 0.0f;
    uint32_t u = pack_bf16(r, 0.f) & 0xffffu;
    u = (u & 0x8000u) ? (~u & 0xffffu) : (u | 0x8000u);
    if (r != r) u = 0;
    return (u << 16) | (uint32_t)(0x7fff - row);
}

#define g_ab g_scr.frag
#define g_fb_h ((float*)g_scr.part)
#define g_fb_upd (g_fb_h + 2048)
#define g_fb_gate (g_fb_h + 4096)
#define g_fb_keys (g_scr.part + 8192)
__global__ void fb_hidden(const bf16* x, const bf16* dre, const bf16* dim, const bf16* gw, const bf16* wr) {
    __shared__ float xs[D_];
    const int s = blockIdx.x, t = threadIdx.x;
    xs[t] = __bfloat162float(x[s * D_ + t]);
    __syncthreads();
    float a = 0.f, b = 0.f;
    for (int d = 0; d < D_; d++) { a = fmaf(xs[d], __bfloat162float(dre[t * D_ + d]), a); b = fmaf(xs[d], __bfloat162float(dim[t * D_ + d]), b); }
    ((bf16*)g_ab)[s * 1024 + t] = __float2bfloat16(a);
    ((bf16*)g_ab)[s * 1024 + 512 + t] = __float2bfloat16(b);
    if (t == 0) {
        float u = 0.f, v = 0.f;
        for (int d = 0; d < D_; d++) { u = fmaf(xs[d], __bfloat162float(gw[d]), u); v = fmaf(xs[d], __bfloat162float(wr[d]), v); }
        g_fb_gate[s] = sigmoidf_(u);
        g_fb_keys[s] = router_key(v, s);
    }
}
__device__ uint32_t fb_best() {
    uint32_t k = 0;
    for (int i = 0; i < S_; i++) k = max(k, g_fb_keys[i]);
    return k;
}
__global__ void fb_ffn1(const bf16* x, const bf16* wg, const bf16* wu) {
    const int f = blockIdx.x * blockDim.x + threadIdx.x, idx = 0x7fff - (int)(fb_best() & 0x7fffu);
    float a = 0.f, b = 0.f;
    for (int d = 0; d < D_; d++) {
        const float xv = __bfloat162float(x[idx * D_ + d]);
        a = fmaf(xv, __bfloat162float(wg[d * F_ + f]), a); b = fmaf(xv, __bfloat162float(wu[d * F_ + f]), b);
    }
    g_fb_h[f] = a * sigmoidf_(a) * b;
}
__global__ void fb_ffn2(const bf16* wd) {
    const int e = blockIdx.x * blockDim.x + threadIdx.x;
    const uint32_t u = fb_best() >> 16, rb = (u & 0x8000u) ? (u & 0x7fffu) : (~u & 0xffffu);
    float a = 0.f;
    for (int f = 0; f < F_; f++) a = fmaf(g_fb_h[f], __bfloat162float(wd[f * D_ + e]), a);
    g_fb_upd[e] = a * sigmoidf_(__uint_as_float(rb << 16));
}
__global__ void fb_seq(const bf16* x, const bf16* cre, const bf16* cim, bf16* out) {
    __shared__ float c[2][S_];
    __shared__ int idx;
    const int t = blockIdx.x, e = threadIdx.x;
    for (int i = e; i < S_; i += D_) { c[0][i] = __bfloat162float(cre[t * S_ + i]); c[1][i] = __bfloat162float(cim[t * S_ + i]); }
    if (e == 0) idx = 0x7fff - (int)(fb_best() & 0x7fffu);
    __syncthreads();
    float y = 0.f;
    for (int s = 0; s < S_; s++)
        y += c[0][s] * __bfloat162float(((const bf16*)g_ab)[s * 1024 + e]) - c[1][s] * __bfloat162float(((const bf16*)g_ab)[s * 1024 + 512 + e]);
    const float g = g_fb_gate[t];
    out[t * D_ + e] = __float2bfloat16(g * y + (1.f - g) * (__bfloat162float(x[t * D_ + e]) + (t == idx ? g_fb_upd[e] : 0.f)));
}

__device__ __forceinline__ void spare_job(const Params& p, Scratch* g, unsigned char* smem, int sp, uint32_t tstart) {
    const int tid = threadIdx.x, warp = tid >> 5, lane = tid & 31;
    if (warp >= 8) {
#pragma unroll 1
        for (int i = 0; i < 16; i++) {
            nap_until(tstart + PFD_T0 + i * (PFD_DT / 2));
            prefetch_l2((const char*)((sp & 2) ? p.dim : p.dre) + (sp & 1) * 262144 + i * 16384 + (tid - 256) * 128);
        }
        return;
    }
    named_bar(2, 288);
    mbar_wait(smem_u32(smem) + B_FULL, 0);
    nap_until(tstart + SUM_T0 - 2000);
    const uint32_t e1 = ld_relaxed(g->epoch + NCTA + sp) + 1u, par = e1 & 1u;
    const uint32_t u = best_key(g->keys + warp * NCTA, par) >> 16;
    const float rs = sigmoidf_(__uint_as_float(((u & 0x8000u) ? (u & 0x7fffu) : (~u & 0xffffu)) << 16));
    nap_until(tstart + SUM_T0);
    uint32_t n = 0;
#pragma unroll 1
    while ((int)(ld_relaxed(g->phint + (sp * 8 + warp) * 8) - e1 * 14u) < 0) {
        __nanosleep(40);
        if (++n > SPIN_LIMIT) break;
    }
    const unsigned int* src = g->part + warp * 7 * D_ + sp * 128 + lane * 4;
    uint4 v[7];
#pragma unroll 1
    while (true) {
        uint32_t bad = 0;
#pragma unroll
        for (int i = 0; i < 7; i++) v[i] = ld_relaxed4(src + i * D_);
#pragma unroll
        for (int i = 0; i < 7; i++) bad |= (v[i].x ^ par) | (v[i].y ^ par) | (v[i].z ^ par) | (v[i].w ^ par);
        if (!__any_sync(0xffffffffu, bad & 1u)) break;
        if (++n > SPIN_LIMIT) break;
    }
    float4 s = make_float4(0.f, 0.f, 0.f, 0.f);
#pragma unroll
    for (int i = 0; i < 7; i++) {
        s.x += __uint_as_float(v[i].x); s.y += __uint_as_float(v[i].y);
        s.z += __uint_as_float(v[i].z); s.w += __uint_as_float(v[i].w);
    }
    float* acc = (float*)(smem + R6);
    *(float4*)&acc[warp * 128 + lane * 4] = s;
    named_bar(1, 256);
    if (tid < 128) {
        float t = 0.f;
#pragma unroll
        for (int i = 0; i < 8; i++) t += acc[i * 128 + tid];
        st_relaxed(&g->upd[sp * 128 + tid], tagf(t * rs, par));
        if (tid == 0) st_relaxed(g->epoch + NCTA + sp, e1);
    }
}

__device__ __forceinline__ int ffn_pair(int role) { return role - __popcll(NOFFN_MASK & ((1ull << role) - 1)); }
__device__ __forceinline__ int other(int i, int tn) { return i + (i >= tn); }
__device__ __forceinline__ int dcol(int p, int tn) { return p < 2 ? tn * 128 + p * 64 : other((p - 2) % 3, tn) * 128 + (p >= 5 ? 64 : 0); }

template <int H>
__device__ __forceinline__ void fetch_job(const Params& p, Scratch* g, unsigned char* smem, uint32_t sb, int cta, int i, uint32_t par) {
    const int lane = threadIdx.x & 31, comp = cta & 1;
    const int j = other(i, (cta >> 1) & 3), src = (cta & ~6) + 2 * j;
    const int slot = i == 0 ? 29 % NST : i - 1;
    const uint32_t land = sb + B_LAND + 8 * (3 * H + i);
    uint32_t ph = 0, th;
    mbar_expect_tx_elect(land, 8192);
    if (H == 0) {
        mbar_wait(sb + B_S0, 0);
        const uint32_t t0 = clk();
        if (i == 0) {
            mbar_wait(sb + B_FULL + 8 * (31 % NST), (31 / NST) & 1);
            const uint32_t t1 = t0 + max(clk() - t0, 180u) - 180u;
            asm volatile("{.reg .pred p; .reg .b64 t; setp.eq.b32 p, %3, 0; mov.b64 t, {%1, %2}; @p st.relaxed.gpu.global.b64 [%0], t;}"
                         ::"l"(g->stamp + cta * 32), "r"((t1 & ~1u) | par), "r"(gtime()), "r"(lane) : "memory");
        }
        until(t0 + SDEL);
        uint32_t gt;
#pragma unroll 1
        for (uint32_t n = 0; n < SPIN_LIMIT; n++) {
            asm volatile("{.reg .b64 t; ld.relaxed.gpu.global.b64 t, [%2]; mov.b64 {%0,%1}, t;}" : "=r"(th), "=r"(gt) : "l"(g->stamp + src * 32) : "memory");
            if (!__any_sync(0xffffffffu, (th ^ par) & 1u)) break;
        }
        const uint32_t ns = min(gtime() - gt, 4096u), now = clk();
        if (now - th >= 8192u) th = now - (ns + (ns >> 1) + (ns >> 4));
        th += SG * j;
        if (lane == 0) { *(volatile uint32_t*)(smem + M_TH + 4 * i) = th; mbar_arrive(sb + B_TH + 8 * i); }
        __syncwarp();
    } else {
        mbar_wait(sb + B_TH + 8 * i, 0);
        th = lds32(sb + M_TH + 4 * i);
    }
    mbar_wait(sb + B_EA, 0);
#pragma unroll 1
    for (int c = 0; c < 2; c++) {
        const uint32_t dst = sb + slot * 16384 + (c ? NST * 16384 + H * 8192 : (comp ^ H) * 8192);
        if (c != H) mbar_wait(sb + B_EMPTY + 8 * slot, i != 0);
        until(th + (c ? (H ? L_RD1 : L_RD0) : (H ? E_RD1 : E_RD0)));
#pragma unroll 1
        for (uint32_t r = 0; r < SPIN_LIMIT; r++) {
            tma2d_elect(dst, &p.mF, 0, (src * 2 + (comp ^ c)) * 128 + H * 64, land);
            mbar_wait(land, ph);
            ph ^= 1;
            const uint32_t a = dst + (lane >> 2) * 132 + (lane & 3) * 32;
            uint32_t v[8], m0 = 0, m1 = ~0u;
#pragma unroll
            for (int k = 0; k < 8; k++) v[k] = lds32(a + k * 1024);
#pragma unroll
            for (int k = 0; k < 8; k++) { m0 |= v[k]; m1 &= v[k]; }
            if (__all_sync(0xffffffffu, (par ? m1 : ~m0) & 1u)) break;
            mbar_expect_tx_elect(land, 8192);
        }
        mbar_arrive_if(sb + B_VAL + 8 * (6 * c + 3 * H + i), lane == 0);
        if (c == 0) mbar_expect_tx_elect(land, 8192);
    }
}

__global__ void __cluster_dims__(2, 1, 1) __launch_bounds__(NTHREADS, 1)
fused_kernel(const __grid_constant__ CPtr pc, const char* px, char* pout, Scratch* g, const __grid_constant__ Params p) {
    extern __shared__ __align__(1024) unsigned char smem[];
    const uint32_t sb = smem_u32(smem);
    const int tid = threadIdx.x, warp = tid >> 5, lane = tid & 31;
    const int rank = blockIdx.x & 1;
    const char* pcr = pc.c[rank];
    asm volatile("{.reg .pred p; setp.lt.u32 p, %1, 32; @p prefetch.global.L2 [%0];}"
                 ::"l"(pcr + (uint32_t)(((blockIdx.x << 16) & 0x7e0000) + (tid << 12))), "r"(tid));
    const uint32_t tstart = clk();
    asm volatile("{.reg .pred p; setp.lt.u32 p, %1, 4; @p prefetch.global.L2 [%0];}"
                 ::"l"(px + (uint32_t)(((blockIdx.x << 9) & 0xfe00) + (tid << 7))), "r"(tid));
    uint32_t smid;
    asm volatile("mov.u32 %0, %%smid;" : "=r"(smid));
    const int u = smid >> 1;
    const int code = sel(u, sel(((u - 32) * 293) >> 8, 8 * u - 489, u < 60), u < 32);
    const int tn = code >> 3, tm = (code & 7) + sel(0, 8, u < 32);
    const int comp = rank;
    const CUtensorMap* mC = &p.mCre + comp;
#define ARM(j) do { mbar_init(sb + B_FULL + 8 * (j), 1); mbar_expect_tx(sb + B_FULL + 8 * (j), 32768); } while (0)
#define STEP0(j) do { tma2d_elect(sb + (j) * 16384, mC, (j) * 64, tm * 128, sb + B_FULL + 8 * (j));                            \
                      tma3d_elect(sb + (NST + (j)) * 16384, &p.mX2, (j) * 64, tn * 2, sb + B_FULL + 8 * (j)); } while (0)
    if (__all_sync(0xffffffffu, warp == 12)) {
        asm volatile("{.reg .pred p; elect.sync _|p, 0xffffffff; @p mbarrier.init.shared::cta.b64 [%0], 1;}" ::"r"(sb + B_FULL) : "memory");
        STEP0(0);
        mbar_expect_tx_elect(sb + B_FULL, 32768);
        asm volatile("bar.arrive 2, 288;" ::: "memory");
    }
    const bool spare = tn < 0;
    const int role = tm * 4 + tn, cta = role * 2 + rank;
    const int wu = __shfl_sync(0xffffffffu, warp, 0);
    if (wu < 12) {
        if (lane == 0) {
            mbar_init(sb + B_EMPTY + 8 * wu, 2);
            mbar_init(sb + B_VD + 8 * wu, wu ? 1 : 4);
#pragma unroll
            for (int i = 24; i < NBAR; i += 12) if (i + 12 <= NBAR || wu < NBAR - i) mbar_init(sb + B_EMPTY + 8 * (i + wu), 1);
            if (wu >= 1 && wu < 4) mbar_expect_tx(sb + B_VD + 8 * wu, wu < 3 ? 8192 : 256);
        }
        asm volatile("fence.mbarrier_init.release.cluster;" ::: "memory");
        __syncwarp();
        asm volatile("barrier.cluster.arrive.relaxed.aligned;" ::: "memory");
        if (spare) {
            spare_job(p, g, smem, smid & 3, tstart);
        } else if (wu >= 8) {
            asm volatile("setmaxnreg.dec.sync.aligned.u32 " STR(RS_) ";");
            asm volatile("barrier.cluster.wait.acquire.aligned;" ::: "memory");
            const int t = tid - 256, w = wu - 8, fr = ffn_pair(role);
            const bool ffn = !((NOFFN_MASK >> role) & 1);
            nap_until(tstart + SIDE_T0);
            const uint4 gw0 = ldg_nc_off<0>(p.gate_w + lane * 8), gw1 = ldg_nc_off<512>(p.gate_w + lane * 8);
            const uint4 rw0 = ldg_nc_off<0>(p.w_r + lane * 8), rw1 = ldg_nc_off<512>(p.w_r + lane * 8);
            const uint32_t par = ~ld_relaxed(g->epoch + cta) & 1u;
            nap_until(tstart + ROUTER_T0 + (2 * w + rank) * ROUTER_DT);
            {
                const int row0 = cta * 16 + w * 4;
                const char* xp = px + (uint32_t)row0 * (D_ * 2) + lane * 16;
                uint4 xa[4], xb[4];
                xa[0] = ldg_nc_off<0>(xp);    xb[0] = ldg_nc_off<512>(xp);  xa[1] = ldg_nc_off<1024>(xp); xb[1] = ldg_nc_off<1536>(xp);
                xa[2] = ldg_nc_off<2048>(xp); xb[2] = ldg_nc_off<2560>(xp); xa[3] = ldg_nc_off<3072>(xp); xb[3] = ldg_nc_off<3584>(xp);
                float a[8];
#pragma unroll
                for (int i = 0; i < 4; i++) {
                    const uint32_t xv[8] = {xa[i].x, xa[i].y, xa[i].z, xa[i].w, xb[i].x, xb[i].y, xb[i].z, xb[i].w};
                    const uint32_t gv[8] = {gw0.x, gw0.y, gw0.z, gw0.w, gw1.x, gw1.y, gw1.z, gw1.w};
                    const uint32_t rv[8] = {rw0.x, rw0.y, rw0.z, rw0.w, rw1.x, rw1.y, rw1.z, rw1.w};
                    float uu = 0.f, vv = 0.f;
#pragma unroll
                    for (int j = 0; j < 8; j++) {
                        uu = fmaf(bflo(xv[j]), bflo(gv[j]), uu); uu = fmaf(bfhi(xv[j]), bfhi(gv[j]), uu);
                        vv = fmaf(bflo(xv[j]), bflo(rv[j]), vv); vv = fmaf(bfhi(xv[j]), bfhi(rv[j]), vv);
                    }
                    a[i] = uu; a[4 + i] = vv;
                }
                halve<4, 16>(a); halve<2, 8>(a); halve<1, 4>(a);
                {
                    const float b1 = __shfl_xor_sync(0xffffffffu, a[0], 1), b2 = __shfl_xor_sync(0xffffffffu, a[0], 2),
                                b3 = __shfl_xor_sync(0xffffffffu, a[0], 3);
                    a[0] = (a[0] + b1) + (b2 + b3);
                }
                const int row = row0 + ((lane >> 2) & 3);
                const uint32_t best = __reduce_max_sync(0xffffffffu, lane >= 16 && (lane & 3) == 0 ? router_key(a[0], row) : 0u);
                if (lane <= 16 && (lane & 3) == 0)
                    *(volatile uint32_t*)(smem + M_RED + (lane < 16 ? w * 16 + lane : 64 + w * 4)) = lane < 16 ? tagf(sigmoidf_(a[0]), par) : best;
                named_bar(1, 128);
                if (t < 8) {
                    const uint4 k = lds128(sb + M_RED + 64);
                    asm volatile("{.reg .b32 old; atom.relaxed.gpu.global.exch.b32 old, [%0], %1;}"
                                 ::"l"(g->keys + t * NCTA + cta), "r"(max(max(k.x, k.y), max(k.z, k.w)) | (par << 15)) : "memory");
                }
                if (w == 1 && lane < 16) st_relaxed(g->gate + cta * 16 + lane, lds32(sb + M_RED + lane * 4));
            }
            uint32_t vd[32];
            if (ffn) {
                mbar_wait(sb + B_FFN + 24, 0);
#pragma unroll
                for (int j = 0; j < 32; j++) vd[j] = lds32(sb + R6 + ((j >> 3) & 1) * 16384 + (2 + (j >> 4)) * 4096 + (j & 7) * 512 + t * 4);
                mbar_arrive_warp(sb + B_VD);
            }
            mbar_wait(sb + B_GATE, 0);
            const int idx = 0x7fff - (int)(*(volatile uint32_t*)(smem + M_KEY) & 0x7fffu);
            if (ffn) {
                float a[16];
#pragma unroll
                for (int i = 0; i < 16; i++) a[i] = 0.f;
#pragma unroll 1
                for (int qu = 0; qu < 4; qu++) {
                    mbar_wait(sb + B_FFN + 8 * qu, qu == 3);
#pragma unroll
                    for (int i = 2 * qu; i < 2 * qu + 2; i++) {
                        const float xs = __bfloat162float(((const bf16*)(smem + M_UPD))[32 * i + (t >> 2)]);
                        const uint4 vg = lds128(sb + R6 + i * 2048 + t * 16);
                        const uint4 vu = lds128(sb + R6 + 16384 + i * 2048 + t * 16);
                        const uint32_t g4[4] = {vg.x, vg.y, vg.z, vg.w};
                        const uint32_t u4[4] = {vu.x, vu.y, vu.z, vu.w};
#pragma unroll
                        for (int j = 0; j < 4; j++) {
                            a[2 * j] = fmaf(xs, bflo(g4[j]), a[2 * j]);         a[2 * j + 1] = fmaf(xs, bfhi(g4[j]), a[2 * j + 1]);
                            a[8 + 2 * j] = fmaf(xs, bflo(u4[j]), a[8 + 2 * j]); a[9 + 2 * j] = fmaf(xs, bfhi(u4[j]), a[9 + 2 * j]);
                        }
                    }
                }
                named_bar(1, 128);
                mbar_arrive_if(sb + B_R6, t == 0);
                halve<8, 16>(a); halve<4, 8>(a); halve<2, 4>(a);
                float* red = (float*)(smem + M_UPD);
                *(float2*)&red[w * 64 + (lane >> 4) * 32 + (lane & 3) * 8 + ((lane >> 2) & 3) * 2] = make_float2(a[0], a[1]);
                named_bar(1, 128);
                const float sg = red[lane] + red[64 + lane] + red[128 + lane] + red[192 + lane];
                const float su = red[32 + lane] + red[96 + lane] + red[160 + lane] + red[224 + lane];
                if (w < 2) {
                    asm volatile("st.async.weak.shared::cluster.mbarrier::complete_tx::bytes.f32 [%0], %1, [%2];"
                                 ::"r"(mapa(sb + M_HX + t * 4, rank ^ 1)), "f"(w ? su : sg), "r"(mapa(sb + B_HX, rank ^ 1)) : "memory");
                }
                named_bar(1, 128);
                mbar_wait(sb + B_HX, 0);
                const float pg = ((const float*)(smem + M_HX))[lane], pu = ((const float*)(smem + M_HX))[32 + lane];
                const float gs = sg + pg, us = su + pu;
                float* hrow = red + w * 32;
                hrow[lane] = gs * sigmoidf_(gs) * us;
                __syncwarp();
                float o0 = 0.f, o1 = 0.f;
#pragma unroll
                for (int j4 = 0; j4 < 8; j4++) {
                    const float4 hv = *(const float4*)&hrow[j4 * 4];
                    o0 = fmaf(hv.x, bflo(vd[4 * j4]), o0);     o1 = fmaf(hv.x, bfhi(vd[4 * j4]), o1);
                    o0 = fmaf(hv.y, bflo(vd[4 * j4 + 1]), o0); o1 = fmaf(hv.y, bfhi(vd[4 * j4 + 1]), o1);
                    o0 = fmaf(hv.z, bflo(vd[4 * j4 + 2]), o0); o1 = fmaf(hv.z, bfhi(vd[4 * j4 + 2]), o1);
                    o0 = fmaf(hv.w, bflo(vd[4 * j4 + 3]), o0); o1 = fmaf(hv.w, bfhi(vd[4 * j4 + 3]), o1);
                }
                asm volatile("st.relaxed.gpu.global.v2.u32 [%0], {%1,%2};" ::"l"(&g->part[fr * D_ + rank * 256 + t * 2]),
                             "r"(tagf(o0, par)), "r"(tagf(o1, par)) : "memory");
                if (lane == 0) asm volatile("red.relaxed.gpu.global.add.u32 [%0], 1;" ::"l"(g->phint + ((rank * 2 + (w >> 1)) * 8 + fr / 7) * 8) : "memory");
            }
            if (!ffn) mbar_arrive_if(sb + B_R6, t == 0);
            if (w < 3) {
                fetch_job<1>(p, g, smem, sb, cta, w, par);
            } else {
                if (lds32(sb + M_ROLE) != (uint32_t)role) __trap();
                if ((idx >> 6) == 2 * tm + comp) {
                    const uint4 u4 = wait_tags(g->upd + tn * 128 + lane * 4, par);
                    const float og = 1.f - ((const float*)(smem + M_G))[idx & 127];
                    *(float4*)(smem + M_RED + lane * 16) = make_float4(og * __uint_as_float(u4.x), og * __uint_as_float(u4.y),
                                                                       og * __uint_as_float(u4.z), og * __uint_as_float(u4.w));
                    mbar_arrive_warp(sb + B_SIDE);
                }
            }
        } else {
            const int wg = wu >> 2;
            const uint32_t sbd = (sb & 0x3FFFF) >> 4;
            const bool lead = (tid & 127) == 0;
            const bool early = wg == comp;
            const int q = lane & 3;
            const int r0 = (warp & 3) * 16 + (lane >> 2);
            float acc[64];
            const uint32_t da0 = sbd + 0x10000 + wg * 512, db0 = sbd + 0x2000000, dd0 = sbd + 0x10000;
            const uint32_t rE = mapa(sb + B_EMPR, rank ^ 1);
#define WAITFULL(s) mbar_wait(sb + B_FULL + 8 * ((s) % NST), ((s) / NST) & 1)
#define TESTFULL(s) mbar_test(sb + B_FULL + 8 * ((s) % NST), ((s) / NST) & 1)
#define WAITD(pos) do { if ((pos) >= 4) mbar_wait(sb + B_DL + 8 * ((pos) & 3), 0); else if ((pos) >= 2) mbar_wait(sb + B_D6, 0); else WAITFULL(32); } while (0)
#define MMA_A(s, kk) wgmma128(acc, desc_lo(da0 + a_addr(s) / 16 + (kk) * 2), desc_lo(db0 + b_addr(s) / 16 + (kk) * 128), 1)
            named_bar(2, 288);
            WAITFULL(0);
            wg_fence();
#pragma unroll
            for (int kk = 0; kk < 4; kk++) wgmma128(acc, desc_lo(da0 + kk * 2), desc_lo(db0 + b_addr(0) / 16 + kk * 128), kk != 0);
            wg_commit();
            asm volatile("setmaxnreg.inc.sync.aligned.u32 " STR(RC) ";");
            asm volatile("barrier.cluster.wait.acquire.aligned;" ::: "memory");
            int slot = 1, ph = 0, pslot = 0;
            const uint32_t ooff = (uint32_t)((tm * 128 + wg * 64 + r0) * D_ + tn * 128 + q * 8) * 2u;
            uint32_t* fout = g->frag + (cta * 2 + wg) * 4096 + (warp & 3) * 128 + lane;
            uint32_t tagm[4];
#pragma unroll
            for (int c = 0; c < 4; c++) tagm[c] = (lane & 7) == (warp & 1) * 4 + c;
            const char* xp = px + ooff;
            asm volatile("" : "+r"(tagm[0]), "+r"(tagm[1]), "+r"(tagm[2]), "+r"(tagm[3]), "+l"(xp), "+l"(fout));
            uint4 w[8];
#pragma unroll
            for (int i = 0; i < 8; i++) w[i] = make_uint4(0, 0, 0, 0);
#pragma unroll
            for (int part = 0; part <= XN; part++) {
                if (part) {
#pragma unroll
                    for (int i = (part - 1) * 8 / XN; i < part * 8 / XN; i++) ldg_nc_if(w[i], xp + (i & 1) * 8192 + (i >> 1) * 64, early);
                }
#pragma unroll 1
                for (int step = part ? XLD + (part - 1) * XD : 1; step < (part < XN ? XLD + part * XD : SP0); step++) {
                    mbar_wait(sb + B_FULL + 8 * slot, ph);
                    const uint32_t a = da0 + slot * 1024, b = db0 + b_addr(0) / 16 + slot * 1024;
                    wg_fence();
                    wgmma128(acc, desc_lo(a), desc_lo(b), 1);
                    wg_commit();
                    wg_wait<1>();
                    mbar_arrive_if(sb + B_EMPTY + 8 * pslot, lead);
                    mbar_arrive_cluster_if(rE + 8 * pslot, lead);
                    pslot = slot;
                    if (++slot == NST) { slot = 0; ph ^= 1; }
                    wg_fence();
#pragma unroll
                    for (int kk = 1; kk < 4; kk++) wgmma128(acc, desc_lo(a + kk * 2), desc_lo(b + kk * 128), 1);
                    wg_commit();
                }
            }
            uint32_t par;
            float g0, g1;
#define GATES() do { par = lds32(sb + M_PAR); g0 = __uint_as_float(lds32(sb + M_G + (wg * 64 + r0) * 4)); g1 = __uint_as_float(lds32(sb + M_G + (wg * 64 + r0 + 8) * 4)); } while (0)
            if (early) {
                WAITFULL(SP0);
                wg_fence();
                MMA_A(SP0, 0); MMA_A(SP0, 1);
                wg_commit();
                wg_wait<1>();
                mbar_arrive_if(sb + B_EMPTY + 8 * ((SP0 - 1) % NST), lead);
                bool ok = TESTFULL(SP0 + 1);
                MMA_A(SP0, 2); MMA_A(SP0, 3);
                wg_commit();
#pragma unroll
                for (int s = SP0 + 1; s < 32; s++) {
                    if (!ok) { WAITFULL(s); if (s == 29) mbar_wait(sb + B_GATE, 0); }
                    wg_fence();
                    MMA_A(s, 0); MMA_A(s, 1);
                    if (s == 29) GATES();
                    if (s >= 30) { wg_commit(); wg_wait<1>(); mbar_arrive_if(sb + (s == 30 ? B_S0 : B_S1), lead); wg_fence(); }
                    if (s < 31) ok = TESTFULL(s + 1) & (s != 28 || mbar_test(sb + B_GATE, 0));
                    MMA_A(s, 2); MMA_A(s, 3);
                    wg_commit();
                }
                wg_wait<0>();
                mbar_arrive_if(sb + B_EA, lead);
            } else {
                wg_wait<0>();
                mbar_arrive_if(sb + B_EMPTY + 8 * ((SP0 - 1) % NST), lead);
#pragma unroll
                for (int s = SP0; s < 32; s++) WAITFULL(s);
                mbar_wait(sb + B_GATE, 0);
                GATES();
                mbar_wait(sb + B_S1, 0);
                wg_fence();
#pragma unroll
                for (int s = SP0; s < 32; s++) {
                    MMA_A(s, 0); MMA_A(s, 1);
                    if (s > SP0) {
                        wg_commit();
                        wg_wait<1>();
                        mbar_arrive_n_if<2>(sb + B_EMPTY + 8 * ((s - 1) % NST), lead);
                        if (s == 31) mbar_arrive_if(sb + B_S3, lead);
                        if (s == 30) WAITD(0);
                        wg_fence();
                    }
                    MMA_A(s, 2); MMA_A(s, 3);
                    wg_commit();
                }
                wg_wait<0>();
                mbar_arrive_n_if<2>(sb + B_EMPTY + 8 * (31 % NST), lead);
            }
            fence_regs<0, 64>(acc);
            uint4 f[8];
#define TAG(v, c) (((v) & ~tagm[c]) | (par & tagm[c]))
#define PACK(k) f[k] = make_uint4(TAG(pack_bf16(acc[8 * (k)], acc[8 * (k) + 1]), 0), TAG(pack_bf16(acc[8 * (k) + 2], acc[8 * (k) + 3]), 2), \
                                  TAG(pack_bf16(acc[8 * (k) + 4], acc[8 * (k) + 5]), 1), TAG(pack_bf16(acc[8 * (k) + 6], acc[8 * (k) + 7]), 3))
#define SEND(k) do { st_relaxed(fout + 512 * (k), f[k].x); st_relaxed(fout + 512 * (k) + 32, f[k].z);                        \
                     st_relaxed(fout + 512 * (k) + 64, f[k].y); st_relaxed(fout + 512 * (k) + 96, f[k].w); } while (0)
#define OWN(k) wgmma128rs(acc, f[k], desc_lo(dd0 + d_addr((k) >> 2) / 16 + ((k) & 3) * 2), (k) != 0)
            const uint32_t dfa = sbd + 0x80000 + (early ? comp * 512 : NST * 1024), dfb = sbd + 0x80000 + (early ? (1 - comp) * 512 : NST * 1024 + 512);
#define MMA_F(pos, kk) wgmma128<0>(acc, (uint64_t)(((pos) < 5 ? dfa : dfb) + a_addr(29 + ((pos) - 2) % 3) / 16 + (kk) * 128) | (0x10ull << 32), \
                                   desc_lo(dd0 + d_addr(pos) / 16 + (kk) * 2), 1)
#define WAITF(pos) mbar_wait(vb + 8 * ((pos) - 2), 0)
            const uint32_t vb = sb + B_VAL + (early ? 0 : 48);
            const uint32_t ts = clk();
            if (early) {
                PACK(0); SEND(0); PACK(1); SEND(1); PACK(2); SEND(2); PACK(3); SEND(3);
                until(ts);
                PACK(4); PACK(5); PACK(6); PACK(7);
                const float s0 = comp ? -g0 : g0, s1 = comp ? -g1 : g1;
                const uint32_t og0 = pack_bf16(1.f - g0, 1.f - g0), og1 = pack_bf16(1.f - g1, 1.f - g1);
                const int rr = 0x7fff - (int)(lds32(sb + M_KEY) & 0x7fffu) - (tm * 128 + wg * 64 + r0);
#pragma unroll
                for (int k = 4; k < 8; k++) {
                    if (k < ESEND) { until(ts + ET1 + (k - 4) * STP); SEND(k); }
#pragma unroll
                    for (int i = 2 * k - 8; i < 2 * k - 6; i++) {
                        const uint32_t og = (i & 1) ? og1 : og0;
                        w[i] = make_uint4(hmul2_bf16(og, w[i].x), hmul2_bf16(og, w[i].y), hmul2_bf16(og, w[i].z), hmul2_bf16(og, w[i].w));
                        asm volatile("" : "+r"(w[i].x), "+r"(w[i].y), "+r"(w[i].z), "+r"(w[i].w));
                    }
                }
                WAITD(0);
                mbar_wait(sb + B_S3, 0);
                wg_fence();
#pragma unroll
                for (int k = 0; k < 8; k++) {
                    OWN(k);
                    if (k >= 1 && k + ESEND - 1 < 8) { wg_commit(); until(ts + ET1 + (k + ESEND - 5) * STP); SEND(k + ESEND - 1); wg_fence(); }
                }
                wg_commit();
                WAITD(2);
                bool ok = false;
#pragma unroll
                for (int pos = 2; pos < 8; pos++) {
                    if (!ok) {
                        if (pos >= 4) WAITD(pos);
                        WAITF(pos);
                    }
                    wg_fence();
                    MMA_F(pos, 0); MMA_F(pos, 1);
                    if (pos == 6) { wg_commit(); wg_wait<1>(); mbar_arrive_cluster_if(mapa(sb + B_XF, rank ^ 1), lead); wg_fence(); }
                    if (pos == 7) mbar_arrive_if(sb + B_S2, lead);
                    if (pos < 7) ok = mbar_test(vb + 8 * (pos - 1), 0) & (pos < 3 || mbar_test(sb + B_DL + 8 * (pos - 3), 0));
                    MMA_F(pos, 2); MMA_F(pos, 3);
                    wg_commit();
                }
                const uint32_t xd = mapa(sb + a_addr(29) + (tid & 127) * 16, rank ^ 1), xb = mapa(sb + B_X, rank ^ 1);
                if (rr == 0 || rr == 8) {
                    mbar_wait(sb + B_SIDE, 0);
#pragma unroll
                    for (int j = 0; j < 4; j++) {
                        const float4 ua = *(const float4*)(smem + M_RED + j * 128 + q * 32), ub = *(const float4*)(smem + M_RED + j * 128 + q * 32 + 16);
                        uint4 v = rr ? w[2 * j + 1] : w[2 * j];
                        v = make_uint4(pack_bf16(ua.x + bflo(v.x), ua.y + bfhi(v.x)), pack_bf16(ua.z + bflo(v.y), ua.w + bfhi(v.y)),
                                       pack_bf16(ub.x + bflo(v.z), ub.y + bfhi(v.z)), pack_bf16(ub.z + bflo(v.w), ub.w + bfhi(v.w)));
                        if (rr) w[2 * j + 1] = v; else w[2 * j] = v;
                    }
                }
                __syncwarp();
                mbar_wait(sb + B_XF, 0);
                wg_wait<0>();
                fence_regs<0, 64>(acc);
                keep_regs<0, 8>(f);
#pragma unroll
                for (int i = 0; i < 8; i++) {
                    const uint4 z = scale_add((i & 1) ? s1 : s0, acc, 16 * (i >> 1) + 2 * (i & 1), w[i]);
                    st_async16(xd + i * 2048, z.x, z.y, z.z, z.w, xb + 2 * (i & 4));
                    if (i & 1) until(ts);
                }
            } else {
#pragma unroll
                for (int k = 0; k < 4; k++) {
                    PACK(2 * k); PACK(2 * k + 1);
                    if (k < LPRE) { until(ts + LT0 + k * LTP); SEND(k); }
                }
                wg_fence();
#pragma unroll
                for (int k = 0; k < 8; k++) {
                    OWN(k);
                    if ((k & 1) && k / 2 < LSEND) { wg_commit(); until(ts + LT0 + (LPRE + k / 2) * LTP); SEND(LPRE + k / 2); wg_fence(); }
                }
                wg_commit();
#pragma unroll
                for (int k = LPRE + LSEND; k < 8; k++) { until(ts + LT0 + k * LTP); SEND(k); }
                float s0 = comp ? -g0 : g0, s1 = comp ? -g1 : g1;
                uint32_t xs = sb + a_addr(29) + (tid & 127) * 16;
                char* op = pout + ooff;
                asm volatile("" : "+f"(s0), "+f"(s1), "+r"(xs), "+l"(op));
                wg_wait<0>();
                keep_regs<0, 8>(f);
                WAITF(2);
                mbar_wait(sb + B_S2, 0);
                bool there = false, there1 = false, ok = true;
#pragma unroll
                for (int pos = 2; pos < 8; pos++) {
                    if (!ok) WAITF(pos);
                    wg_fence();
                    MMA_F(pos, 0);
                    if (pos == XPOS) there = mbar_test(sb + B_X, 0);
                    MMA_F(pos, 1);
                    if (pos == XPOS) {
#pragma unroll
                        for (int i = 0; i < 4; i++) lds128_if(w[i], xs + i * 2048, there);
                    }
                    if (pos < 7) ok = mbar_test(vb + 8 * (pos - 1), 0);
                    MMA_F(pos, 2); MMA_F(pos, 3);
                    wg_commit();
                }
                if (!there) {
                    mbar_wait(sb + B_X, 0);
#pragma unroll
                    for (int i = 0; i < 4; i++) w[i] = lds128(xs + i * 2048);
                }
                there1 = mbar_test(sb + B_X + 8, 0);
                float z[32];
#pragma unroll
                for (int i = 0; i < 4; i++) {
                    z[8 * i] = bflo(w[i].x); z[8 * i + 1] = bfhi(w[i].x); z[8 * i + 2] = bflo(w[i].y); z[8 * i + 3] = bfhi(w[i].y);
                    z[8 * i + 4] = bflo(w[i].z); z[8 * i + 5] = bfhi(w[i].z); z[8 * i + 6] = bflo(w[i].w); z[8 * i + 7] = bfhi(w[i].w);
                }
                fence_regs<0, 32>(z);
#pragma unroll 1
                for (int n = there1; n > 0; n--) {
#pragma unroll
                    for (int i = 4; i < 8; i++) w[i] = lds128(xs + i * 2048);
                }
                wg_wait<0>();
                fence_regs<0, 64>(acc);
#pragma unroll
                for (int i = 0; i < 8; i++) {
                    const int o = 16 * (i >> 1) + 2 * (i & 1);
                    const float s = (i & 1) ? s1 : s0;
                    if (i == XW && !there1) {
                        mbar_wait(sb + B_X + 8, 0);
#pragma unroll
                        for (int k = 4; k < 8; k++) w[k] = lds128(xs + k * 2048);
                    }
                    stg_off<0>(op + (i & 1) * 8192 + (i >> 1) * 64,
                               i >= 4 ? scale_add(s, acc, o, w[i])
                                      : make_uint4(pack_bf16(fmaf(s, acc[o], z[8 * (i & 3)]), fmaf(s, acc[o + 1], z[8 * (i & 3) + 1])),
                                                   pack_bf16(fmaf(s, acc[o + 4], z[8 * (i & 3) + 2]), fmaf(s, acc[o + 5], z[8 * (i & 3) + 3])),
                                                   pack_bf16(fmaf(s, acc[o + 8], z[8 * (i & 3) + 4]), fmaf(s, acc[o + 9], z[8 * (i & 3) + 5])),
                                                   pack_bf16(fmaf(s, acc[o + 12], z[8 * (i & 3) + 6]), fmaf(s, acc[o + 13], z[8 * (i & 3) + 7]))));
                    __syncwarp();
                }
            }
        }
    } else {
        if (wu >= 14) {
            const uint32_t b = blockIdx.x;
            const char* q = wu == 14 ? pcr + (uint32_t)((b >> 1) * 32 + lane) * (S_ * 2) + 128 : px + (uint32_t)(b * 4 + lane) * 128 + 65536;
            until(tstart + P_1);
            if (b < 128 && (wu == 14 || lane < 4)) prefetch_l2(q);
        } else if (wu == 13 && !spare) {
            if (lane == 0) ARM(1);
            __syncwarp();
            until(tstart + T_1);
            STEP0(1);
        }
        if (lane == 0) ARM(wu - 10);
        asm volatile("fence.mbarrier_init.release.cluster;" ::: "memory");
        __syncwarp();
        asm volatile("barrier.cluster.arrive.relaxed.aligned;" ::: "memory");
        if (spare) return;
        asm volatile("setmaxnreg.dec.sync.aligned.u32 " STR(RU) ";");
        if (wu < 14) {
            until(tstart + T_2 + (wu - 12) * PACE);
            STEP0(wu - 10);
        }
        asm volatile("barrier.cluster.wait.acquire.aligned;" ::: "memory");
        if (wu == 13) {
            const CUtensorMap* mD = comp ? &p.mDim : &p.mDre;
#pragma unroll
            for (int step = 4; step < NST; step++) {
                until(tstart + T_2 + (step - 2) * PACE);
                tma3d_elect(sb + b_addr(step), &p.mX2, step * 64, tn * 2, sb + B_FULL + 8 * step);
            }
#pragma unroll 1
            for (int step = NST, slot = 0, ph = 0; step < 32; step++) {
                mbar_wait(sb + B_EMPTY + 8 * slot, ph);
                mbar_wait(sb + B_EMPR + 8 * slot, ph);
                tma2d_pair_elect(sb + b_addr(0) + slot * 16384 + rank * 8192, &p.mX, tn * 128 + rank * 64, step * 64, sb + B_FULL + 8 * slot);
                if (++slot == NST) { slot = 0; ph ^= 1; }
            }
#pragma unroll
            for (int c = 0; c < 4; c += 2) {
                const uint32_t bar = sb + (c ? B_D6 : B_FULL + 8 * (32 % NST));
                if (c) mbar_wait(sb + B_R6, 0);
                else mbar_wait(sb + B_EMPTY + 8 * (26 % NST), (26 / NST) & 1);
                tma5d_elect(sb + d_addr(c), mD, dcol(c, tn), tn * 4, bar);
                tma5d_elect(sb + d_addr(c + 1), mD, dcol(c + 1, tn), tn * 4, bar);
                mbar_expect_tx_elect(bar, 32768);
            }
#pragma unroll
            for (int c = 0; c < 4; c++) mbar_expect_tx_elect(sb + B_DL + 8 * c, 16384);
            mbar_wait(sb + B_S1, 0);
            const uint32_t tq = clk();
#pragma unroll
            for (int c = 0; c < 4; c++) {
                if (!(c & 1)) mbar_wait(sb + B_EMPTY + 8 * ((27 + c / 2) % NST), ((27 + c / 2) / NST) & 1);
                if (c) until(tq + (c == 1 ? T_D5 : c == 2 ? T_D6 : T_D7));
                tma5d_elect(sb + d_addr(4 + c), mD, dcol(4 + c, tn), tn * 4, sb + B_DL + 8 * c);
            }
        } else {
            if (wu == 12) {
#pragma unroll
                for (int step = 4; step < NST; step++) {
                    until(tstart + T_2 + (step - 2) * PACE);
                    tma2d_elect(sb + a_addr(step), mC, step * 64, tm * 128, sb + B_FULL + 8 * step);
                }
#pragma unroll 1
                for (int step = NST, slot = 0, ph = 0; step < 32; step++) {
                    mbar_wait(sb + B_EMPTY + 8 * slot, ph);
                    tma2d_elect(sb + slot * 16384, mC, step * 64, tm * 128, sb + B_FULL + 8 * slot);
                    mbar_expect_tx_elect(sb + B_FULL + 8 * slot, 32768);
                    if (++slot == NST) { slot = 0; ph ^= 1; }
                }
            } else if (wu == 14) {
                if (lane == 0) {
                    asm volatile("prefetch.tensormap [%0];" ::"l"(&p.mX) : "memory");
                    asm volatile("prefetch.tensormap [%0];" ::"l"(&p.mF) : "memory");
                    asm volatile("prefetch.tensormap [%0];" ::"l"(comp ? &p.mDim : &p.mDre) : "memory");
                    asm volatile("st.shared::cluster.u32 [%0], %1;" ::"r"(mapa(sb + M_ROLE, rank ^ 1)), "r"(role) : "memory");
                }
                nap_until(tstart + KEY_T0 - 1000);
                const uint32_t epoch = ld_relaxed(g->epoch + cta) + 1u, par = epoch & 1u;
                if (lane < 8) stg_off<0>(g->stamp + cta * 32 + lane * 4, make_uint4(par ^ 1u, 0, 0, 0));
                nap_until(tstart + KEY_T0);
                const uint32_t k = best_key(g->keys + ((tm + (tm >> 3)) & 7) * NCTA, par);
                const uint4 xr = ldg_nc_off<0>(px + (0x7fff - (k & 0x7fffu)) * (D_ * 2) + rank * 512 + lane * 16);
                const uint4 g4 = wait_tags(g->gate + tm * 128 + lane * 4, par);
                sts128(sb + M_G + lane * 16, make_uint4(g4.x & ~1u, g4.y & ~1u, g4.z & ~1u, g4.w & ~1u));
                sts128(sb + M_UPD + lane * 16, xr);
                if (lane == 0) {
                    *(volatile uint32_t*)(smem + M_KEY) = k;
                    *(volatile uint32_t*)(smem + M_PAR) = par;
                    st_relaxed(g->epoch + cta, epoch);
                }
                mbar_arrive_warp(sb + B_GATE);
            } else {
                const int fr = ffn_pair(role);
                const uint32_t t1 = tstart + FFN_T0 + (rank + ((fr >> 2) & 6)) * (FFN_DT / 8);
                if (!((NOFFN_MASK >> role) & 1)) {
#pragma unroll 1
                    for (int i = 0; i < 12; i++) {
                        const int qu = i < 4 ? 2 + (i >> 1) : (i - 4) >> 1;
                        const uint32_t bar = sb + B_FFN + 8 * (i < 4 ? 3 : qu), dst = sb + R6 + (i & 1) * 16384 + qu * 4096;
                        if (i == 8) mbar_wait(sb + B_VD, 0);
                        if (i == 0 || (i >= 4 && !(i & 1))) mbar_expect_tx_elect(bar, i ? 8192 : 16384);
                        nap_until(t1 + i * FFN_DT);
                        tma2d_elect(dst, i < 4 ? &p.mWd : (i & 1) ? &p.mWu : &p.mWg, i < 4 ? rank * 256 : fr * 32, i < 4 ? fr * 32 + i * 8 : rank * 256 + qu * 64, bar);
                    }
                }
            }
            __syncwarp();
            mbar_wait(sb + B_GATE, 0);
            fetch_job<0>(p, g, smem, sb, cta, wu == 12 ? 2 : wu - 14, lds32(sb + M_PAR));
        }
    }
}

typedef CUresult (*EncodeTiledFn)(CUtensorMap*, CUtensorMapDataType, cuuint32_t, void*, const cuuint64_t*, const cuuint64_t*,
                                  const cuuint32_t*, const cuuint32_t*, CUtensorMapInterleave, CUtensorMapSwizzle,
                                  CUtensorMapL2promotion, CUtensorMapFloatOOBfill);

static void make_map(EncodeTiledFn enc, CUtensorMap* m, const void* base, uint64_t cols, uint64_t rows, uint32_t box_rows,
                     CUtensorMapSwizzle sw = CU_TENSOR_MAP_SWIZZLE_128B, uint32_t box_cols = 64) {
    cuuint64_t dims[2] = {cols, rows};
    cuuint64_t str[1] = {cols * 2};
    cuuint32_t box[2] = {box_cols, box_rows};
    cuuint32_t es[2] = {1, 1};
    enc(m, CU_TENSOR_MAP_DATA_TYPE_BFLOAT16, 2, (void*)base, dims, str, box, es, CU_TENSOR_MAP_INTERLEAVE_NONE,
        sw, CU_TENSOR_MAP_L2_PROMOTION_L2_128B, CU_TENSOR_MAP_FLOAT_OOB_FILL_NONE);
}

static void make_map_chunks(EncodeTiledFn enc, CUtensorMap* m, const void* base, uint64_t rows) {
    cuuint64_t dims[3] = {64, rows, D_ / 64};
    cuuint64_t str[2] = {D_ * 2, 128};
    cuuint32_t box[3] = {64, 64, 2};
    cuuint32_t es[3] = {1, 1, 1};
    enc(m, CU_TENSOR_MAP_DATA_TYPE_BFLOAT16, 3, (void*)base, dims, str, box, es, CU_TENSOR_MAP_INTERLEAVE_NONE,
        CU_TENSOR_MAP_SWIZZLE_128B, CU_TENSOR_MAP_L2_PROMOTION_L2_128B, CU_TENSOR_MAP_FLOAT_OOB_FILL_NONE);
}

static void make_map_perm(EncodeTiledFn enc, CUtensorMap* m, const void* base) {
    cuuint64_t dims[5] = {D_, 2, 4, 4, D_ / 32};
    cuuint64_t str[4] = {D_ * 2, 8 * D_ * 2, 2 * D_ * 2, 32 * D_ * 2};
    cuuint32_t box[5] = {64, 2, 4, 4, 4};
    cuuint32_t es[5] = {1, 1, 1, 1, 1};
    enc(m, CU_TENSOR_MAP_DATA_TYPE_BFLOAT16, 5, (void*)base, dims, str, box, es, CU_TENSOR_MAP_INTERLEAVE_NONE,
        CU_TENSOR_MAP_SWIZZLE_128B, CU_TENSOR_MAP_L2_PROMOTION_L2_128B, CU_TENSOR_MAP_FLOAT_OOB_FILL_NONE);
}

extern "C" void kernel_launch(void* const* d_in, const int* in_sizes, int n_in, void* d_out, int out_size) {
    (void)in_sizes; (void)n_in; (void)out_size;
    static EncodeTiledFn enc = nullptr;
    static bool fused_ok = false;
    static void* scr = nullptr;
    if (!enc) {
        void* fn = nullptr;
        cudaDriverEntryPointQueryResult q;
        cudaGetDriverEntryPoint("cuTensorMapEncodeTiled", &fn, cudaEnableDefault, &q);
        enc = (EncodeTiledFn)fn;
        cudaGetSymbolAddress(&scr, g_scr);
        cudaFuncSetAttribute(fused_kernel, cudaFuncAttributeMaxDynamicSharedMemorySize, SMEM_BYTES);
        int dev = 0, nsm = 0, ncl = 0;
        cudaGetDevice(&dev);
        cudaDeviceGetAttribute(&nsm, cudaDevAttrMultiProcessorCount, dev);
        cudaLaunchConfig_t cfg = {};
        cfg.gridDim = dim3(132); cfg.blockDim = dim3(NTHREADS); cfg.dynamicSmemBytes = SMEM_BYTES;
        cudaLaunchAttribute at;
        at.id = cudaLaunchAttributeClusterDimension;
        at.val.clusterDim.x = 2; at.val.clusterDim.y = 1; at.val.clusterDim.z = 1;
        cfg.attrs = &at; cfg.numAttrs = 1;
        fused_ok = cudaOccupancyMaxActiveClusters(&ncl, fused_kernel, &cfg) == cudaSuccess && nsm == 132 && ncl == 66;
        (void)cudaGetLastError();
    }
    if (!fused_ok) {
        const bf16* const* in = (const bf16* const*)d_in;
        fb_hidden<<<S_, D_, 0, cudaStreamPerThread>>>(in[0], in[3], in[4], in[10], in[6]);
        fb_ffn1<<<F_ / 128, 128, 0, cudaStreamPerThread>>>(in[0], in[7], in[8]);
        fb_ffn2<<<D_ / 64, 64, 0, cudaStreamPerThread>>>(in[9]);
        fb_seq<<<S_, D_, 0, cudaStreamPerThread>>>(in[0], in[1], in[2], (bf16*)d_out);
        return;
    }
    Params p;
    p.dre = (const bf16*)d_in[3];
    p.dim = (const bf16*)d_in[4];
    p.w_r = (const bf16*)d_in[6];
    p.gate_w = (const bf16*)d_in[10];
    make_map_chunks(enc, &p.mX2, d_in[0], S_);
    make_map(enc, &p.mX, d_in[0], D_, S_, 64);
    make_map(enc, &p.mCre, d_in[1], S_, S_, 128);
    make_map(enc, &p.mCim, d_in[2], S_, S_, 128);
    make_map_perm(enc, &p.mDre, d_in[3]);
    make_map_perm(enc, &p.mDim, d_in[4]);
    make_map(enc, &p.mF, scr, 64, NCTA * 256, 64, CU_TENSOR_MAP_SWIZZLE_NONE);
    make_map(enc, &p.mWg, d_in[7], F_, D_, 64, CU_TENSOR_MAP_SWIZZLE_NONE, 32);
    make_map(enc, &p.mWu, d_in[8], F_, D_, 64, CU_TENSOR_MAP_SWIZZLE_NONE, 32);
    make_map(enc, &p.mWd, d_in[9], D_, F_, 8, CU_TENSOR_MAP_SWIZZLE_NONE, 256);
    fused_kernel<<<132, NTHREADS, SMEM_BYTES, cudaStreamPerThread>>>(CPtr{{(const char*)d_in[1], (const char*)d_in[2]}}, (const char*)d_in[0], (char*)d_out, (Scratch*)scr, p);
}
```

```cpp
#include <cuda_runtime.h>
#include <cuda.h>
#include <cuda_bf16.h>
#include <stdint.h>

typedef __nv_bfloat16 bf16;

constexpr int S_ = 2048, D_ = 512, F_ = 1792;
constexpr int NCTA = 128;
constexpr int NTHREADS = 512;
constexpr int NST = 6;
constexpr int SP0 = 27;
constexpr int FFN_CTAS = F_ / 16;
constexpr uint32_t SPIN_LIMIT = 1u << 16;

#define P_1 450
#define T_1 500
#define T_2 1050
#define PACE 420
#define SIDE_T0 2800
#define ROUTER_T0 3000
#define ROUTER_DT 280
#define KEY_T0 9800
#define FFN_T0 5200
#define FFN_DT 640
#define XLD 14
#define XN 8
#define XD 1
#define PFD_T0 11900
#define PFD_DT 250
#define SUM_T0 15500
#define ET1 600
#define STP 170
#define ESEND 6
#define LT0 200
#define LTP 170
#define LPRE 2
#define LSEND 3
#define SDEL 280
#define E_RD0 1350
#define E_RD1 2180
#define L_RD0 3200
#define L_RD1 3880
#define SG 130
#define T_D5 1500
#define T_D6 1700
#define T_D7 2400
#define XPOS 7
#define XW 4
#define RC 168
#define RS_ 112
#define RU 64
#define NOFFN_MASK 0xf00c880000000000ull
#define STR2(x) #x
#define STR(x) STR2(x)

__host__ __device__ constexpr int a_addr(int s) { return s % NST * 16384; }
__host__ __device__ constexpr int b_addr(int s) { return (NST + s % NST) * 16384; }
constexpr int R6 = 2 * NST * 16384;
__host__ __device__ constexpr int d_addr(int p) { return p / 2 == 1 ? R6 + (p & 1) * 16384 : (p & 1) ? b_addr(26 + p / 3) : a_addr(26 + p / 3); }
static_assert(d_addr(0) == a_addr(26) && d_addr(4) == a_addr(27) && d_addr(6) == a_addr(28), "");
constexpr int OFF_MISC = R6 + 32768;
constexpr int B_FULL = OFF_MISC;
constexpr int B_EMPTY = B_FULL + 48;
constexpr int B_EMPR = B_EMPTY + 48;
constexpr int B_VD = B_EMPR + 48;
constexpr int B_X = B_VD + 8;
constexpr int B_HX = B_X + 16;
constexpr int B_XF = B_HX + 8;
constexpr int B_S0 = B_XF + 8;
constexpr int B_S1 = B_S0 + 8;
constexpr int B_EA = B_S1 + 8;
constexpr int B_S2 = B_EA + 8;
constexpr int B_S3 = B_S2 + 8;
constexpr int B_D6 = B_S3 + 8;
constexpr int B_DL = B_D6 + 8;
constexpr int B_GATE = B_DL + 32;
constexpr int B_SIDE = B_GATE + 8;
constexpr int B_FFN = B_SIDE + 8;
constexpr int B_R6 = B_FFN + 32;
constexpr int B_LAND = B_R6 + 8;
constexpr int B_VAL = B_LAND + 48;
constexpr int B_TH = B_VAL + 96;
constexpr int M_TH = B_TH + 24;
constexpr int NBAR = (M_TH - B_EMPTY) / 8;
constexpr int M_KEY = M_TH + 12;
constexpr int M_PAR = M_KEY + 4;
constexpr int M_ROLE = M_PAR + 4;
constexpr int M_HX = OFF_MISC + 544;
constexpr int M_G = M_HX + 256;
constexpr int M_UPD = M_G + 512;
constexpr int M_RED = M_UPD + 512;
constexpr int SMEM_BYTES = 232448;
static_assert(M_RED + 512 <= SMEM_BYTES && M_ROLE + 4 <= M_HX, "smem");

struct Params {
    const bf16 *gate_w, *w_r, *dre, *dim;
    CUtensorMap mCre, mCim, mX2, mX, mDre, mDim, mF, mWg, mWu, mWd;
};

struct CPtr { const char* c[2]; };

struct Scratch {
    uint32_t frag[NCTA * 2 * 4096];
    uint32_t stamp[NCTA * 32];
    uint32_t gate[S_];
    uint32_t keys[8 * NCTA];
    uint32_t part[FFN_CTAS / 2 * D_];
    uint32_t phint[4 * 8 * 8];
    uint32_t upd[D_];
    uint32_t epoch[NCTA + 4];
};
__device__ __align__(1024) Scratch g_scr;

__device__ __forceinline__ uint32_t smem_u32(const void* p) { return (uint32_t)__cvta_generic_to_shared(p); }
__device__ __forceinline__ void mbar_init(uint32_t bar, uint32_t cnt) {
    asm volatile("mbarrier.init.shared::cta.b64 [%0], %1;" ::"r"(bar), "r"(cnt) : "memory");
}
__device__ __forceinline__ void mbar_expect_tx(uint32_t bar, uint32_t bytes) {
    asm volatile("mbarrier.arrive.expect_tx.shared::cta.b64 _, [%0], %1;" ::"r"(bar), "r"(bytes) : "memory");
}
__device__ __forceinline__ void mbar_arrive(uint32_t bar) {
    asm volatile("mbarrier.arrive.shared::cta.b64 _, [%0];" ::"r"(bar) : "memory");
}
template <int N>
__device__ __forceinline__ void mbar_arrive_n_if(uint32_t bar, bool pred) {
    asm volatile("{.reg .pred p; setp.ne.b32 p, %1, 0; @p mbarrier.arrive.shared::cta.b64 _, [%0], %2;}" ::"r"(bar), "r"((int)pred), "n"(N) : "memory");
}
__device__ __forceinline__ void mbar_arrive_if(uint32_t bar, bool pred) {
    asm volatile("{.reg .pred p; setp.ne.b32 p, %1, 0; @p mbarrier.arrive.shared::cta.b64 _, [%0];}" ::"r"(bar), "r"((int)pred) : "memory");
}
__device__ __forceinline__ void mbar_arrive_warp(uint32_t bar) {
    __syncwarp();
    mbar_arrive_if(bar, (threadIdx.x & 31) == 0);
}
__device__ __forceinline__ void mbar_arrive_cluster_if(uint32_t bar, bool pred) {
    asm volatile("{.reg .pred p; setp.ne.b32 p, %1, 0; @p mbarrier.arrive.shared::cluster.b64 _, [%0], 1;}"
                 ::"r"(bar), "r"((int)pred) : "memory");
}
__device__ __forceinline__ uint32_t mapa(uint32_t a, uint32_t cta) {
    uint32_t r;
    asm volatile("mapa.shared::cluster.u32 %0, %1, %2;" : "=r"(r) : "r"(a), "r"(cta));
    return r;
}
__device__ __forceinline__ bool mbar_try(uint32_t bar, uint32_t parity) {
    uint32_t ok;
    asm volatile("{.reg .pred p; mbarrier.try_wait.parity.shared::cta.b64 p, [%1], %2; selp.u32 %0,1,0,p;}"
                 : "=r"(ok) : "r"(bar), "r"(parity) : "memory");
    return ok;
}
__device__ __forceinline__ bool mbar_test(uint32_t bar, uint32_t parity) {
    uint32_t ok;
    asm volatile("{.reg .pred p; mbarrier.test_wait.parity.shared::cta.b64 p, [%1], %2; selp.u32 %0,1,0,p;}"
                 : "=r"(ok) : "r"(bar), "r"(parity) : "memory");
    return ok;
}
__device__ __forceinline__ void mbar_wait(uint32_t bar, uint32_t parity) {
    uint32_t n = 0;
#pragma unroll 1
    while (!mbar_try(bar, parity)) { if (++n > SPIN_LIMIT) break; }
}
__device__ __forceinline__ void tma2d_elect(uint32_t dst, const CUtensorMap* m, int c0, int c1, uint32_t bar) {
    asm volatile("{.reg .pred p; elect.sync _|p, 0xffffffff;"
                 " @p cp.async.bulk.tensor.2d.shared::cluster.global.mbarrier::complete_tx::bytes [%0], [%1, {%3,%4}], [%2];}"
                 ::"r"(dst), "l"(m), "r"(bar), "r"(c0), "r"(c1) : "memory");
}
__device__ __forceinline__ void tma2d_pair_elect(uint32_t dst, const CUtensorMap* m, int c0, int c1, uint32_t bar) {
    asm volatile("{.reg .pred p; elect.sync _|p, 0xffffffff;"
                 " @p cp.async.bulk.tensor.2d.shared::cluster.global.mbarrier::complete_tx::bytes.multicast::cluster"
                 " [%0], [%1, {%3,%4}], [%2], %5;}" ::"r"(dst), "l"(m), "r"(bar), "r"(c0), "r"(c1), "h"((uint16_t)3) : "memory");
}
__device__ __forceinline__ void tma3d_elect(uint32_t dst, const CUtensorMap* m, int row, int chunk, uint32_t bar) {
    asm volatile("{.reg .pred p; elect.sync _|p, 0xffffffff;"
                 " @p cp.async.bulk.tensor.3d.shared::cluster.global.mbarrier::complete_tx::bytes [%0], [%1, {%3,%4,%5}], [%2];}"
                 ::"r"(dst), "l"(m), "r"(bar), "r"(0), "r"(row), "r"(chunk) : "memory");
}
__device__ __forceinline__ void tma5d_elect(uint32_t dst, const CUtensorMap* m, int c0, int c4, uint32_t bar) {
    asm volatile("{.reg .pred p; elect.sync _|p, 0xffffffff;"
                 " @p cp.async.bulk.tensor.5d.shared::cluster.global.mbarrier::complete_tx::bytes [%0], [%1, {%3,%5,%5,%5,%4}], [%2];}"
                 ::"r"(dst), "l"(m), "r"(bar), "r"(c0), "r"(c4), "r"(0) : "memory");
}
__device__ __forceinline__ void mbar_expect_tx_elect(uint32_t bar, uint32_t bytes) {
    asm volatile("{.reg .pred p; elect.sync _|p, 0xffffffff; @p mbarrier.arrive.expect_tx.shared::cta.b64 _, [%0], %1;}"
                 ::"r"(bar), "r"(bytes) : "memory");
}
__device__ __forceinline__ void prefetch_l2(const void* p) { asm volatile("prefetch.global.L2 [%0];" ::"l"(p)); }
__device__ __forceinline__ uint32_t ld_relaxed(const void* p) {
    uint32_t v;
    asm volatile("ld.relaxed.gpu.global.u32 %0, [%1];" : "=r"(v) : "l"(p) : "memory");
    return v;
}
__device__ __forceinline__ uint4 ld_relaxed4(const void* p) {
    uint4 v;
    asm volatile("ld.relaxed.gpu.global.v4.u32 {%0,%1,%2,%3}, [%4];" : "=r"(v.x), "=r"(v.y), "=r"(v.z), "=r"(v.w) : "l"(p) : "memory");
    return v;
}
__device__ __forceinline__ void st_relaxed(unsigned int* p, uint32_t v) {
    asm volatile("st.relaxed.gpu.global.u32 [%0], %1;" ::"l"(p), "r"(v) : "memory");
}
__device__ __forceinline__ uint32_t tagf(float v, uint32_t par) { return (__float_as_uint(v) & ~1u) | par; }
template <int BIT = 0>
__device__ __forceinline__ uint4 wait_tags(const unsigned int* p, uint32_t par) {
    uint32_t n = 0;
#pragma unroll 1
    while (true) {
        const uint4 v = ld_relaxed4(p);
        const uint32_t m = par ? (v.x & v.y & v.z & v.w) : ~(v.x | v.y | v.z | v.w);
        if (__all_sync(0xffffffffu, (m >> BIT) & 1u)) return v;
        __nanosleep(100);
        if (++n > SPIN_LIMIT) return v;
    }
}
__device__ __forceinline__ uint32_t best_key(const uint32_t* keys, uint32_t par) {
    const uint4 k = wait_tags<15>(keys + (threadIdx.x & 31) * 4, par);
    return __reduce_max_sync(0xffffffffu, max(max(k.x, k.y), max(k.z, k.w)));
}
__device__ __forceinline__ void named_bar(int id, int n) { asm volatile("bar.sync %0, %1;" ::"r"(id), "r"(n) : "memory"); }
template <int OFF>
__device__ __forceinline__ uint4 ldg_nc_off(const void* p) {
    uint4 v;
    asm volatile("ld.global.nc.v4.u32 {%0,%1,%2,%3}, [%4+%5];" : "=r"(v.x), "=r"(v.y), "=r"(v.z), "=r"(v.w) : "l"(p), "n"(OFF));
    return v;
}
__device__ __forceinline__ void ldg_nc_if(uint4& v, const void* a, bool pred) {
    asm volatile("{.reg .pred p; setp.ne.b32 p, %5, 0; @p ld.global.nc.v4.u32 {%0,%1,%2,%3}, [%4];}"
                 : "+r"(v.x), "+r"(v.y), "+r"(v.z), "+r"(v.w) : "l"(a), "r"((int)pred) : "memory");
}
template <int OFF>
__device__ __forceinline__ void stg_off(void* p, const uint4& v) {
    asm volatile("st.global.v4.u32 [%0+%5], {%1,%2,%3,%4};" ::"l"(p), "r"(v.x), "r"(v.y), "r"(v.z), "r"(v.w), "n"(OFF) : "memory");
}
__device__ __forceinline__ void sts128(uint32_t a, const uint4& v) {
    asm volatile("st.shared.v4.u32 [%0], {%1,%2,%3,%4};" ::"r"(a), "r"(v.x), "r"(v.y), "r"(v.z), "r"(v.w) : "memory");
}
__device__ __forceinline__ uint4 lds128(uint32_t a) {
    uint4 v;
    asm volatile("ld.shared.v4.u32 {%0,%1,%2,%3}, [%4];" : "=r"(v.x), "=r"(v.y), "=r"(v.z), "=r"(v.w) : "r"(a) : "memory");
    return v;
}
__device__ __forceinline__ void lds128_if(uint4& v, uint32_t a, bool pred) {
    asm volatile("{.reg .pred p; setp.ne.b32 p, %5, 0; @p ld.shared.v4.u32 {%0,%1,%2,%3}, [%4];}"
                 : "+r"(v.x), "+r"(v.y), "+r"(v.z), "+r"(v.w) : "r"(a), "r"((int)pred) : "memory");
}
__device__ __forceinline__ uint32_t lds32(uint32_t a) {
    uint32_t v;
    asm volatile("ld.shared.u32 %0, [%1];" : "=r"(v) : "r"(a) : "memory");
    return v;
}
__device__ __forceinline__ void st_async16(uint32_t dst, uint32_t x, uint32_t y, uint32_t z, uint32_t w, uint32_t bar) {
    asm volatile("st.async.weak.shared::cluster.mbarrier::complete_tx::bytes.v4.b32 [%0], {%1,%2,%3,%4}, [%5];"
                 ::"r"(dst), "r"(x), "r"(y), "r"(z), "r"(w), "r"(bar) : "memory");
}
__device__ __forceinline__ int sel(int a, int b, bool p) {
    int r;
    asm("{.reg .pred q; setp.ne.b32 q, %3, 0; selp.b32 %0, %1, %2, q;}" : "=r"(r) : "r"(a), "r"(b), "r"((int)p));
    return r;
}
__device__ __forceinline__ float selpf(float a, float b, bool p) {
    float r;
    asm("{.reg .pred q; setp.ne.b32 q, %3, 0; selp.f32 %0, %1, %2, q;}" : "=f"(r) : "f"(a), "f"(b), "r"((int)p));
    return r;
}
template <int N, int MASK, int SZ>
__device__ __forceinline__ void halve(float (&a)[SZ]) {
    const bool up = threadIdx.x & MASK;
#pragma unroll
    for (int j = 0; j < N; j++) a[j] = selpf(a[N + j], a[j], up) + __shfl_xor_sync(0xffffffffu, selpf(a[j], a[N + j], up), MASK);
}
__device__ __forceinline__ float bflo(uint32_t u) { return __uint_as_float(u << 16); }
__device__ __forceinline__ float bfhi(uint32_t u) { return __uint_as_float(u & 0xffff0000u); }
__device__ __forceinline__ uint32_t pack_bf16(float lo, float hi) {
    uint32_t r;
    asm("cvt.rn.bf16x2.f32 %0, %1, %2;" : "=r"(r) : "f"(hi), "f"(lo));
    return r;
}
__device__ __forceinline__ uint32_t hmul2_bf16(uint32_t a, uint32_t b) {
    uint32_t r;
    asm("mul.rn.bf16x2 %0, %1, %2;" : "=r"(r) : "r"(a), "r"(b));
    return r;
}
__device__ __forceinline__ float sigmoidf_(float v) { return 1.0f / (1.0f + __expf(-v)); }
__device__ __forceinline__ void wg_fence() { asm volatile("wgmma.fence.sync.aligned;" ::: "memory"); }
__device__ __forceinline__ void wg_commit() { asm volatile("wgmma.commit_group.sync.aligned;" ::: "memory"); }
template <int N> __device__ __forceinline__ void wg_wait() { asm volatile("wgmma.wait_group.sync.aligned %0;" ::"n"(N) : "memory"); }
__device__ __forceinline__ uint64_t desc_lo(uint32_t lo) { return (uint64_t)lo | (0x40000040ull << 32); }
template <int LO, int HI, int N>
__device__ __forceinline__ void fence_regs(float (&d)[N]) {
#pragma unroll
    for (int i = LO; i < HI; i++) asm volatile("" : "+f"(d[i])::"memory");
}
template <int LO, int HI, int N>
__device__ __forceinline__ void keep_regs(uint4 (&f)[N]) {
#pragma unroll
    for (int i = LO; i < HI; i++) asm volatile("" ::"r"(f[i].x), "r"(f[i].y), "r"(f[i].z), "r"(f[i].w) : "memory");
}
template <int TB = 1>
__device__ __forceinline__ void wgmma128(float (&d)[64], uint64_t da, uint64_t db, int scaleD) {
    asm volatile(
        "{ .reg .pred p; setp.ne.b32 p, %66, 0;\n"
        "wgmma.mma_async.sync.aligned.m64n128k16.f32.bf16.bf16 "
        "{%0,%1,%2,%3,%4,%5,%6,%7,%8,%9,%10,%11,%12,%13,%14,%15,%16,%17,%18,%19,%20,%21,%22,%23,%24,%25,%26,%27,%28,%29,%30,%31,"
        "%32,%33,%34,%35,%36,%37,%38,%39,%40,%41,%42,%43,%44,%45,%46,%47,%48,%49,%50,%51,%52,%53,%54,%55,%56,%57,%58,%59,%60,%61,%62,%63}, "
        "%64, %65, p, 1, 1, 0, %67;\n}"
        : "+f"(d[0]), "+f"(d[1]), "+f"(d[2]), "+f"(d[3]), "+f"(d[4]), "+f"(d[5]), "+f"(d[6]), "+f"(d[7]),
          "+f"(d[8]), "+f"(d[9]), "+f"(d[10]), "+f"(d[11]), "+f"(d[12]), "+f"(d[13]), "+f"(d[14]), "+f"(d[15]),
          "+f"(d[16]), "+f"(d[17]), "+f"(d[18]), "+f"(d[19]), "+f"(d[20]), "+f"(d[21]), "+f"(d[22]), "+f"(d[23]),
          "+f"(d[24]), "+f"(d[25]), "+f"(d[26]), "+f"(d[27]), "+f"(d[28]), "+f"(d[29]), "+f"(d[30]), "+f"(d[31]),
          "+f"(d[32]), "+f"(d[33]), "+f"(d[34]), "+f"(d[35]), "+f"(d[36]), "+f"(d[37]), "+f"(d[38]), "+f"(d[39]),
          "+f"(d[40]), "+f"(d[41]), "+f"(d[42]), "+f"(d[43]), "+f"(d[44]), "+f"(d[45]), "+f"(d[46]), "+f"(d[47]),
          "+f"(d[48]), "+f"(d[49]), "+f"(d[50]), "+f"(d[51]), "+f"(d[52]), "+f"(d[53]), "+f"(d[54]), "+f"(d[55]),
          "+f"(d[56]), "+f"(d[57]), "+f"(d[58]), "+f"(d[59]), "+f"(d[60]), "+f"(d[61]), "+f"(d[62]), "+f"(d[63])
        : "l"(da), "l"(db), "r"(scaleD), "n"(TB));
}
__device__ __forceinline__ void wgmma128rs(float (&d)[64], const uint4& a, uint64_t db, int scaleD) {
    asm volatile(
        "{ .reg .pred p; setp.ne.b32 p, %69, 0;\n"
        "wgmma.mma_async.sync.aligned.m64n128k16.f32.bf16.bf16 "
        "{%0,%1,%2,%3,%4,%5,%6,%7,%8,%9,%10,%11,%12,%13,%14,%15,%16,%17,%18,%19,%20,%21,%22,%23,%24,%25,%26,%27,%28,%29,%30,%31,"
        "%32,%33,%34,%35,%36,%37,%38,%39,%40,%41,%42,%43,%44,%45,%46,%47,%48,%49,%50,%51,%52,%53,%54,%55,%56,%57,%58,%59,%60,%61,%62,%63}, "
        "{%64,%65,%66,%67}, %68, p, 1, 1, 0;\n}"
        : "+f"(d[0]), "+f"(d[1]), "+f"(d[2]), "+f"(d[3]), "+f"(d[4]), "+f"(d[5]), "+f"(d[6]), "+f"(d[7]),
          "+f"(d[8]), "+f"(d[9]), "+f"(d[10]), "+f"(d[11]), "+f"(d[12]), "+f"(d[13]), "+f"(d[14]), "+f"(d[15]),
          "+f"(d[16]), "+f"(d[17]), "+f"(d[18]), "+f"(d[19]), "+f"(d[20]), "+f"(d[21]), "+f"(d[22]), "+f"(d[23]),
          "+f"(d[24]), "+f"(d[25]), "+f"(d[26]), "+f"(d[27]), "+f"(d[28]), "+f"(d[29]), "+f"(d[30]), "+f"(d[31]),
          "+f"(d[32]), "+f"(d[33]), "+f"(d[34]), "+f"(d[35]), "+f"(d[36]), "+f"(d[37]), "+f"(d[38]), "+f"(d[39]),
          "+f"(d[40]), "+f"(d[41]), "+f"(d[42]), "+f"(d[43]), "+f"(d[44]), "+f"(d[45]), "+f"(d[46]), "+f"(d[47]),
          "+f"(d[48]), "+f"(d[49]), "+f"(d[50]), "+f"(d[51]), "+f"(d[52]), "+f"(d[53]), "+f"(d[54]), "+f"(d[55]),
          "+f"(d[56]), "+f"(d[57]), "+f"(d[58]), "+f"(d[59]), "+f"(d[60]), "+f"(d[61]), "+f"(d[62]), "+f"(d[63])
        : "r"(a.x), "r"(a.y), "r"(a.z), "r"(a.w), "l"(db), "r"(scaleD));
}
__device__ __forceinline__ uint32_t clk() { uint64_t c; asm volatile("mov.u64 %0, %%clock64;" : "=l"(c)::"memory"); return (uint32_t)c; }
__device__ __forceinline__ uint32_t gtime() { uint64_t t; asm volatile("mov.u64 %0, %%globaltimer;" : "=l"(t)::"memory"); return (uint32_t)t; }
__device__ __forceinline__ void until(uint32_t t) { while (t - clk() < 0x8000u) {} }
__device__ __forceinline__ void nap_until(uint32_t t) { while (t - clk() < 0x8000u) __nanosleep(20); }
__device__ __forceinline__ uint4 scale_add(float s, const float (&a)[64], int o, const uint4& w) {
    return make_uint4(pack_bf16(fmaf(s, a[o], bflo(w.x)), fmaf(s, a[o + 1], bfhi(w.x))), pack_bf16(fmaf(s, a[o + 4], bflo(w.y)), fmaf(s, a[o + 5], bfhi(w.y))),
                      pack_bf16(fmaf(s, a[o + 8], bflo(w.z)), fmaf(s, a[o + 9], bfhi(w.z))), pack_bf16(fmaf(s, a[o + 12], bflo(w.w)), fmaf(s, a[o + 13], bfhi(w.w))));
}

__device__ __forceinline__ uint32_t router_key(float score, int row) {
    const float r = score + 0.0f;
    uint32_t u = pack_bf16(r, 0.f) & 0xffffu;
    u = (u & 0x8000u) ? (~u & 0xffffu) : (u | 0x8000u);
    if (r != r) u = 0;
    return (u << 16) | (uint32_t)(0x7fff - row);
}

#define g_ab g_scr.frag
#define g_fb_h ((float*)g_scr.part)
#define g_fb_upd (g_fb_h + 2048)
#define g_fb_gate (g_fb_h + 4096)
#define g_fb_keys (g_scr.part + 8192)
__global__ void fb_hidden(const bf16* x, const bf16* dre, const bf16* dim, const bf16* gw, const bf16* wr) {
    __shared__ float xs[D_];
    const int s = blockIdx.x, t = threadIdx.x;
    xs[t] = __bfloat162float(x[s * D_ + t]);
    __syncthreads();
    float a = 0.f, b = 0.f;
    for (int d = 0; d < D_; d++) { a = fmaf(xs[d], __bfloat162float(dre[t * D_ + d]), a); b = fmaf(xs[d], __bfloat162float(dim[t * D_ + d]), b); }
    ((bf16*)g_ab)[s * 1024 + t] = __float2bfloat16(a);
    ((bf16*)g_ab)[s * 1024 + 512 + t] = __float2bfloat16(b);
    if (t == 0) {
        float u = 0.f, v = 0.f;
        for (int d = 0; d < D_; d++) { u += bfhi(pack_bf16(0.f, xs[d] * __bfloat162float(gw[d]))); v = fmaf(xs[d], __bfloat162float(wr[d]), v); }
        g_fb_gate[s] = bfhi(pack_bf16(0.f, sigmoidf_(bfhi(pack_bf16(0.f, u)))));
        g_fb_keys[s] = router_key(v, s);
    }
}
__device__ uint32_t fb_best() {
    uint32_t k = 0;
    for (int i = 0; i < S_; i++) k = max(k, g_fb_keys[i]);
    return k;
}
__global__ void fb_ffn1(const bf16* x, const bf16* wg, const bf16* wu) {
    const int f = blockIdx.x * blockDim.x + threadIdx.x, idx = 0x7fff - (int)(fb_best() & 0x7fffu);
    float a = 0.f, b = 0.f;
    for (int d = 0; d < D_; d++) {
        const float xv = __bfloat162float(x[idx * D_ + d]);
        a = fmaf(xv, __bfloat162float(wg[d * F_ + f]), a); b = fmaf(xv, __bfloat162float(wu[d * F_ + f]), b);
    }
    g_fb_h[f] = a * sigmoidf_(a) * b;
}
__global__ void fb_ffn2(const bf16* wd) {
    const int e = blockIdx.x * blockDim.x + threadIdx.x;
    const uint32_t u = fb_best() >> 16, rb = (u & 0x8000u) ? (u & 0x7fffu) : (~u & 0xffffu);
    float a = 0.f;
    for (int f = 0; f < F_; f++) a = fmaf(g_fb_h[f], __bfloat162float(wd[f * D_ + e]), a);
    g_fb_upd[e] = a * sigmoidf_(__uint_as_float(rb << 16));
}
__global__ void fb_seq(const bf16* x, const bf16* cre, const bf16* cim, bf16* out) {
    __shared__ float c[2][S_];
    __shared__ int idx;
    const int t = blockIdx.x, e = threadIdx.x;
    for (int i = e; i < S_; i += D_) { c[0][i] = __bfloat162float(cre[t * S_ + i]); c[1][i] = __bfloat162float(cim[t * S_ + i]); }
    if (e == 0) idx = 0x7fff - (int)(fb_best() & 0x7fffu);
    __syncthreads();
    float y = 0.f;
    for (int s = 0; s < S_; s++)
        y += c[0][s] * __bfloat162float(((const bf16*)g_ab)[s * 1024 + e]) - c[1][s] * __bfloat162float(((const bf16*)g_ab)[s * 1024 + 512 + e]);
    const float g = g_fb_gate[t];
    out[t * D_ + e] = __float2bfloat16(g * y + (1.f - g) * (__bfloat162float(x[t * D_ + e]) + (t == idx ? g_fb_upd[e] : 0.f)));
}

__device__ __forceinline__ void spare_job(const Params& p, Scratch* g, unsigned char* smem, int sp, uint32_t tstart) {
    const int tid = threadIdx.x, warp = tid >> 5, lane = tid & 31;
    if (warp >= 8) {
#pragma unroll 1
        for (int i = 0; i < 16; i++) {
            nap_until(tstart + PFD_T0 + i * (PFD_DT / 2));
            prefetch_l2((const char*)((sp & 2) ? p.dim : p.dre) + (sp & 1) * 262144 + i * 16384 + (tid - 256) * 128);
        }
        return;
    }
    named_bar(2, 288);
    mbar_wait(smem_u32(smem) + B_FULL, 0);
    nap_until(tstart + SUM_T0 - 2000);
    const uint32_t e1 = ld_relaxed(g->epoch + NCTA + sp) + 1u, par = e1 & 1u;
    const uint32_t u = best_key(g->keys + warp * NCTA, par) >> 16;
    const float rs = sigmoidf_(__uint_as_float(((u & 0x8000u) ? (u & 0x7fffu) : (~u & 0xffffu)) << 16));
    nap_until(tstart + SUM_T0);
    uint32_t n = 0;
#pragma unroll 1
    while ((int)(ld_relaxed(g->phint + (sp * 8 + warp) * 8) - e1 * 14u) < 0) {
        __nanosleep(40);
        if (++n > SPIN_LIMIT) break;
    }
    const unsigned int* src = g->part + warp * 7 * D_ + sp * 128 + lane * 4;
    uint4 v[7];
#pragma unroll 1
    while (true) {
        uint32_t bad = 0;
#pragma unroll
        for (int i = 0; i < 7; i++) v[i] = ld_relaxed4(src + i * D_);
#pragma unroll
        for (int i = 0; i < 7; i++) bad |= (v[i].x ^ par) | (v[i].y ^ par) | (v[i].z ^ par) | (v[i].w ^ par);
        if (!__any_sync(0xffffffffu, bad & 1u)) break;
        if (++n > SPIN_LIMIT) break;
    }
    float4 s = make_float4(0.f, 0.f, 0.f, 0.f);
#pragma unroll
    for (int i = 0; i < 7; i++) {
        s.x += __uint_as_float(v[i].x); s.y += __uint_as_float(v[i].y);
        s.z += __uint_as_float(v[i].z); s.w += __uint_as_float(v[i].w);
    }
    float* acc = (float*)(smem + R6);
    *(float4*)&acc[warp * 128 + lane * 4] = s;
    named_bar(1, 256);
    if (tid < 128) {
        float t = 0.f;
#pragma unroll
        for (int i = 0; i < 8; i++) t += acc[i * 128 + tid];
        st_relaxed(&g->upd[sp * 128 + tid], tagf(t * rs, par));
        if (tid == 0) st_relaxed(g->epoch + NCTA + sp, e1);
    }
}

__device__ __forceinline__ int ffn_pair(int role) { return role - __popcll(NOFFN_MASK & ((1ull << role) - 1)); }
__device__ __forceinline__ int other(int i, int tn) { return i + (i >= tn); }
__device__ __forceinline__ int dcol(int p, int tn) { return p < 2 ? tn * 128 + p * 64 : other((p - 2) % 3, tn) * 128 + (p >= 5 ? 64 : 0); }

template <int H>
__device__ __forceinline__ void fetch_job(const Params& p, Scratch* g, unsigned char* smem, uint32_t sb, int cta, int i, uint32_t par) {
    const int lane = threadIdx.x & 31, comp = cta & 1;
    const int j = other(i, (cta >> 1) & 3), src = (cta & ~6) + 2 * j;
    const int slot = i == 0 ? 29 % NST : i - 1;
    const uint32_t land = sb + B_LAND + 8 * (3 * H + i);
    uint32_t ph = 0, th;
    mbar_expect_tx_elect(land, 8192);
    if (H == 0) {
        mbar_wait(sb + B_S0, 0);
        const uint32_t t0 = clk();
        if (i == 0) {
            mbar_wait(sb + B_FULL + 8 * (31 % NST), (31 / NST) & 1);
            const uint32_t t1 = t0 + max(clk() - t0, 180u) - 180u;
            asm volatile("{.reg .pred p; .reg .b64 t; setp.eq.b32 p, %3, 0; mov.b64 t, {%1, %2}; @p st.relaxed.gpu.global.b64 [%0], t;}"
                         ::"l"(g->stamp + cta * 32), "r"((t1 & ~1u) | par), "r"(gtime()), "r"(lane) : "memory");
        }
        until(t0 + SDEL);
        uint32_t gt;
#pragma unroll 1
        for (uint32_t n = 0; n < SPIN_LIMIT; n++) {
            asm volatile("{.reg .b64 t; ld.relaxed.gpu.global.b64 t, [%2]; mov.b64 {%0,%1}, t;}" : "=r"(th), "=r"(gt) : "l"(g->stamp + src * 32) : "memory");
            if (!__any_sync(0xffffffffu, (th ^ par) & 1u)) break;
        }
        const uint32_t ns = min(gtime() - gt, 4096u), now = clk();
        if (now - th >= 8192u) th = now - (ns + (ns >> 1) + (ns >> 4));
        th += SG * j;
        if (lane == 0) { *(volatile uint32_t*)(smem + M_TH + 4 * i) = th; mbar_arrive(sb + B_TH + 8 * i); }
        __syncwarp();
    } else {
        mbar_wait(sb + B_TH + 8 * i, 0);
        th = lds32(sb + M_TH + 4 * i);
    }
    mbar_wait(sb + B_EA, 0);
#pragma unroll 1
    for (int c = 0; c < 2; c++) {
        const uint32_t dst = sb + slot * 16384 + (c ? NST * 16384 + H * 8192 : (comp ^ H) * 8192);
        if (c != H) mbar_wait(sb + B_EMPTY + 8 * slot, i != 0);
        until(th + (c ? (H ? L_RD1 : L_RD0) : (H ? E_RD1 : E_RD0)));
#pragma unroll 1
        for (uint32_t r = 0; r < SPIN_LIMIT; r++) {
            tma2d_elect(dst, &p.mF, 0, (src * 2 + (comp ^ c)) * 128 + H * 64, land);
            mbar_wait(land, ph);
            ph ^= 1;
            const uint32_t a = dst + (lane >> 2) * 132 + (lane & 3) * 32;
            uint32_t v[8], m0 = 0, m1 = ~0u;
#pragma unroll
            for (int k = 0; k < 8; k++) v[k] = lds32(a + k * 1024);
#pragma unroll
            for (int k = 0; k < 8; k++) { m0 |= v[k]; m1 &= v[k]; }
            if (__all_sync(0xffffffffu, (par ? m1 : ~m0) & 1u)) break;
            mbar_expect_tx_elect(land, 8192);
        }
        mbar_arrive_if(sb + B_VAL + 8 * (6 * c + 3 * H + i), lane == 0);
        if (c == 0) mbar_expect_tx_elect(land, 8192);
    }
}

__global__ void __cluster_dims__(2, 1, 1) __launch_bounds__(NTHREADS, 1)
fused_kernel(const __grid_constant__ CPtr pc, const char* px, char* pout, Scratch* g, const __grid_constant__ Params p) {
    extern __shared__ __align__(1024) unsigned char smem[];
    const uint32_t sb = smem_u32(smem);
    const int tid = threadIdx.x, warp = tid >> 5, lane = tid & 31;
    const int rank = blockIdx.x & 1;
    const char* pcr = pc.c[rank];
    asm volatile("{.reg .pred p; setp.lt.u32 p, %1, 32; @p prefetch.global.L2 [%0];}"
                 ::"l"(pcr + (uint32_t)(((blockIdx.x << 16) & 0x7e0000) + (tid << 12))), "r"(tid));
    const uint32_t tstart = clk();
    asm volatile("{.reg .pred p; setp.lt.u32 p, %1, 4; @p prefetch.global.L2 [%0];}"
                 ::"l"(px + (uint32_t)(((blockIdx.x << 9) & 0xfe00) + (tid << 7))), "r"(tid));
    uint32_t smid;
    asm volatile("mov.u32 %0, %%smid;" : "=r"(smid));
    const int u = smid >> 1;
    const int code = sel(u, sel(((u - 32) * 293) >> 8, 8 * u - 489, u < 60), u < 32);
    const int tn = code >> 3, tm = (code & 7) + sel(0, 8, u < 32);
    const int comp = rank;
    const CUtensorMap* mC = &p.mCre + comp;
#define ARM(j) do { mbar_init(sb + B_FULL + 8 * (j), 1); mbar_expect_tx(sb + B_FULL + 8 * (j), 32768); } while (0)
#define STEP0(j) do { tma2d_elect(sb + (j) * 16384, mC, (j) * 64, tm * 128, sb + B_FULL + 8 * (j));                            \
                      tma3d_elect(sb + (NST + (j)) * 16384, &p.mX2, (j) * 64, tn * 2, sb + B_FULL + 8 * (j)); } while (0)
    if (__all_sync(0xffffffffu, warp == 12)) {
        asm volatile("{.reg .pred p; elect.sync _|p, 0xffffffff; @p mbarrier.init.shared::cta.b64 [%0], 1;}" ::"r"(sb + B_FULL) : "memory");
        STEP0(0);
        mbar_expect_tx_elect(sb + B_FULL, 32768);
        asm volatile("bar.arrive 2, 288;" ::: "memory");
    }
    const bool spare = tn < 0;
    const int role = tm * 4 + tn, cta = role * 2 + rank;
    const int wu = __shfl_sync(0xffffffffu, warp, 0);
    if (wu < 12) {
        if (lane == 0) {
            mbar_init(sb + B_EMPTY + 8 * wu, 2);
            mbar_init(sb + B_VD + 8 * wu, wu ? 1 : 4);
#pragma unroll
            for (int i = 24; i < NBAR; i += 12) if (i + 12 <= NBAR || wu < NBAR - i) mbar_init(sb + B_EMPTY + 8 * (i + wu), 1);
            if (wu >= 1 && wu < 4) mbar_expect_tx(sb + B_VD + 8 * wu, wu < 3 ? 8192 : 256);
        }
        asm volatile("fence.mbarrier_init.release.cluster;" ::: "memory");
        __syncwarp();
        asm volatile("barrier.cluster.arrive.relaxed.aligned;" ::: "memory");
        if (spare) {
            spare_job(p, g, smem, smid & 3, tstart);
        } else if (wu >= 8) {
            asm volatile("setmaxnreg.dec.sync.aligned.u32 " STR(RS_) ";");
            asm volatile("barrier.cluster.wait.acquire.aligned;" ::: "memory");
            const int t = tid - 256, w = wu - 8, fr = ffn_pair(role);
            const bool ffn = !((NOFFN_MASK >> role) & 1);
            nap_until(tstart + SIDE_T0);
            const uint4 gw0 = ldg_nc_off<0>(p.gate_w + lane * 8), gw1 = ldg_nc_off<512>(p.gate_w + lane * 8);
            const uint4 rw0 = ldg_nc_off<0>(p.w_r + lane * 8), rw1 = ldg_nc_off<512>(p.w_r + lane * 8);
            const uint32_t par = ~ld_relaxed(g->epoch + cta) & 1u;
            nap_until(tstart + ROUTER_T0 + (2 * w + rank) * ROUTER_DT);
            {
                const int row0 = cta * 16 + w * 4;
                const char* xp = px + (uint32_t)row0 * (D_ * 2) + lane * 16;
                uint4 xa[4], xb[4];
                xa[0] = ldg_nc_off<0>(xp);    xb[0] = ldg_nc_off<512>(xp);  xa[1] = ldg_nc_off<1024>(xp); xb[1] = ldg_nc_off<1536>(xp);
                xa[2] = ldg_nc_off<2048>(xp); xb[2] = ldg_nc_off<2560>(xp); xa[3] = ldg_nc_off<3072>(xp); xb[3] = ldg_nc_off<3584>(xp);
                float a[8];
#pragma unroll
                for (int i = 0; i < 4; i++) {
                    const uint32_t xv[8] = {xa[i].x, xa[i].y, xa[i].z, xa[i].w, xb[i].x, xb[i].y, xb[i].z, xb[i].w};
                    const uint32_t gv[8] = {gw0.x, gw0.y, gw0.z, gw0.w, gw1.x, gw1.y, gw1.z, gw1.w};
                    const uint32_t rv[8] = {rw0.x, rw0.y, rw0.z, rw0.w, rw1.x, rw1.y, rw1.z, rw1.w};
                    float uu = 0.f, vv = 0.f;
#pragma unroll
                    for (int j = 0; j < 8; j++) {
                        uu = fmaf(bflo(xv[j]), bflo(gv[j]), uu); uu = fmaf(bfhi(xv[j]), bfhi(gv[j]), uu);
                        vv = fmaf(bflo(xv[j]), bflo(rv[j]), vv); vv = fmaf(bfhi(xv[j]), bfhi(rv[j]), vv);
                    }
                    a[i] = uu; a[4 + i] = vv;
                }
                halve<4, 16>(a); halve<2, 8>(a); halve<1, 4>(a);
                {
                    const float b1 = __shfl_xor_sync(0xffffffffu, a[0], 1), b2 = __shfl_xor_sync(0xffffffffu, a[0], 2),
                                b3 = __shfl_xor_sync(0xffffffffu, a[0], 3);
                    a[0] = (a[0] + b1) + (b2 + b3);
                }
                const int row = row0 + ((lane >> 2) & 3);
                const uint32_t best = __reduce_max_sync(0xffffffffu, lane >= 16 && (lane & 3) == 0 ? router_key(a[0], row) : 0u);
                if (lane <= 16 && (lane & 3) == 0)
                    *(volatile uint32_t*)(smem + M_RED + (lane < 16 ? w * 16 + lane : 64 + w * 4)) = lane < 16 ? pack_bf16(0.f, sigmoidf_(bfhi(pack_bf16(0.f, a[0])))) | par : best;
                named_bar(1, 128);
                if (t < 8) {
                    const uint4 k = lds128(sb + M_RED + 64);
                    asm volatile("{.reg .b32 old; atom.relaxed.gpu.global.exch.b32 old, [%0], %1;}"
                                 ::"l"(g->keys + t * NCTA + cta), "r"(max(max(k.x, k.y), max(k.z, k.w)) | (par << 15)) : "memory");
                }
                if (w == 1 && lane < 16) st_relaxed(g->gate + cta * 16 + lane, lds32(sb + M_RED + lane * 4));
            }
            uint32_t vd[32];
            if (ffn) {
                mbar_wait(sb + B_FFN + 24, 0);
#pragma unroll
                for (int j = 0; j < 32; j++) vd[j] = lds32(sb + R6 + ((j >> 3) & 1) * 16384 + (2 + (j >> 4)) * 4096 + (j & 7) * 512 + t * 4);
                mbar_arrive_warp(sb + B_VD);
            }
            mbar_wait(sb + B_GATE, 0);
            const int idx = 0x7fff - (int)(*(volatile uint32_t*)(smem + M_KEY) & 0x7fffu);
            if (ffn) {
                float a[16];
#pragma unroll
                for (int i = 0; i < 16; i++) a[i] = 0.f;
#pragma unroll 1
                for (int qu = 0; qu < 4; qu++) {
                    mbar_wait(sb + B_FFN + 8 * qu, qu == 3);
#pragma unroll
                    for (int i = 2 * qu; i < 2 * qu + 2; i++) {
                        const float xs = __bfloat162float(((const bf16*)(smem + M_UPD))[32 * i + (t >> 2)]);
                        const uint4 vg = lds128(sb + R6 + i * 2048 + t * 16);
                        const uint4 vu = lds128(sb + R6 + 16384 + i * 2048 + t * 16);
                        const uint32_t g4[4] = {vg.x, vg.y, vg.z, vg.w};
                        const uint32_t u4[4] = {vu.x, vu.y, vu.z, vu.w};
#pragma unroll
                        for (int j = 0; j < 4; j++) {
                            a[2 * j] = fmaf(xs, bflo(g4[j]), a[2 * j]);         a[2 * j + 1] = fmaf(xs, bfhi(g4[j]), a[2 * j + 1]);
                            a[8 + 2 * j] = fmaf(xs, bflo(u4[j]), a[8 + 2 * j]); a[9 + 2 * j] = fmaf(xs, bfhi(u4[j]), a[9 + 2 * j]);
                        }
                    }
                }
                named_bar(1, 128);
                mbar_arrive_if(sb + B_R6, t == 0);
                halve<8, 16>(a); halve<4, 8>(a); halve<2, 4>(a);
                float* red = (float*)(smem + M_UPD);
                *(float2*)&red[w * 64 + (lane >> 4) * 32 + (lane & 3) * 8 + ((lane >> 2) & 3) * 2] = make_float2(a[0], a[1]);
                named_bar(1, 128);
                const float sg = red[lane] + red[64 + lane] + red[128 + lane] + red[192 + lane];
                const float su = red[32 + lane] + red[96 + lane] + red[160 + lane] + red[224 + lane];
                if (w < 2) {
                    asm volatile("st.async.weak.shared::cluster.mbarrier::complete_tx::bytes.f32 [%0], %1, [%2];"
                                 ::"r"(mapa(sb + M_HX + t * 4, rank ^ 1)), "f"(w ? su : sg), "r"(mapa(sb + B_HX, rank ^ 1)) : "memory");
                }
                named_bar(1, 128);
                mbar_wait(sb + B_HX, 0);
                const float pg = ((const float*)(smem + M_HX))[lane], pu = ((const float*)(smem + M_HX))[32 + lane];
                const float gs = sg + pg, us = su + pu;
                float* hrow = red + w * 32;
                hrow[lane] = gs * sigmoidf_(gs) * us;
                __syncwarp();
                float o0 = 0.f, o1 = 0.f;
#pragma unroll
                for (int j4 = 0; j4 < 8; j4++) {
                    const float4 hv = *(const float4*)&hrow[j4 * 4];
                    o0 = fmaf(hv.x, bflo(vd[4 * j4]), o0);     o1 = fmaf(hv.x, bfhi(vd[4 * j4]), o1);
                    o0 = fmaf(hv.y, bflo(vd[4 * j4 + 1]), o0); o1 = fmaf(hv.y, bfhi(vd[4 * j4 + 1]), o1);
                    o0 = fmaf(hv.z, bflo(vd[4 * j4 + 2]), o0); o1 = fmaf(hv.z, bfhi(vd[4 * j4 + 2]), o1);
                    o0 = fmaf(hv.w, bflo(vd[4 * j4 + 3]), o0); o1 = fmaf(hv.w, bfhi(vd[4 * j4 + 3]), o1);
                }
                asm volatile("st.relaxed.gpu.global.v2.u32 [%0], {%1,%2};" ::"l"(&g->part[fr * D_ + rank * 256 + t * 2]),
                             "r"(tagf(o0, par)), "r"(tagf(o1, par)) : "memory");
                if (lane == 0) asm volatile("red.relaxed.gpu.global.add.u32 [%0], 1;" ::"l"(g->phint + ((rank * 2 + (w >> 1)) * 8 + fr / 7) * 8) : "memory");
            }
            if (!ffn) mbar_arrive_if(sb + B_R6, t == 0);
            if (w < 3) {
                fetch_job<1>(p, g, smem, sb, cta, w, par);
            } else {
                if (lds32(sb + M_ROLE) != (uint32_t)role) __trap();
                if ((idx >> 6) == 2 * tm + comp) {
                    float lg = 0.f;
#pragma unroll
                    for (int h = 0; h < 2; h++) {
                        const uint4 xv = ldg_nc_off<0>(px + idx * (D_ * 2) + h * 512 + lane * 16), gv = ldg_nc_off<0>(p.gate_w + h * 256 + lane * 8);
                        const uint32_t pr[4] = {hmul2_bf16(xv.x, gv.x), hmul2_bf16(xv.y, gv.y), hmul2_bf16(xv.z, gv.z), hmul2_bf16(xv.w, gv.w)};
#pragma unroll
                        for (int j = 0; j < 4; j++) lg += bflo(pr[j]) + bfhi(pr[j]);
                    }
#pragma unroll
                    for (int m = 16; m > 0; m >>= 1) lg += __shfl_xor_sync(0xffffffffu, lg, m);
                    const float og = bfhi(pack_bf16(0.f, 1.f - bfhi(pack_bf16(0.f, sigmoidf_(bfhi(pack_bf16(0.f, lg)))))));
                    const uint4 u4 = wait_tags(g->upd + tn * 128 + lane * 4, par);
                    *(float4*)(smem + M_RED + lane * 16) = make_float4(og * __uint_as_float(u4.x), og * __uint_as_float(u4.y),
                                                                       og * __uint_as_float(u4.z), og * __uint_as_float(u4.w));
                    mbar_arrive_warp(sb + B_SIDE);
                }
            }
        } else {
            const int wg = wu >> 2;
            const uint32_t sbd = (sb & 0x3FFFF) >> 4;
            const bool lead = (tid & 127) == 0;
            const bool early = wg == comp;
            const int q = lane & 3;
            const int r0 = (warp & 3) * 16 + (lane >> 2);
            float acc[64];
            const uint32_t da0 = sbd + 0x10000 + wg * 512, db0 = sbd + 0x2000000, dd0 = sbd + 0x10000;
            const uint32_t rE = mapa(sb + B_EMPR, rank ^ 1);
#define WAITFULL(s) mbar_wait(sb + B_FULL + 8 * ((s) % NST), ((s) / NST) & 1)
#define TESTFULL(s) mbar_test(sb + B_FULL + 8 * ((s) % NST), ((s) / NST) & 1)
#define WAITD(pos) do { if ((pos) >= 4) mbar_wait(sb + B_DL + 8 * ((pos) & 3), 0); else if ((pos) >= 2) mbar_wait(sb + B_D6, 0); else WAITFULL(32); } while (0)
#define MMA_A(s, kk) wgmma128(acc, desc_lo(da0 + a_addr(s) / 16 + (kk) * 2), desc_lo(db0 + b_addr(s) / 16 + (kk) * 128), 1)
            named_bar(2, 288);
            WAITFULL(0);
            wg_fence();
#pragma unroll
            for (int kk = 0; kk < 4; kk++) wgmma128(acc, desc_lo(da0 + kk * 2), desc_lo(db0 + b_addr(0) / 16 + kk * 128), kk != 0);
            wg_commit();
            asm volatile("setmaxnreg.inc.sync.aligned.u32 " STR(RC) ";");
            asm volatile("barrier.cluster.wait.acquire.aligned;" ::: "memory");
            int slot = 1, ph = 0, pslot = 0;
            const uint32_t ooff = (uint32_t)((tm * 128 + wg * 64 + r0) * D_ + tn * 128 + q * 8) * 2u;
            uint32_t* fout = g->frag + (cta * 2 + wg) * 4096 + (warp & 3) * 128 + lane;
            uint32_t tagm[4];
#pragma unroll
            for (int c = 0; c < 4; c++) tagm[c] = (lane & 7) == (warp & 1) * 4 + c;
            const char* xp = px + ooff;
            asm volatile("" : "+r"(tagm[0]), "+r"(tagm[1]), "+r"(tagm[2]), "+r"(tagm[3]), "+l"(xp), "+l"(fout));
            uint4 w[8];
#pragma unroll
            for (int i = 0; i < 8; i++) w[i] = make_uint4(0, 0, 0, 0);
#pragma unroll
            for (int part = 0; part <= XN; part++) {
                if (part) {
#pragma unroll
                    for (int i = (part - 1) * 8 / XN; i < part * 8 / XN; i++) ldg_nc_if(w[i], xp + (i & 1) * 8192 + (i >> 1) * 64, early);
                }
#pragma unroll 1
                for (int step = part ? XLD + (part - 1) * XD : 1; step < (part < XN ? XLD + part * XD : SP0); step++) {
                    mbar_wait(sb + B_FULL + 8 * slot, ph);
                    const uint32_t a = da0 + slot * 1024, b = db0 + b_addr(0) / 16 + slot * 1024;
                    wg_fence();
                    wgmma128(acc, desc_lo(a), desc_lo(b), 1);
                    wg_commit();
                    wg_wait<1>();
                    mbar_arrive_if(sb + B_EMPTY + 8 * pslot, lead);
                    mbar_arrive_cluster_if(rE + 8 * pslot, lead);
                    pslot = slot;
                    if (++slot == NST) { slot = 0; ph ^= 1; }
                    wg_fence();
#pragma unroll
                    for (int kk = 1; kk < 4; kk++) wgmma128(acc, desc_lo(a + kk * 2), desc_lo(b + kk * 128), 1);
                    wg_commit();
                }
            }
            uint32_t par;
            float g0, g1;
#define GATES() do { par = lds32(sb + M_PAR); g0 = __uint_as_float(lds32(sb + M_G + (wg * 64 + r0) * 4)); g1 = __uint_as_float(lds32(sb + M_G + (wg * 64 + r0 + 8) * 4)); } while (0)
            if (early) {
                WAITFULL(SP0);
                wg_fence();
                MMA_A(SP0, 0); MMA_A(SP0, 1);
                wg_commit();
                wg_wait<1>();
                mbar_arrive_if(sb + B_EMPTY + 8 * ((SP0 - 1) % NST), lead);
                bool ok = TESTFULL(SP0 + 1);
                MMA_A(SP0, 2); MMA_A(SP0, 3);
                wg_commit();
#pragma unroll
                for (int s = SP0 + 1; s < 32; s++) {
                    if (!ok) { WAITFULL(s); if (s == 29) mbar_wait(sb + B_GATE, 0); }
                    wg_fence();
                    MMA_A(s, 0); MMA_A(s, 1);
                    if (s == 29) GATES();
                    if (s >= 30) { wg_commit(); wg_wait<1>(); mbar_arrive_if(sb + (s == 30 ? B_S0 : B_S1), lead); wg_fence(); }
                    if (s < 31) ok = TESTFULL(s + 1) & (s != 28 || mbar_test(sb + B_GATE, 0));
                    MMA_A(s, 2); MMA_A(s, 3);
                    wg_commit();
                }
                wg_wait<0>();
                mbar_arrive_if(sb + B_EA, lead);
            } else {
                wg_wait<0>();
                mbar_arrive_if(sb + B_EMPTY + 8 * ((SP0 - 1) % NST), lead);
#pragma unroll
                for (int s = SP0; s < 32; s++) WAITFULL(s);
                mbar_wait(sb + B_GATE, 0);
                GATES();
                mbar_wait(sb + B_S1, 0);
                wg_fence();
#pragma unroll
                for (int s = SP0; s < 32; s++) {
                    MMA_A(s, 0); MMA_A(s, 1);
                    if (s > SP0) {
                        wg_commit();
                        wg_wait<1>();
                        mbar_arrive_n_if<2>(sb + B_EMPTY + 8 * ((s - 1) % NST), lead);
                        if (s == 31) mbar_arrive_if(sb + B_S3, lead);
                        if (s == 30) WAITD(0);
                        wg_fence();
                    }
                    MMA_A(s, 2); MMA_A(s, 3);
                    wg_commit();
                }
                wg_wait<0>();
                mbar_arrive_n_if<2>(sb + B_EMPTY + 8 * (31 % NST), lead);
            }
            fence_regs<0, 64>(acc);
            uint4 f[8];
#define TAG(v, c) (((v) & ~tagm[c]) | (par & tagm[c]))
#define PACK(k) f[k] = make_uint4(TAG(pack_bf16(acc[8 * (k)], acc[8 * (k) + 1]), 0), TAG(pack_bf16(acc[8 * (k) + 2], acc[8 * (k) + 3]), 2), \
                                  TAG(pack_bf16(acc[8 * (k) + 4], acc[8 * (k) + 5]), 1), TAG(pack_bf16(acc[8 * (k) + 6], acc[8 * (k) + 7]), 3))
#define SEND(k) do { st_relaxed(fout + 512 * (k), f[k].x); st_relaxed(fout + 512 * (k) + 32, f[k].z);                        \
                     st_relaxed(fout + 512 * (k) + 64, f[k].y); st_relaxed(fout + 512 * (k) + 96, f[k].w); } while (0)
#define OWN(k) wgmma128rs(acc, f[k], desc_lo(dd0 + d_addr((k) >> 2) / 16 + ((k) & 3) * 2), (k) != 0)
            const uint32_t dfa = sbd + 0x80000 + (early ? comp * 512 : NST * 1024), dfb = sbd + 0x80000 + (early ? (1 - comp) * 512 : NST * 1024 + 512);
#define MMA_F(pos, kk) wgmma128<0>(acc, (uint64_t)(((pos) < 5 ? dfa : dfb) + a_addr(29 + ((pos) - 2) % 3) / 16 + (kk) * 128) | (0x10ull << 32), \
                                   desc_lo(dd0 + d_addr(pos) / 16 + (kk) * 2), 1)
#define WAITF(pos) mbar_wait(vb + 8 * ((pos) - 2), 0)
            const uint32_t vb = sb + B_VAL + (early ? 0 : 48);
            const uint32_t ts = clk();
            if (early) {
                PACK(0); SEND(0); PACK(1); SEND(1); PACK(2); SEND(2); PACK(3); SEND(3);
                until(ts);
                PACK(4); PACK(5); PACK(6); PACK(7);
                const float s0 = comp ? -g0 : g0, s1 = comp ? -g1 : g1;
                const uint32_t og0 = pack_bf16(1.f - g0, 1.f - g0), og1 = pack_bf16(1.f - g1, 1.f - g1);
                const int rr = 0x7fff - (int)(lds32(sb + M_KEY) & 0x7fffu) - (tm * 128 + wg * 64 + r0);
#pragma unroll
                for (int k = 4; k < 8; k++) {
                    if (k < ESEND) { until(ts + ET1 + (k - 4) * STP); SEND(k); }
#pragma unroll
                    for (int i = 2 * k - 8; i < 2 * k - 6; i++) {
                        const uint32_t og = (i & 1) ? og1 : og0;
                        w[i] = make_uint4(hmul2_bf16(og, w[i].x), hmul2_bf16(og, w[i].y), hmul2_bf16(og, w[i].z), hmul2_bf16(og, w[i].w));
                        asm volatile("" : "+r"(w[i].x), "+r"(w[i].y), "+r"(w[i].z), "+r"(w[i].w));
                    }
                }
                WAITD(0);
                mbar_wait(sb + B_S3, 0);
                wg_fence();
#pragma unroll
                for (int k = 0; k < 8; k++) {
                    OWN(k);
                    if (k >= 1 && k + ESEND - 1 < 8) { wg_commit(); until(ts + ET1 + (k + ESEND - 5) * STP); SEND(k + ESEND - 1); wg_fence(); }
                }
                wg_commit();
                WAITD(2);
                bool ok = false;
#pragma unroll
                for (int pos = 2; pos < 8; pos++) {
                    if (!ok) {
                        if (pos >= 4) WAITD(pos);
                        WAITF(pos);
                    }
                    wg_fence();
                    MMA_F(pos, 0); MMA_F(pos, 1);
                    if (pos == 6) { wg_commit(); wg_wait<1>(); mbar_arrive_cluster_if(mapa(sb + B_XF, rank ^ 1), lead); wg_fence(); }
                    if (pos == 7) mbar_arrive_if(sb + B_S2, lead);
                    if (pos < 7) ok = mbar_test(vb + 8 * (pos - 1), 0) & (pos < 3 || mbar_test(sb + B_DL + 8 * (pos - 3), 0));
                    MMA_F(pos, 2); MMA_F(pos, 3);
                    wg_commit();
                }
                const uint32_t xd = mapa(sb + a_addr(29) + (tid & 127) * 16, rank ^ 1), xb = mapa(sb + B_X, rank ^ 1);
                if (rr == 0 || rr == 8) {
                    mbar_wait(sb + B_SIDE, 0);
#pragma unroll
                    for (int j = 0; j < 4; j++) {
                        const float4 ua = *(const float4*)(smem + M_RED + j * 128 + q * 32), ub = *(const float4*)(smem + M_RED + j * 128 + q * 32 + 16);
                        uint4 v = rr ? w[2 * j + 1] : w[2 * j];
                        v = make_uint4(pack_bf16(ua.x + bflo(v.x), ua.y + bfhi(v.x)), pack_bf16(ua.z + bflo(v.y), ua.w + bfhi(v.y)),
                                       pack_bf16(ub.x + bflo(v.z), ub.y + bfhi(v.z)), pack_bf16(ub.z + bflo(v.w), ub.w + bfhi(v.w)));
                        if (rr) w[2 * j + 1] = v; else w[2 * j] = v;
                    }
                }
                __syncwarp();
                mbar_wait(sb + B_XF, 0);
                wg_wait<0>();
                fence_regs<0, 64>(acc);
                keep_regs<0, 8>(f);
#pragma unroll
                for (int i = 0; i < 8; i++) {
                    const uint4 z = scale_add((i & 1) ? s1 : s0, acc, 16 * (i >> 1) + 2 * (i & 1), w[i]);
                    st_async16(xd + i * 2048, z.x, z.y, z.z, z.w, xb + 2 * (i & 4));
                    if (i & 1) until(ts);
                }
            } else {
#pragma unroll
                for (int k = 0; k < 4; k++) {
                    PACK(2 * k); PACK(2 * k + 1);
                    if (k < LPRE) { until(ts + LT0 + k * LTP); SEND(k); }
                }
                wg_fence();
#pragma unroll
                for (int k = 0; k < 8; k++) {
                    OWN(k);
                    if ((k & 1) && k / 2 < LSEND) { wg_commit(); until(ts + LT0 + (LPRE + k / 2) * LTP); SEND(LPRE + k / 2); wg_fence(); }
                }
                wg_commit();
#pragma unroll
                for (int k = LPRE + LSEND; k < 8; k++) { until(ts + LT0 + k * LTP); SEND(k); }
                float s0 = comp ? -g0 : g0, s1 = comp ? -g1 : g1;
                uint32_t xs = sb + a_addr(29) + (tid & 127) * 16;
                char* op = pout + ooff;
                asm volatile("" : "+f"(s0), "+f"(s1), "+r"(xs), "+l"(op));
                wg_wait<0>();
                keep_regs<0, 8>(f);
                WAITF(2);
                mbar_wait(sb + B_S2, 0);
                bool there = false, there1 = false, ok = true;
#pragma unroll
                for (int pos = 2; pos < 8; pos++) {
                    if (!ok) WAITF(pos);
                    wg_fence();
                    MMA_F(pos, 0);
                    if (pos == XPOS) there = mbar_test(sb + B_X, 0);
                    MMA_F(pos, 1);
                    if (pos == XPOS) {
#pragma unroll
                        for (int i = 0; i < 4; i++) lds128_if(w[i], xs + i * 2048, there);
                    }
                    if (pos < 7) ok = mbar_test(vb + 8 * (pos - 1), 0);
                    MMA_F(pos, 2); MMA_F(pos, 3);
                    wg_commit();
                }
                if (!there) {
                    mbar_wait(sb + B_X, 0);
#pragma unroll
                    for (int i = 0; i < 4; i++) w[i] = lds128(xs + i * 2048);
                }
                there1 = mbar_test(sb + B_X + 8, 0);
                float z[32];
#pragma unroll
                for (int i = 0; i < 4; i++) {
                    z[8 * i] = bflo(w[i].x); z[8 * i + 1] = bfhi(w[i].x); z[8 * i + 2] = bflo(w[i].y); z[8 * i + 3] = bfhi(w[i].y);
                    z[8 * i + 4] = bflo(w[i].z); z[8 * i + 5] = bfhi(w[i].z); z[8 * i + 6] = bflo(w[i].w); z[8 * i + 7] = bfhi(w[i].w);
                }
                fence_regs<0, 32>(z);
#pragma unroll 1
                for (int n = there1; n > 0; n--) {
#pragma unroll
                    for (int i = 4; i < 8; i++) w[i] = lds128(xs + i * 2048);
                }
                wg_wait<0>();
                fence_regs<0, 64>(acc);
#pragma unroll
                for (int i = 0; i < 8; i++) {
                    const int o = 16 * (i >> 1) + 2 * (i & 1);
                    const float s = (i & 1) ? s1 : s0;
                    if (i == XW && !there1) {
                        mbar_wait(sb + B_X + 8, 0);
#pragma unroll
                        for (int k = 4; k < 8; k++) w[k] = lds128(xs + k * 2048);
                    }
                    stg_off<0>(op + (i & 1) * 8192 + (i >> 1) * 64,
                               i >= 4 ? scale_add(s, acc, o, w[i])
                                      : make_uint4(pack_bf16(fmaf(s, acc[o], z[8 * (i & 3)]), fmaf(s, acc[o + 1], z[8 * (i & 3) + 1])),
                                                   pack_bf16(fmaf(s, acc[o + 4], z[8 * (i & 3) + 2]), fmaf(s, acc[o + 5], z[8 * (i & 3) + 3])),
                                                   pack_bf16(fmaf(s, acc[o + 8], z[8 * (i & 3) + 4]), fmaf(s, acc[o + 9], z[8 * (i & 3) + 5])),
                                                   pack_bf16(fmaf(s, acc[o + 12], z[8 * (i & 3) + 6]), fmaf(s, acc[o + 13], z[8 * (i & 3) + 7]))));
                    __syncwarp();
                }
            }
        }
    } else {
        if (wu >= 14) {
            const uint32_t b = blockIdx.x;
            const char* q = wu == 14 ? pcr + (uint32_t)((b >> 1) * 32 + lane) * (S_ * 2) + 128 : px + (uint32_t)(b * 4 + lane) * 128 + 65536;
            until(tstart + P_1);
            if (b < 128 && (wu == 14 || lane < 4)) prefetch_l2(q);
        } else if (wu == 13 && !spare) {
            if (lane == 0) ARM(1);
            __syncwarp();
            until(tstart + T_1);
            STEP0(1);
        }
        if (lane == 0) ARM(wu - 10);
        asm volatile("fence.mbarrier_init.release.cluster;" ::: "memory");
        __syncwarp();
        asm volatile("barrier.cluster.arrive.relaxed.aligned;" ::: "memory");
        if (spare) return;
        asm volatile("setmaxnreg.dec.sync.aligned.u32 " STR(RU) ";");
        if (wu < 14) {
            until(tstart + T_2 + (wu - 12) * PACE);
            STEP0(wu - 10);
        }
        asm volatile("barrier.cluster.wait.acquire.aligned;" ::: "memory");
        if (wu == 13) {
            const CUtensorMap* mD = comp ? &p.mDim : &p.mDre;
#pragma unroll
            for (int step = 4; step < NST; step++) {
                until(tstart + T_2 + (step - 2) * PACE);
                tma3d_elect(sb + b_addr(step), &p.mX2, step * 64, tn * 2, sb + B_FULL + 8 * step);
            }
#pragma unroll 1
            for (int step = NST, slot = 0, ph = 0; step < 32; step++) {
                mbar_wait(sb + B_EMPTY + 8 * slot, ph);
                mbar_wait(sb + B_EMPR + 8 * slot, ph);
                tma2d_pair_elect(sb + b_addr(0) + slot * 16384 + rank * 8192, &p.mX, tn * 128 + rank * 64, step * 64, sb + B_FULL + 8 * slot);
                if (++slot == NST) { slot = 0; ph ^= 1; }
            }
#pragma unroll
            for (int c = 0; c < 4; c += 2) {
                const uint32_t bar = sb + (c ? B_D6 : B_FULL + 8 * (32 % NST));
                if (c) mbar_wait(sb + B_R6, 0);
                else mbar_wait(sb + B_EMPTY + 8 * (26 % NST), (26 / NST) & 1);
                tma5d_elect(sb + d_addr(c), mD, dcol(c, tn), tn * 4, bar);
                tma5d_elect(sb + d_addr(c + 1), mD, dcol(c + 1, tn), tn * 4, bar);
                mbar_expect_tx_elect(bar, 32768);
            }
#pragma unroll
            for (int c = 0; c < 4; c++) mbar_expect_tx_elect(sb + B_DL + 8 * c, 16384);
            mbar_wait(sb + B_S1, 0);
            const uint32_t tq = clk();
#pragma unroll
            for (int c = 0; c < 4; c++) {
                if (!(c & 1)) mbar_wait(sb + B_EMPTY + 8 * ((27 + c / 2) % NST), ((27 + c / 2) / NST) & 1);
                if (c) until(tq + (c == 1 ? T_D5 : c == 2 ? T_D6 : T_D7));
                tma5d_elect(sb + d_addr(4 + c), mD, dcol(4 + c, tn), tn * 4, sb + B_DL + 8 * c);
            }
        } else {
            if (wu == 12) {
#pragma unroll
                for (int step = 4; step < NST; step++) {
                    until(tstart + T_2 + (step - 2) * PACE);
                    tma2d_elect(sb + a_addr(step), mC, step * 64, tm * 128, sb + B_FULL + 8 * step);
                }
#pragma unroll 1
                for (int step = NST, slot = 0, ph = 0; step < 32; step++) {
                    mbar_wait(sb + B_EMPTY + 8 * slot, ph);
                    tma2d_elect(sb + slot * 16384, mC, step * 64, tm * 128, sb + B_FULL + 8 * slot);
                    mbar_expect_tx_elect(sb + B_FULL + 8 * slot, 32768);
                    if (++slot == NST) { slot = 0; ph ^= 1; }
                }
            } else if (wu == 14) {
                if (lane == 0) {
                    asm volatile("prefetch.tensormap [%0];" ::"l"(&p.mX) : "memory");
                    asm volatile("prefetch.tensormap [%0];" ::"l"(&p.mF) : "memory");
                    asm volatile("prefetch.tensormap [%0];" ::"l"(comp ? &p.mDim : &p.mDre) : "memory");
                    asm volatile("st.shared::cluster.u32 [%0], %1;" ::"r"(mapa(sb + M_ROLE, rank ^ 1)), "r"(role) : "memory");
                }
                nap_until(tstart + KEY_T0 - 1000);
                const uint32_t epoch = ld_relaxed(g->epoch + cta) + 1u, par = epoch & 1u;
                if (lane < 8) stg_off<0>(g->stamp + cta * 32 + lane * 4, make_uint4(par ^ 1u, 0, 0, 0));
                nap_until(tstart + KEY_T0);
                const uint32_t k = best_key(g->keys + ((tm + (tm >> 3)) & 7) * NCTA, par);
                const uint4 xr = ldg_nc_off<0>(px + (0x7fff - (k & 0x7fffu)) * (D_ * 2) + rank * 512 + lane * 16);
                const uint4 g4 = wait_tags(g->gate + tm * 128 + lane * 4, par);
                sts128(sb + M_G + lane * 16, make_uint4(g4.x & ~1u, g4.y & ~1u, g4.z & ~1u, g4.w & ~1u));
                sts128(sb + M_UPD + lane * 16, xr);
                if (lane == 0) {
                    *(volatile uint32_t*)(smem + M_KEY) = k;
                    *(volatile uint32_t*)(smem + M_PAR) = par;
                    st_relaxed(g->epoch + cta, epoch);
                }
                mbar_arrive_warp(sb + B_GATE);
            } else {
                const int fr = ffn_pair(role);
                const uint32_t t1 = tstart + FFN_T0 + (rank + ((fr >> 2) & 6)) * (FFN_DT / 8);
                if (!((NOFFN_MASK >> role) & 1)) {
#pragma unroll 1
                    for (int i = 0; i < 12; i++) {
                        const int qu = i < 4 ? 2 + (i >> 1) : (i - 4) >> 1;
                        const uint32_t bar = sb + B_FFN + 8 * (i < 4 ? 3 : qu), dst = sb + R6 + (i & 1) * 16384 + qu * 4096;
                        if (i == 8) mbar_wait(sb + B_VD, 0);
                        if (i == 0 || (i >= 4 && !(i & 1))) mbar_expect_tx_elect(bar, i ? 8192 : 16384);
                        nap_until(t1 + i * FFN_DT);
                        tma2d_elect(dst, i < 4 ? &p.mWd : (i & 1) ? &p.mWu : &p.mWg, i < 4 ? rank * 256 : fr * 32, i < 4 ? fr * 32 + i * 8 : rank * 256 + qu * 64, bar);
                    }
                }
            }
            __syncwarp();
            mbar_wait(sb + B_GATE, 0);
            fetch_job<0>(p, g, smem, sb, cta, wu == 12 ? 2 : wu - 14, lds32(sb + M_PAR));
        }
    }
}

typedef CUresult (*EncodeTiledFn)(CUtensorMap*, CUtensorMapDataType, cuuint32_t, void*, const cuuint64_t*, const cuuint64_t*,
                                  const cuuint32_t*, const cuuint32_t*, CUtensorMapInterleave, CUtensorMapSwizzle,
                                  CUtensorMapL2promotion, CUtensorMapFloatOOBfill);

static void make_map(EncodeTiledFn enc, CUtensorMap* m, const void* base, uint64_t cols, uint64_t rows, uint32_t box_rows,
                     CUtensorMapSwizzle sw = CU_TENSOR_MAP_SWIZZLE_128B, uint32_t box_cols = 64) {
    cuuint64_t dims[2] = {cols, rows};
    cuuint64_t str[1] = {cols * 2};
    cuuint32_t box[2] = {box_cols, box_rows};
    cuuint32_t es[2] = {1, 1};
    enc(m, CU_TENSOR_MAP_DATA_TYPE_BFLOAT16, 2, (void*)base, dims, str, box, es, CU_TENSOR_MAP_INTERLEAVE_NONE,
        sw, CU_TENSOR_MAP_L2_PROMOTION_L2_128B, CU_TENSOR_MAP_FLOAT_OOB_FILL_NONE);
}

static void make_map_chunks(EncodeTiledFn enc, CUtensorMap* m, const void* base, uint64_t rows) {
    cuuint64_t dims[3] = {64, rows, D_ / 64};
    cuuint64_t str[2] = {D_ * 2, 128};
    cuuint32_t box[3] = {64, 64, 2};
    cuuint32_t es[3] = {1, 1, 1};
    enc(m, CU_TENSOR_MAP_DATA_TYPE_BFLOAT16, 3, (void*)base, dims, str, box, es, CU_TENSOR_MAP_INTERLEAVE_NONE,
        CU_TENSOR_MAP_SWIZZLE_128B, CU_TENSOR_MAP_L2_PROMOTION_L2_128B, CU_TENSOR_MAP_FLOAT_OOB_FILL_NONE);
}

static void make_map_perm(EncodeTiledFn enc, CUtensorMap* m, const void* base) {
    cuuint64_t dims[5] = {D_, 2, 4, 4, D_ / 32};
    cuuint64_t str[4] = {D_ * 2, 8 * D_ * 2, 2 * D_ * 2, 32 * D_ * 2};
    cuuint32_t box[5] = {64, 2, 4, 4, 4};
    cuuint32_t es[5] = {1, 1, 1, 1, 1};
    enc(m, CU_TENSOR_MAP_DATA_TYPE_BFLOAT16, 5, (void*)base, dims, str, box, es, CU_TENSOR_MAP_INTERLEAVE_NONE,
        CU_TENSOR_MAP_SWIZZLE_128B, CU_TENSOR_MAP_L2_PROMOTION_L2_128B, CU_TENSOR_MAP_FLOAT_OOB_FILL_NONE);
}

extern "C" void kernel_launch(void* const* d_in, const int* in_sizes, int n_in, void* d_out, int out_size) {
    (void)in_sizes; (void)n_in; (void)out_size;
    static EncodeTiledFn enc = nullptr;
    static bool fused_ok = false;
    static void* scr = nullptr;
    if (!enc) {
        void* fn = nullptr;
        cudaDriverEntryPointQueryResult q;
        cudaGetDriverEntryPoint("cuTensorMapEncodeTiled", &fn, cudaEnableDefault, &q);
        enc = (EncodeTiledFn)fn;
        cudaGetSymbolAddress(&scr, g_scr);
        cudaFuncSetAttribute(fused_kernel, cudaFuncAttributeMaxDynamicSharedMemorySize, SMEM_BYTES);
        int dev = 0, nsm = 0, ncl = 0;
        cudaGetDevice(&dev);
        cudaDeviceGetAttribute(&nsm, cudaDevAttrMultiProcessorCount, dev);
        cudaLaunchConfig_t cfg = {};
        cfg.gridDim = dim3(132); cfg.blockDim = dim3(NTHREADS); cfg.dynamicSmemBytes = SMEM_BYTES;
        cudaLaunchAttribute at;
        at.id = cudaLaunchAttributeClusterDimension;
        at.val.clusterDim.x = 2; at.val.clusterDim.y = 1; at.val.clusterDim.z = 1;
        cfg.attrs = &at; cfg.numAttrs = 1;
        fused_ok = cudaOccupancyMaxActiveClusters(&ncl, fused_kernel, &cfg) == cudaSuccess && nsm == 132 && ncl == 66;
        (void)cudaGetLastError();
    }
    if (!fused_ok) {
        const bf16* const* in = (const bf16* const*)d_in;
        fb_hidden<<<S_, D_, 0, cudaStreamPerThread>>>(in[0], in[3], in[4], in[10], in[6]);
        fb_ffn1<<<F_ / 128, 128, 0, cudaStreamPerThread>>>(in[0], in[7], in[8]);
        fb_ffn2<<<D_ / 64, 64, 0, cudaStreamPerThread>>>(in[9]);
        fb_seq<<<S_, D_, 0, cudaStreamPerThread>>>(in[0], in[1], in[2], (bf16*)d_out);
        return;
    }
    Params p;
    p.dre = (const bf16*)d_in[3];
    p.dim = (const bf16*)d_in[4];
    p.w_r = (const bf16*)d_in[6];
    p.gate_w = (const bf16*)d_in[10];
    make_map_chunks(enc, &p.mX2, d_in[0], S_);
    make_map(enc, &p.mX, d_in[0], D_, S_, 64);
    make_map(enc, &p.mCre, d_in[1], S_, S_, 128);
    make_map(enc, &p.mCim, d_in[2], S_, S_, 128);
    make_map_perm(enc, &p.mDre, d_in[3]);
    make_map_perm(enc, &p.mDim, d_in[4]);
    make_map(enc, &p.mF, scr, 64, NCTA * 256, 64, CU_TENSOR_MAP_SWIZZLE_NONE);
    make_map(enc, &p.mWg, d_in[7], F_, D_, 64, CU_TENSOR_MAP_SWIZZLE_NONE, 32);
    make_map(enc, &p.mWu, d_in[8], F_, D_, 64, CU_TENSOR_MAP_SWIZZLE_NONE, 32);
    make_map(enc, &p.mWd, d_in[9], D_, F_, 8, CU_TENSOR_MAP_SWIZZLE_NONE, 256);
    fused_kernel<<<132, NTHREADS, SMEM_BYTES, cudaStreamPerThread>>>(CPtr{{(const char*)d_in[1], (const char*)d_in[2]}}, (const char*)d_in[0], (char*)d_out, (Scratch*)scr, p);
}
```

```cpp
#include <cuda_runtime.h>
#include <cuda.h>
#include <cuda_bf16.h>
#include <stdint.h>

typedef __nv_bfloat16 bf16;

constexpr int S_ = 2048, D_ = 512, F_ = 1792;
constexpr int NCTA = 128;
constexpr int NTHREADS = 512;
constexpr int NST = 6;
constexpr int SP0 = 27;
constexpr int FFN_CTAS = F_ / 16;
constexpr uint32_t SPIN_LIMIT = 1u << 16;

#define P_1 450
#define T_1 500
#define T_2 1050
#define PACE 420
#define SIDE_T0 2800
#define ROUTER_T0 3000
#define ROUTER_DT 280
#define KEY_T0 9800
#define FFN_T0 5200
#define FFN_DT 640
#define XLD 14
#define XN 8
#define XD 1
#define PFD_T0 11900
#define PFD_DT 250
#define SUM_T0 15500
#define ET1 600
#define STP 170
#define ESEND 6
#define LT0 200
#define LTP 170
#define LPRE 2
#define LSEND 3
#define SDEL 280
#define E_RD0 1350
#define E_RD1 2180
#define L_RD0 3200
#define L_RD1 3880
#define SG 130
#define T_D5 1500
#define T_D6 1700
#define T_D7 2400
#define XPOS 7
#define XW 4
#define RC 168
#define RS_ 112
#define RU 64
#define NOFFN_MASK 0xf00c880000000000ull
#define STR2(x) #x
#define STR(x) STR2(x)

__host__ __device__ constexpr int a_addr(int s) { return s % NST * 16384; }
__host__ __device__ constexpr int b_addr(int s) { return (NST + s % NST) * 16384; }
constexpr int R6 = 2 * NST * 16384;
__host__ __device__ constexpr int d_addr(int p) { return p / 2 == 1 ? R6 + (p & 1) * 16384 : (p & 1) ? b_addr(26 + p / 3) : a_addr(26 + p / 3); }
static_assert(d_addr(0) == a_addr(26) && d_addr(4) == a_addr(27) && d_addr(6) == a_addr(28), "");
constexpr int OFF_MISC = R6 + 32768;
constexpr int B_FULL = OFF_MISC;
constexpr int B_EMPTY = B_FULL + 48;
constexpr int B_EMPR = B_EMPTY + 48;
constexpr int B_VD = B_EMPR + 48;
constexpr int B_X = B_VD + 8;
constexpr int B_HX = B_X + 16;
constexpr int B_XF = B_HX + 8;
constexpr int B_S0 = B_XF + 8;
constexpr int B_S1 = B_S0 + 8;
constexpr int B_EA = B_S1 + 8;
constexpr int B_S2 = B_EA + 8;
constexpr int B_S3 = B_S2 + 8;
constexpr int B_D6 = B_S3 + 8;
constexpr int B_DL = B_D6 + 8;
constexpr int B_GATE = B_DL + 32;
constexpr int B_SIDE = B_GATE + 8;
constexpr int B_FFN = B_SIDE + 8;
constexpr int B_R6 = B_FFN + 32;
constexpr int B_LAND = B_R6 + 8;
constexpr int B_VAL = B_LAND + 48;
constexpr int B_TH = B_VAL + 96;
constexpr int M_TH = B_TH + 24;
constexpr int NBAR = (M_TH - B_EMPTY) / 8;
constexpr int M_KEY = M_TH + 12;
constexpr int M_PAR = M_KEY + 4;
constexpr int M_ROLE = M_PAR + 4;
constexpr int M_HX = OFF_MISC + 544;
constexpr int M_G = M_HX + 256;
constexpr int M_UPD = M_G + 512;
constexpr int M_RED = M_UPD + 512;
constexpr int SMEM_BYTES = 232448;
static_assert(M_RED + 512 <= SMEM_BYTES && M_ROLE + 4 <= M_HX, "smem");

struct Params {
    const bf16 *gate_w, *w_r, *dre, *dim;
    CUtensorMap mCre, mCim, mX2, mX, mDre, mDim, mF, mWg, mWu, mWd;
};

struct CPtr { const char* c[2]; };

struct Scratch {
    uint32_t frag[NCTA * 2 * 4096];
    uint32_t stamp[NCTA * 32];
    uint32_t gate[S_];
    uint32_t keys[8 * NCTA];
    uint32_t part[FFN_CTAS / 2 * D_];
    uint32_t phint[4 * 8 * 8];
    uint32_t upd[D_];
    uint32_t epoch[NCTA + 4];
};
__device__ __align__(1024) Scratch g_scr;

__device__ __forceinline__ uint32_t smem_u32(const void* p) { return (uint32_t)__cvta_generic_to_shared(p); }
__device__ __forceinline__ void mbar_init(uint32_t bar, uint32_t cnt) {
    asm volatile("mbarrier.init.shared::cta.b64 [%0], %1;" ::"r"(bar), "r"(cnt) : "memory");
}
__device__ __forceinline__ void mbar_expect_tx(uint32_t bar, uint32_t bytes) {
    asm volatile("mbarrier.arrive.expect_tx.shared::cta.b64 _, [%0], %1;" ::"r"(bar), "r"(bytes) : "memory");
}
__device__ __forceinline__ void mbar_arrive(uint32_t bar) {
    asm volatile("mbarrier.arrive.shared::cta.b64 _, [%0];" ::"r"(bar) : "memory");
}
template <int N>
__device__ __forceinline__ void mbar_arrive_n_if(uint32_t bar, bool pred) {
    asm volatile("{.reg .pred p; setp.ne.b32 p, %1, 0; @p mbarrier.arrive.shared::cta.b64 _, [%0], %2;}" ::"r"(bar), "r"((int)pred), "n"(N) : "memory");
}
__device__ __forceinline__ void mbar_arrive_if(uint32_t bar, bool pred) {
    asm volatile("{.reg .pred p; setp.ne.b32 p, %1, 0; @p mbarrier.arrive.shared::cta.b64 _, [%0];}" ::"r"(bar), "r"((int)pred) : "memory");
}
__device__ __forceinline__ void mbar_arrive_warp(uint32_t bar) {
    __syncwarp();
    mbar_arrive_if(bar, (threadIdx.x & 31) == 0);
}
__device__ __forceinline__ void mbar_arrive_cluster_if(uint32_t bar, bool pred) {
    asm volatile("{.reg .pred p; setp.ne.b32 p, %1, 0; @p mbarrier.arrive.shared::cluster.b64 _, [%0], 1;}"
                 ::"r"(bar), "r"((int)pred) : "memory");
}
__device__ __forceinline__ uint32_t mapa(uint32_t a, uint32_t cta) {
    uint32_t r;
    asm volatile("mapa.shared::cluster.u32 %0, %1, %2;" : "=r"(r) : "r"(a), "r"(cta));
    return r;
}
__device__ __forceinline__ bool mbar_try(uint32_t bar, uint32_t parity) {
    uint32_t ok;
    asm volatile("{.reg .pred p; mbarrier.try_wait.parity.shared::cta.b64 p, [%1], %2; selp.u32 %0,1,0,p;}"
                 : "=r"(ok) : "r"(bar), "r"(parity) : "memory");
    return ok;
}
__device__ __forceinline__ bool mbar_test(uint32_t bar, uint32_t parity) {
    uint32_t ok;
    asm volatile("{.reg .pred p; mbarrier.test_wait.parity.shared::cta.b64 p, [%1], %2; selp.u32 %0,1,0,p;}"
                 : "=r"(ok) : "r"(bar), "r"(parity) : "memory");
    return ok;
}
__device__ __forceinline__ void mbar_wait(uint32_t bar, uint32_t parity) {
    uint32_t n = 0;
#pragma unroll 1
    while (!mbar_try(bar, parity)) { if (++n > SPIN_LIMIT) break; }
}
__device__ __forceinline__ void tma2d_elect(uint32_t dst, const CUtensorMap* m, int c0, int c1, uint32_t bar) {
    asm volatile("{.reg .pred p; elect.sync _|p, 0xffffffff;"
                 " @p cp.async.bulk.tensor.2d.shared::cluster.global.mbarrier::complete_tx::bytes [%0], [%1, {%3,%4}], [%2];}"
                 ::"r"(dst), "l"(m), "r"(bar), "r"(c0), "r"(c1) : "memory");
}
__device__ __forceinline__ void tma2d_pair_elect(uint32_t dst, const CUtensorMap* m, int c0, int c1, uint32_t bar) {
    asm volatile("{.reg .pred p; elect.sync _|p, 0xffffffff;"
                 " @p cp.async.bulk.tensor.2d.shared::cluster.global.mbarrier::complete_tx::bytes.multicast::cluster"
                 " [%0], [%1, {%3,%4}], [%2], %5;}" ::"r"(dst), "l"(m), "r"(bar), "r"(c0), "r"(c1), "h"((uint16_t)3) : "memory");
}
__device__ __forceinline__ void tma3d_elect(uint32_t dst, const CUtensorMap* m, int row, int chunk, uint32_t bar) {
    asm volatile("{.reg .pred p; elect.sync _|p, 0xffffffff;"
                 " @p cp.async.bulk.tensor.3d.shared::cluster.global.mbarrier::complete_tx::bytes [%0], [%1, {%3,%4,%5}], [%2];}"
                 ::"r"(dst), "l"(m), "r"(bar), "r"(0), "r"(row), "r"(chunk) : "memory");
}
__device__ __forceinline__ void tma5d_elect(uint32_t dst, const CUtensorMap* m, int c0, int c4, uint32_t bar) {
    asm volatile("{.reg .pred p; elect.sync _|p, 0xffffffff;"
                 " @p cp.async.bulk.tensor.5d.shared::cluster.global.mbarrier::complete_tx::bytes [%0], [%1, {%3,%5,%5,%5,%4}], [%2];}"
                 ::"r"(dst), "l"(m), "r"(bar), "r"(c0), "r"(c4), "r"(0) : "memory");
}
__device__ __forceinline__ void mbar_expect_tx_elect(uint32_t bar, uint32_t bytes) {
    asm volatile("{.reg .pred p; elect.sync _|p, 0xffffffff; @p mbarrier.arrive.expect_tx.shared::cta.b64 _, [%0], %1;}"
                 ::"r"(bar), "r"(bytes) : "memory");
}
__device__ __forceinline__ void prefetch_l2(const void* p) { asm volatile("prefetch.global.L2 [%0];" ::"l"(p)); }
__device__ __forceinline__ uint32_t ld_relaxed(const void* p) {
    uint32_t v;
    asm volatile("ld.relaxed.gpu.global.u32 %0, [%1];" : "=r"(v) : "l"(p) : "memory");
    return v;
}
__device__ __forceinline__ uint4 ld_relaxed4(const void* p) {
    uint4 v;
    asm volatile("ld.relaxed.gpu.global.v4.u32 {%0,%1,%2,%3}, [%4];" : "=r"(v.x), "=r"(v.y), "=r"(v.z), "=r"(v.w) : "l"(p) : "memory");
    return v;
}
__device__ __forceinline__ void st_relaxed(unsigned int* p, uint32_t v) {
    asm volatile("st.relaxed.gpu.global.u32 [%0], %1;" ::"l"(p), "r"(v) : "memory");
}
__device__ __forceinline__ uint32_t tagf(float v, uint32_t par) { return (__float_as_uint(v) & ~1u) | par; }
template <int BIT = 0>
__device__ __forceinline__ uint4 wait_tags(const unsigned int* p, uint32_t par) {
    uint32_t n = 0;
#pragma unroll 1
    while (true) {
        const uint4 v = ld_relaxed4(p);
        const uint32_t m = par ? (v.x & v.y & v.z & v.w) : ~(v.x | v.y | v.z | v.w);
        if (__all_sync(0xffffffffu, (m >> BIT) & 1u)) return v;
        __nanosleep(100);
        if (++n > SPIN_LIMIT) return v;
    }
}
__device__ __forceinline__ uint32_t best_key(const uint32_t* keys, uint32_t par) {
    const uint4 k = wait_tags<15>(keys + (threadIdx.x & 31) * 4, par);
    return __reduce_max_sync(0xffffffffu, max(max(k.x, k.y), max(k.z, k.w)));
}
__device__ __forceinline__ void named_bar(int id, int n) { asm volatile("bar.sync %0, %1;" ::"r"(id), "r"(n) : "memory"); }
template <int OFF>
__device__ __forceinline__ uint4 ldg_nc_off(const void* p) {
    uint4 v;
    asm volatile("ld.global.nc.v4.u32 {%0,%1,%2,%3}, [%4+%5];" : "=r"(v.x), "=r"(v.y), "=r"(v.z), "=r"(v.w) : "l"(p), "n"(OFF));
    return v;
}
__device__ __forceinline__ void ldg_nc_if(uint4& v, const void* a, bool pred) {
    asm volatile("{.reg .pred p; setp.ne.b32 p, %5, 0; @p ld.global.nc.v4.u32 {%0,%1,%2,%3}, [%4];}"
                 : "+r"(v.x), "+r"(v.y), "+r"(v.z), "+r"(v.w) : "l"(a), "r"((int)pred) : "memory");
}
template <int OFF>
__device__ __forceinline__ void stg_off(void* p, const uint4& v) {
    asm volatile("st.global.v4.u32 [%0+%5], {%1,%2,%3,%4};" ::"l"(p), "r"(v.x), "r"(v.y), "r"(v.z), "r"(v.w), "n"(OFF) : "memory");
}
__device__ __forceinline__ void sts128(uint32_t a, const uint4& v) {
    asm volatile("st.shared.v4.u32 [%0], {%1,%2,%3,%4};" ::"r"(a), "r"(v.x), "r"(v.y), "r"(v.z), "r"(v.w) : "memory");
}
__device__ __forceinline__ uint4 lds128(uint32_t a) {
    uint4 v;
    asm volatile("ld.shared.v4.u32 {%0,%1,%2,%3}, [%4];" : "=r"(v.x), "=r"(v.y), "=r"(v.z), "=r"(v.w) : "r"(a) : "memory");
    return v;
}
__device__ __forceinline__ void lds128_if(uint4& v, uint32_t a, bool pred) {
    asm volatile("{.reg .pred p; setp.ne.b32 p, %5, 0; @p ld.shared.v4.u32 {%0,%1,%2,%3}, [%4];}"
                 : "+r"(v.x), "+r"(v.y), "+r"(v.z), "+r"(v.w) : "r"(a), "r"((int)pred) : "memory");
}
__device__ __forceinline__ uint32_t lds32(uint32_t a) {
    uint32_t v;
    asm volatile("ld.shared.u32 %0, [%1];" : "=r"(v) : "r"(a) : "memory");
    return v;
}
__device__ __forceinline__ void st_async16(uint32_t dst, uint32_t x, uint32_t y, uint32_t z, uint32_t w, uint32_t bar) {
    asm volatile("st.async.weak.shared::cluster.mbarrier::complete_tx::bytes.v4.b32 [%0], {%1,%2,%3,%4}, [%5];"
                 ::"r"(dst), "r"(x), "r"(y), "r"(z), "r"(w), "r"(bar) : "memory");
}
__device__ __forceinline__ int sel(int a, int b, bool p) {
    int r;
    asm("{.reg .pred q; setp.ne.b32 q, %3, 0; selp.b32 %0, %1, %2, q;}" : "=r"(r) : "r"(a), "r"(b), "r"((int)p));
    return r;
}
__device__ __forceinline__ float selpf(float a, float b, bool p) {
    float r;
    asm("{.reg .pred q; setp.ne.b32 q, %3, 0; selp.f32 %0, %1, %2, q;}" : "=f"(r) : "f"(a), "f"(b), "r"((int)p));
    return r;
}
template <int N, int MASK, int SZ>
__device__ __forceinline__ void halve(float (&a)[SZ]) {
    const bool up = threadIdx.x & MASK;
#pragma unroll
    for (int j = 0; j < N; j++) a[j] = selpf(a[N + j], a[j], up) + __shfl_xor_sync(0xffffffffu, selpf(a[j], a[N + j], up), MASK);
}
__device__ __forceinline__ float bflo(uint32_t u) { return __uint_as_float(u << 16); }
__device__ __forceinline__ float bfhi(uint32_t u) { return __uint_as_float(u & 0xffff0000u); }
__device__ __forceinline__ uint32_t pack_bf16(float lo, float hi) {
    uint32_t r;
    asm("cvt.rn.bf16x2.f32 %0, %1, %2;" : "=r"(r) : "f"(hi), "f"(lo));
    return r;
}
__device__ __forceinline__ uint32_t hmul2_bf16(uint32_t a, uint32_t b) {
    uint32_t r;
    asm("mul.rn.bf16x2 %0, %1, %2;" : "=r"(r) : "r"(a), "r"(b));
    return r;
}
__device__ __forceinline__ float sigmoidf_(float v) { return 1.0f / (1.0f + __expf(-v)); }
__device__ __forceinline__ void wg_fence() { asm volatile("wgmma.fence.sync.aligned;" ::: "memory"); }
__device__ __forceinline__ void wg_commit() { asm volatile("wgmma.commit_group.sync.aligned;" ::: "memory"); }
template <int N> __device__ __forceinline__ void wg_wait() { asm volatile("wgmma.wait_group.sync.aligned %0;" ::"n"(N) : "memory"); }
__device__ __forceinline__ uint64_t desc_lo(uint32_t lo) { return (uint64_t)lo | (0x40000040ull << 32); }
template <int LO, int HI, int N>
__device__ __forceinline__ void fence_regs(float (&d)[N]) {
#pragma unroll
    for (int i = LO; i < HI; i++) asm volatile("" : "+f"(d[i])::"memory");
}
template <int LO, int HI, int N>
__device__ __forceinline__ void keep_regs(uint4 (&f)[N]) {
#pragma unroll
    for (int i = LO; i < HI; i++) asm volatile("" ::"r"(f[i].x), "r"(f[i].y), "r"(f[i].z), "r"(f[i].w) : "memory");
}
template <int TB = 1>
__device__ __forceinline__ void wgmma128(float (&d)[64], uint64_t da, uint64_t db, int scaleD) {
    asm volatile(
        "{ .reg .pred p; setp.ne.b32 p, %66, 0;\n"
        "wgmma.mma_async.sync.aligned.m64n128k16.f32.bf16.bf16 "
        "{%0,%1,%2,%3,%4,%5,%6,%7,%8,%9,%10,%11,%12,%13,%14,%15,%16,%17,%18,%19,%20,%21,%22,%23,%24,%25,%26,%27,%28,%29,%30,%31,"
        "%32,%33,%34,%35,%36,%37,%38,%39,%40,%41,%42,%43,%44,%45,%46,%47,%48,%49,%50,%51,%52,%53,%54,%55,%56,%57,%58,%59,%60,%61,%62,%63}, "
        "%64, %65, p, 1, 1, 0, %67;\n}"
        : "+f"(d[0]), "+f"(d[1]), "+f"(d[2]), "+f"(d[3]), "+f"(d[4]), "+f"(d[5]), "+f"(d[6]), "+f"(d[7]),
          "+f"(d[8]), "+f"(d[9]), "+f"(d[10]), "+f"(d[11]), "+f"(d[12]), "+f"(d[13]), "+f"(d[14]), "+f"(d[15]),
          "+f"(d[16]), "+f"(d[17]), "+f"(d[18]), "+f"(d[19]), "+f"(d[20]), "+f"(d[21]), "+f"(d[22]), "+f"(d[23]),
          "+f"(d[24]), "+f"(d[25]), "+f"(d[26]), "+f"(d[27]), "+f"(d[28]), "+f"(d[29]), "+f"(d[30]), "+f"(d[31]),
          "+f"(d[32]), "+f"(d[33]), "+f"(d[34]), "+f"(d[35]), "+f"(d[36]), "+f"(d[37]), "+f"(d[38]), "+f"(d[39]),
          "+f"(d[40]), "+f"(d[41]), "+f"(d[42]), "+f"(d[43]), "+f"(d[44]), "+f"(d[45]), "+f"(d[46]), "+f"(d[47]),
          "+f"(d[48]), "+f"(d[49]), "+f"(d[50]), "+f"(d[51]), "+f"(d[52]), "+f"(d[53]), "+f"(d[54]), "+f"(d[55]),
          "+f"(d[56]), "+f"(d[57]), "+f"(d[58]), "+f"(d[59]), "+f"(d[60]), "+f"(d[61]), "+f"(d[62]), "+f"(d[63])
        : "l"(da), "l"(db), "r"(scaleD), "n"(TB));
}
__device__ __forceinline__ void wgmma128rs(float (&d)[64], const uint4& a, uint64_t db, int scaleD) {
    asm volatile(
        "{ .reg .pred p; setp.ne.b32 p, %69, 0;\n"
        "wgmma.mma_async.sync.aligned.m64n128k16.f32.bf16.bf16 "
        "{%0,%1,%2,%3,%4,%5,%6,%7,%8,%9,%10,%11,%12,%13,%14,%15,%16,%17,%18,%19,%20,%21,%22,%23,%24,%25,%26,%27,%28,%29,%30,%31,"
        "%32,%33,%34,%35,%36,%37,%38,%39,%40,%41,%42,%43,%44,%45,%46,%47,%48,%49,%50,%51,%52,%53,%54,%55,%56,%57,%58,%59,%60,%61,%62,%63}, "
        "{%64,%65,%66,%67}, %68, p, 1, 1, 0;\n}"
        : "+f"(d[0]), "+f"(d[1]), "+f"(d[2]), "+f"(d[3]), "+f"(d[4]), "+f"(d[5]), "+f"(d[6]), "+f"(d[7]),
          "+f"(d[8]), "+f"(d[9]), "+f"(d[10]), "+f"(d[11]), "+f"(d[12]), "+f"(d[13]), "+f"(d[14]), "+f"(d[15]),
          "+f"(d[16]), "+f"(d[17]), "+f"(d[18]), "+f"(d[19]), "+f"(d[20]), "+f"(d[21]), "+f"(d[22]), "+f"(d[23]),
          "+f"(d[24]), "+f"(d[25]), "+f"(d[26]), "+f"(d[27]), "+f"(d[28]), "+f"(d[29]), "+f"(d[30]), "+f"(d[31]),
          "+f"(d[32]), "+f"(d[33]), "+f"(d[34]), "+f"(d[35]), "+f"(d[36]), "+f"(d[37]), "+f"(d[38]), "+f"(d[39]),
          "+f"(d[40]), "+f"(d[41]), "+f"(d[42]), "+f"(d[43]), "+f"(d[44]), "+f"(d[45]), "+f"(d[46]), "+f"(d[47]),
          "+f"(d[48]), "+f"(d[49]), "+f"(d[50]), "+f"(d[51]), "+f"(d[52]), "+f"(d[53]), "+f"(d[54]), "+f"(d[55]),
          "+f"(d[56]), "+f"(d[57]), "+f"(d[58]), "+f"(d[59]), "+f"(d[60]), "+f"(d[61]), "+f"(d[62]), "+f"(d[63])
        : "r"(a.x), "r"(a.y), "r"(a.z), "r"(a.w), "l"(db), "r"(scaleD));
}
__device__ __forceinline__ uint32_t clk() { uint64_t c; asm volatile("mov.u64 %0, %%clock64;" : "=l"(c)::"memory"); return (uint32_t)c; }
__device__ __forceinline__ uint32_t gtime() { uint64_t t; asm volatile("mov.u64 %0, %%globaltimer;" : "=l"(t)::"memory"); return (uint32_t)t; }
__device__ __forceinline__ void until(uint32_t t) { while (t - clk() < 0x8000u) {} }
__device__ __forceinline__ void nap_until(uint32_t t) { while (t - clk() < 0x8000u) __nanosleep(20); }
__device__ __forceinline__ uint4 scale_add(float s, const float (&a)[64], int o, const uint4& w) {
    return make_uint4(pack_bf16(fmaf(s, a[o], bflo(w.x)), fmaf(s, a[o + 1], bfhi(w.x))), pack_bf16(fmaf(s, a[o + 4], bflo(w.y)), fmaf(s, a[o + 5], bfhi(w.y))),
                      pack_bf16(fmaf(s, a[o + 8], bflo(w.z)), fmaf(s, a[o + 9], bfhi(w.z))), pack_bf16(fmaf(s, a[o + 12], bflo(w.w)), fmaf(s, a[o + 13], bfhi(w.w))));
}

__device__ __forceinline__ uint32_t router_key(float score, int row) {
    const float r = score + 0.0f;
    uint32_t u = pack_bf16(r, 0.f) & 0xffffu;
    u = (u & 0x8000u) ? (~u & 0xffffu) : (u | 0x8000u);
    if (r != r) u = 0;
    return (u << 16) | (uint32_t)(0x7fff - row);
}

#define g_ab g_scr.frag
#define g_fb_h ((float*)g_scr.part)
#define g_fb_upd (g_fb_h + 2048)
#define g_fb_gate (g_fb_h + 4096)
#define g_fb_keys (g_scr.part + 8192)
__global__ void fb_hidden(const bf16* x, const bf16* dre, const bf16* dim, const bf16* gw, const bf16* wr) {
    __shared__ float xs[D_];
    const int s = blockIdx.x, t = threadIdx.x;
    xs[t] = __bfloat162float(x[s * D_ + t]);
    __syncthreads();
    float a = 0.f, b = 0.f;
    for (int d = 0; d < D_; d++) { a = fmaf(xs[d], __bfloat162float(dre[t * D_ + d]), a); b = fmaf(xs[d], __bfloat162float(dim[t * D_ + d]), b); }
    ((bf16*)g_ab)[s * 1024 + t] = __float2bfloat16(a);
    ((bf16*)g_ab)[s * 1024 + 512 + t] = __float2bfloat16(b);
    if (t == 0) {
        float u = 0.f, v = 0.f;
        for (int d = 0; d < D_; d++) { u += bfhi(pack_bf16(0.f, xs[d] * __bfloat162float(gw[d]))); v = fmaf(xs[d], __bfloat162float(wr[d]), v); }
        g_fb_gate[s] = bfhi(pack_bf16(0.f, sigmoidf_(bfhi(pack_bf16(0.f, u)))));
        g_fb_keys[s] = router_key(v, s);
    }
}
__device__ uint32_t fb_best() {
    uint32_t k = 0;
    for (int i = 0; i < S_; i++) k = max(k, g_fb_keys[i]);
    return k;
}
__global__ void fb_ffn1(const bf16* x, const bf16* wg, const bf16* wu) {
    const int f = blockIdx.x * blockDim.x + threadIdx.x, idx = 0x7fff - (int)(fb_best() & 0x7fffu);
    float a = 0.f, b = 0.f;
    for (int d = 0; d < D_; d++) {
        const float xv = __bfloat162float(x[idx * D_ + d]);
        a = fmaf(xv, __bfloat162float(wg[d * F_ + f]), a); b = fmaf(xv, __bfloat162float(wu[d * F_ + f]), b);
    }
    g_fb_h[f] = a * sigmoidf_(a) * b;
}
__global__ void fb_ffn2(const bf16* wd) {
    const int e = blockIdx.x * blockDim.x + threadIdx.x;
    const uint32_t u = fb_best() >> 16, rb = (u & 0x8000u) ? (u & 0x7fffu) : (~u & 0xffffu);
    float a = 0.f;
    for (int f = 0; f < F_; f++) a = fmaf(g_fb_h[f], __bfloat162float(wd[f * D_ + e]), a);
    g_fb_upd[e] = a * sigmoidf_(__uint_as_float(rb << 16));
}
__global__ void fb_seq(const bf16* x, const bf16* cre, const bf16* cim, bf16* out) {
    __shared__ float c[2][S_];
    __shared__ int idx;
    const int t = blockIdx.x, e = threadIdx.x;
    for (int i = e; i < S_; i += D_) { c[0][i] = __bfloat162float(cre[t * S_ + i]); c[1][i] = __bfloat162float(cim[t * S_ + i]); }
    if (e == 0) idx = 0x7fff - (int)(fb_best() & 0x7fffu);
    __syncthreads();
    float y = 0.f;
    for (int s = 0; s < S_; s++)
        y += c[0][s] * __bfloat162float(((const bf16*)g_ab)[s * 1024 + e]) - c[1][s] * __bfloat162float(((const bf16*)g_ab)[s * 1024 + 512 + e]);
    const float g = g_fb_gate[t];
    out[t * D_ + e] = __float2bfloat16(g * y + (1.f - g) * (__bfloat162float(x[t * D_ + e]) + (t == idx ? g_fb_upd[e] : 0.f)));
}

__device__ __forceinline__ void spare_job(const Params& p, Scratch* g, unsigned char* smem, int sp, uint32_t tstart) {
    const int tid = threadIdx.x, warp = tid >> 5, lane = tid & 31;
    if (warp >= 8) {
#pragma unroll 1
        for (int i = 0; i < 16; i++) {
            nap_until(tstart + PFD_T0 + i * (PFD_DT / 2));
            prefetch_l2((const char*)((sp & 2) ? p.dim : p.dre) + (sp & 1) * 262144 + i * 16384 + (tid - 256) * 128);
        }
        return;
    }
    named_bar(2, 288);
    mbar_wait(smem_u32(smem) + B_FULL, 0);
    nap_until(tstart + SUM_T0 - 2000);
    const uint32_t e1 = ld_relaxed(g->epoch + NCTA + sp) + 1u, par = e1 & 1u;
    const uint32_t u = best_key(g->keys + warp * NCTA, par) >> 16;
    const float rs = sigmoidf_(__uint_as_float(((u & 0x8000u) ? (u & 0x7fffu) : (~u & 0xffffu)) << 16));
    nap_until(tstart + SUM_T0);
    uint32_t n = 0;
#pragma unroll 1
    while ((int)(ld_relaxed(g->phint + (sp * 8 + warp) * 8) - e1 * 14u) < 0) {
        __nanosleep(40);
        if (++n > SPIN_LIMIT) break;
    }
    const unsigned int* src = g->part + warp * 7 * D_ + sp * 128 + lane * 4;
    uint4 v[7];
#pragma unroll 1
    while (true) {
        uint32_t bad = 0;
#pragma unroll
        for (int i = 0; i < 7; i++) v[i] = ld_relaxed4(src + i * D_);
#pragma unroll
        for (int i = 0; i < 7; i++) bad |= (v[i].x ^ par) | (v[i].y ^ par) | (v[i].z ^ par) | (v[i].w ^ par);
        if (!__any_sync(0xffffffffu, bad & 1u)) break;
        if (++n > SPIN_LIMIT) break;
    }
    float4 s = make_float4(0.f, 0.f, 0.f, 0.f);
#pragma unroll
    for (int i = 0; i < 7; i++) {
        s.x += __uint_as_float(v[i].x); s.y += __uint_as_float(v[i].y);
        s.z += __uint_as_float(v[i].z); s.w += __uint_as_float(v[i].w);
    }
    float* acc = (float*)(smem + R6);
    *(float4*)&acc[warp * 128 + lane * 4] = s;
    named_bar(1, 256);
    if (tid < 128) {
        float t = 0.f;
#pragma unroll
        for (int i = 0; i < 8; i++) t += acc[i * 128 + tid];
        st_relaxed(&g->upd[sp * 128 + tid], tagf(t * rs, par));
        if (tid == 0) st_relaxed(g->epoch + NCTA + sp, e1);
    }
}

__device__ __forceinline__ int ffn_pair(int role) { return role - __popcll(NOFFN_MASK & ((1ull << role) - 1)); }
__device__ __forceinline__ int other(int i, int tn) { return i + (i >= tn); }
__device__ __forceinline__ int dcol(int p, int tn) { return p < 2 ? tn * 128 + p * 64 : other((p - 2) % 3, tn) * 128 + (p >= 5 ? 64 : 0); }

template <int H>
__device__ __forceinline__ void fetch_job(const Params& p, Scratch* g, unsigned char* smem, uint32_t sb, int cta, int i, uint32_t par) {
    const int lane = threadIdx.x & 31, comp = cta & 1;
    const int j = other(i, (cta >> 1) & 3), src = (cta & ~6) + 2 * j;
    const int slot = i == 0 ? 29 % NST : i - 1;
    const uint32_t land = sb + B_LAND + 8 * (3 * H + i);
    uint32_t ph = 0, th;
    mbar_expect_tx_elect(land, 8192);
    if (H == 0) {
        mbar_wait(sb + B_S0, 0);
        const uint32_t t0 = clk();
        if (i == 0) {
            mbar_wait(sb + B_FULL + 8 * (31 % NST), (31 / NST) & 1);
            const uint32_t t1 = t0 + max(clk() - t0, 180u) - 180u;
            asm volatile("{.reg .pred p; .reg .b64 t; setp.eq.b32 p, %3, 0; mov.b64 t, {%1, %2}; @p st.relaxed.gpu.global.b64 [%0], t;}"
                         ::"l"(g->stamp + cta * 32), "r"((t1 & ~1u) | par), "r"(gtime()), "r"(lane) : "memory");
        }
        until(t0 + SDEL);
        uint32_t gt;
#pragma unroll 1
        for (uint32_t n = 0; n < SPIN_LIMIT; n++) {
            asm volatile("{.reg .b64 t; ld.relaxed.gpu.global.b64 t, [%2]; mov.b64 {%0,%1}, t;}" : "=r"(th), "=r"(gt) : "l"(g->stamp + src * 32) : "memory");
            if (!__any_sync(0xffffffffu, (th ^ par) & 1u)) break;
        }
        const uint32_t ns = min(gtime() - gt, 4096u), now = clk();
        if (now - th >= 8192u) th = now - (ns + (ns >> 1) + (ns >> 4));
        th += SG * j;
        if (lane == 0) { *(volatile uint32_t*)(smem + M_TH + 4 * i) = th; mbar_arrive(sb + B_TH + 8 * i); }
        __syncwarp();
    } else {
        mbar_wait(sb + B_TH + 8 * i, 0);
        th = lds32(sb + M_TH + 4 * i);
    }
    mbar_wait(sb + B_EA, 0);
#pragma unroll 1
    for (int c = 0; c < 2; c++) {
        const uint32_t dst = sb + slot * 16384 + (c ? NST * 16384 + H * 8192 : (comp ^ H) * 8192);
        if (c != H) mbar_wait(sb + B_EMPTY + 8 * slot, i != 0);
        until(th + (c ? (H ? L_RD1 : L_RD0) : (H ? E_RD1 : E_RD0)));
#pragma unroll 1
        for (uint32_t r = 0; r < SPIN_LIMIT; r++) {
            tma2d_elect(dst, &p.mF, 0, (src * 2 + (comp ^ c)) * 128 + H * 64, land);
            mbar_wait(land, ph);
            ph ^= 1;
            const uint32_t a = dst + (lane >> 2) * 132 + (lane & 3) * 32;
            uint32_t v[8], m0 = 0, m1 = ~0u;
#pragma unroll
            for (int k = 0; k < 8; k++) v[k] = lds32(a + k * 1024);
#pragma unroll
            for (int k = 0; k < 8; k++) { m0 |= v[k]; m1 &= v[k]; }
            if (__all_sync(0xffffffffu, (par ? m1 : ~m0) & 1u)) break;
            mbar_expect_tx_elect(land, 8192);
        }
        mbar_arrive_if(sb + B_VAL + 8 * (6 * c + 3 * H + i), lane == 0);
        if (c == 0) mbar_expect_tx_elect(land, 8192);
    }
}

__global__ void __cluster_dims__(2, 1, 1) __launch_bounds__(NTHREADS, 1)
fused_kernel(const __grid_constant__ CPtr pc, const char* px, char* pout, Scratch* g, const __grid_constant__ Params p) {
    extern __shared__ __align__(1024) unsigned char smem[];
    const uint32_t sb = smem_u32(smem);
    const int tid = threadIdx.x, warp = tid >> 5, lane = tid & 31;
    const int rank = blockIdx.x & 1;
    const char* pcr = pc.c[rank];
    asm volatile("{.reg .pred p; setp.lt.u32 p, %1, 32; @p prefetch.global.L2 [%0];}"
                 ::"l"(pcr + (uint32_t)(((blockIdx.x << 16) & 0x7e0000) + (tid << 12))), "r"(tid));
    const uint32_t tstart = clk();
    asm volatile("{.reg .pred p; setp.lt.u32 p, %1, 4; @p prefetch.global.L2 [%0];}"
                 ::"l"(px + (uint32_t)(((blockIdx.x << 9) & 0xfe00) + (tid << 7))), "r"(tid));
    uint32_t smid;
    asm volatile("mov.u32 %0, %%smid;" : "=r"(smid));
    const int u = smid >> 1;
    const int code = sel(u, sel(((u - 32) * 293) >> 8, 8 * u - 489, u < 60), u < 32);
    const int tn = code >> 3, tm = (code & 7) + sel(0, 8, u < 32);
    const int comp = rank;
    const CUtensorMap* mC = &p.mCre + comp;
#define ARM(j) do { mbar_init(sb + B_FULL + 8 * (j), 1); mbar_expect_tx(sb + B_FULL + 8 * (j), 32768); } while (0)
#define STEP0(j) do { tma2d_elect(sb + (j) * 16384, mC, (j) * 64, tm * 128, sb + B_FULL + 8 * (j));                            \
                      tma3d_elect(sb + (NST + (j)) * 16384, &p.mX2, (j) * 64, tn * 2, sb + B_FULL + 8 * (j)); } while (0)
    if (__all_sync(0xffffffffu, warp == 12)) {
        asm volatile("{.reg .pred p; elect.sync _|p, 0xffffffff; @p mbarrier.init.shared::cta.b64 [%0], 1;}" ::"r"(sb + B_FULL) : "memory");
        STEP0(0);
        mbar_expect_tx_elect(sb + B_FULL, 32768);
        asm volatile("bar.arrive 2, 288;" ::: "memory");
    }
    const bool spare = tn < 0;
    const int role = tm * 4 + tn, cta = role * 2 + rank;
    const int wu = __shfl_sync(0xffffffffu, warp, 0);
    if (wu < 12) {
        if (lane == 0) {
            mbar_init(sb + B_EMPTY + 8 * wu, 2);
            mbar_init(sb + B_VD + 8 * wu, wu ? 1 : 4);
#pragma unroll
            for (int i = 24; i < NBAR; i += 12) if (i + 12 <= NBAR || wu < NBAR - i) mbar_init(sb + B_EMPTY + 8 * (i + wu), 1);
            if (wu >= 1 && wu < 4) mbar_expect_tx(sb + B_VD + 8 * wu, wu < 3 ? 8192 : 256);
        }
        asm volatile("fence.mbarrier_init.release.cluster;" ::: "memory");
        __syncwarp();
        asm volatile("barrier.cluster.arrive.relaxed.aligned;" ::: "memory");
        if (spare) {
            spare_job(p, g, smem, smid & 3, tstart);
        } else if (wu >= 8) {
            asm volatile("setmaxnreg.dec.sync.aligned.u32 " STR(RS_) ";");
            asm volatile("barrier.cluster.wait.acquire.aligned;" ::: "memory");
            const int t = tid - 256, w = wu - 8, fr = ffn_pair(role);
            const bool ffn = !((NOFFN_MASK >> role) & 1);
            nap_until(tstart + SIDE_T0);
            const uint4 gw0 = ldg_nc_off<0>(p.gate_w + lane * 8), gw1 = ldg_nc_off<512>(p.gate_w + lane * 8);
            const uint4 rw0 = ldg_nc_off<0>(p.w_r + lane * 8), rw1 = ldg_nc_off<512>(p.w_r + lane * 8);
            const uint32_t par = ~ld_relaxed(g->epoch + cta) & 1u;
            nap_until(tstart + ROUTER_T0 + (2 * w + rank) * ROUTER_DT);
            {
                const int row0 = cta * 16 + w * 4;
                const char* xp = px + (uint32_t)row0 * (D_ * 2) + lane * 16;
                uint4 xa[4], xb[4];
                xa[0] = ldg_nc_off<0>(xp);    xb[0] = ldg_nc_off<512>(xp);  xa[1] = ldg_nc_off<1024>(xp); xb[1] = ldg_nc_off<1536>(xp);
                xa[2] = ldg_nc_off<2048>(xp); xb[2] = ldg_nc_off<2560>(xp); xa[3] = ldg_nc_off<3072>(xp); xb[3] = ldg_nc_off<3584>(xp);
                float a[8];
#pragma unroll
                for (int i = 0; i < 4; i++) {
                    const uint32_t xv[8] = {xa[i].x, xa[i].y, xa[i].z, xa[i].w, xb[i].x, xb[i].y, xb[i].z, xb[i].w};
                    const uint32_t gv[8] = {gw0.x, gw0.y, gw0.z, gw0.w, gw1.x, gw1.y, gw1.z, gw1.w};
                    const uint32_t rv[8] = {rw0.x, rw0.y, rw0.z, rw0.w, rw1.x, rw1.y, rw1.z, rw1.w};
                    float uu = 0.f, vv = 0.f;
#pragma unroll
                    for (int j = 0; j < 8; j++) {
                        const uint32_t pr = hmul2_bf16(xv[j], gv[j]);
                        uu += bflo(pr); uu += bfhi(pr);
                        vv = fmaf(bflo(xv[j]), bflo(rv[j]), vv); vv = fmaf(bfhi(xv[j]), bfhi(rv[j]), vv);
                    }
                    a[i] = uu; a[4 + i] = vv;
                }
                halve<4, 16>(a); halve<2, 8>(a); halve<1, 4>(a);
                {
                    const float b1 = __shfl_xor_sync(0xffffffffu, a[0], 1), b2 = __shfl_xor_sync(0xffffffffu, a[0], 2),
                                b3 = __shfl_xor_sync(0xffffffffu, a[0], 3);
                    a[0] = (a[0] + b1) + (b2 + b3);
                }
                const int row = row0 + ((lane >> 2) & 3);
                const uint32_t best = __reduce_max_sync(0xffffffffu, lane >= 16 && (lane & 3) == 0 ? router_key(a[0], row) : 0u);
                if (lane <= 16 && (lane & 3) == 0)
                    *(volatile uint32_t*)(smem + M_RED + (lane < 16 ? w * 16 + lane : 64 + w * 4)) = lane < 16 ? pack_bf16(0.f, sigmoidf_(bfhi(pack_bf16(0.f, a[0])))) | par : best;
                named_bar(1, 128);
                if (t < 8) {
                    const uint4 k = lds128(sb + M_RED + 64);
                    asm volatile("{.reg .b32 old; atom.relaxed.gpu.global.exch.b32 old, [%0], %1;}"
                                 ::"l"(g->keys + t * NCTA + cta), "r"(max(max(k.x, k.y), max(k.z, k.w)) | (par << 15)) : "memory");
                }
                if (w == 1 && lane < 16) st_relaxed(g->gate + cta * 16 + lane, lds32(sb + M_RED + lane * 4));
            }
            uint32_t vd[32];
            if (ffn) {
                mbar_wait(sb + B_FFN + 24, 0);
#pragma unroll
                for (int j = 0; j < 32; j++) vd[j] = lds32(sb + R6 + ((j >> 3) & 1) * 16384 + (2 + (j >> 4)) * 4096 + (j & 7) * 512 + t * 4);
                mbar_arrive_warp(sb + B_VD);
            }
            mbar_wait(sb + B_GATE, 0);
            const int idx = 0x7fff - (int)(*(volatile uint32_t*)(smem + M_KEY) & 0x7fffu);
            if (ffn) {
                float a[16];
#pragma unroll
                for (int i = 0; i < 16; i++) a[i] = 0.f;
#pragma unroll 1
                for (int qu = 0; qu < 4; qu++) {
                    mbar_wait(sb + B_FFN + 8 * qu, qu == 3);
#pragma unroll
                    for (int i = 2 * qu; i < 2 * qu + 2; i++) {
                        const float xs = __bfloat162float(((const bf16*)(smem + M_UPD))[32 * i + (t >> 2)]);
                        const uint4 vg = lds128(sb + R6 + i * 2048 + t * 16);
                        const uint4 vu = lds128(sb + R6 + 16384 + i * 2048 + t * 16);
                        const uint32_t g4[4] = {vg.x, vg.y, vg.z, vg.w};
                        const uint32_t u4[4] = {vu.x, vu.y, vu.z, vu.w};
#pragma unroll
                        for (int j = 0; j < 4; j++) {
                            a[2 * j] = fmaf(xs, bflo(g4[j]), a[2 * j]);         a[2 * j + 1] = fmaf(xs, bfhi(g4[j]), a[2 * j + 1]);
                            a[8 + 2 * j] = fmaf(xs, bflo(u4[j]), a[8 + 2 * j]); a[9 + 2 * j] = fmaf(xs, bfhi(u4[j]), a[9 + 2 * j]);
                        }
                    }
                }
                named_bar(1, 128);
                mbar_arrive_if(sb + B_R6, t == 0);
                halve<8, 16>(a); halve<4, 8>(a); halve<2, 4>(a);
                float* red = (float*)(smem + M_UPD);
                *(float2*)&red[w * 64 + (lane >> 4) * 32 + (lane & 3) * 8 + ((lane >> 2) & 3) * 2] = make_float2(a[0], a[1]);
                named_bar(1, 128);
                const float sg = red[lane] + red[64 + lane] + red[128 + lane] + red[192 + lane];
                const float su = red[32 + lane] + red[96 + lane] + red[160 + lane] + red[224 + lane];
                if (w < 2) {
                    asm volatile("st.async.weak.shared::cluster.mbarrier::complete_tx::bytes.f32 [%0], %1, [%2];"
                                 ::"r"(mapa(sb + M_HX + t * 4, rank ^ 1)), "f"(w ? su : sg), "r"(mapa(sb + B_HX, rank ^ 1)) : "memory");
                }
                named_bar(1, 128);
                mbar_wait(sb + B_HX, 0);
                const float pg = ((const float*)(smem + M_HX))[lane], pu = ((const float*)(smem + M_HX))[32 + lane];
                const float gs = sg + pg, us = su + pu;
                float* hrow = red + w * 32;
                hrow[lane] = gs * sigmoidf_(gs) * us;
                __syncwarp();
                float o0 = 0.f, o1 = 0.f;
#pragma unroll
                for (int j4 = 0; j4 < 8; j4++) {
                    const float4 hv = *(const float4*)&hrow[j4 * 4];
                    o0 = fmaf(hv.x, bflo(vd[4 * j4]), o0);     o1 = fmaf(hv.x, bfhi(vd[4 * j4]), o1);
                    o0 = fmaf(hv.y, bflo(vd[4 * j4 + 1]), o0); o1 = fmaf(hv.y, bfhi(vd[4 * j4 + 1]), o1);
                    o0 = fmaf(hv.z, bflo(vd[4 * j4 + 2]), o0); o1 = fmaf(hv.z, bfhi(vd[4 * j4 + 2]), o1);
                    o0 = fmaf(hv.w, bflo(vd[4 * j4 + 3]), o0); o1 = fmaf(hv.w, bfhi(vd[4 * j4 + 3]), o1);
                }
                asm volatile("st.relaxed.gpu.global.v2.u32 [%0], {%1,%2};" ::"l"(&g->part[fr * D_ + rank * 256 + t * 2]),
                             "r"(tagf(o0, par)), "r"(tagf(o1, par)) : "memory");
                if (lane == 0) asm volatile("red.relaxed.gpu.global.add.u32 [%0], 1;" ::"l"(g->phint + ((rank * 2 + (w >> 1)) * 8 + fr / 7) * 8) : "memory");
            }
            if (!ffn) mbar_arrive_if(sb + B_R6, t == 0);
            if (w < 3) {
                fetch_job<1>(p, g, smem, sb, cta, w, par);
            } else {
                if (lds32(sb + M_ROLE) != (uint32_t)role) __trap();
                if ((idx >> 6) == 2 * tm + comp) {
                    const float og = bfhi(pack_bf16(0.f, 1.f - ((const float*)(smem + M_G))[idx & 127]));
                    const uint4 u4 = wait_tags(g->upd + tn * 128 + lane * 4, par);
                    *(float4*)(smem + M_RED + lane * 16) = make_float4(og * __uint_as_float(u4.x), og * __uint_as_float(u4.y),
                                                                       og * __uint_as_float(u4.z), og * __uint_as_float(u4.w));
                    mbar_arrive_warp(sb + B_SIDE);
                }
            }
        } else {
            const int wg = wu >> 2;
            const uint32_t sbd = (sb & 0x3FFFF) >> 4;
            const bool lead = (tid & 127) == 0;
            const bool early = wg == comp;
            const int q = lane & 3;
            const int r0 = (warp & 3) * 16 + (lane >> 2);
            float acc[64];
            const uint32_t da0 = sbd + 0x10000 + wg * 512, db0 = sbd + 0x2000000, dd0 = sbd + 0x10000;
            const uint32_t rE = mapa(sb + B_EMPR, rank ^ 1);
#define WAITFULL(s) mbar_wait(sb + B_FULL + 8 * ((s) % NST), ((s) / NST) & 1)
#define TESTFULL(s) mbar_test(sb + B_FULL + 8 * ((s) % NST), ((s) / NST) & 1)
#define WAITD(pos) do { if ((pos) >= 4) mbar_wait(sb + B_DL + 8 * ((pos) & 3), 0); else if ((pos) >= 2) mbar_wait(sb + B_D6, 0); else WAITFULL(32); } while (0)
#define MMA_A(s, kk) wgmma128(acc, desc_lo(da0 + a_addr(s) / 16 + (kk) * 2), desc_lo(db0 + b_addr(s) / 16 + (kk) * 128), 1)
            named_bar(2, 288);
            WAITFULL(0);
            wg_fence();
#pragma unroll
            for (int kk = 0; kk < 4; kk++) wgmma128(acc, desc_lo(da0 + kk * 2), desc_lo(db0 + b_addr(0) / 16 + kk * 128), kk != 0);
            wg_commit();
            asm volatile("setmaxnreg.inc.sync.aligned.u32 " STR(RC) ";");
            asm volatile("barrier.cluster.wait.acquire.aligned;" ::: "memory");
            int slot = 1, ph = 0, pslot = 0;
            const uint32_t ooff = (uint32_t)((tm * 128 + wg * 64 + r0) * D_ + tn * 128 + q * 8) * 2u;
            uint32_t* fout = g->frag + (cta * 2 + wg) * 4096 + (warp & 3) * 128 + lane;
            uint32_t tagm[4];
#pragma unroll
            for (int c = 0; c < 4; c++) tagm[c] = (lane & 7) == (warp & 1) * 4 + c;
            const char* xp = px + ooff;
            asm volatile("" : "+r"(tagm[0]), "+r"(tagm[1]), "+r"(tagm[2]), "+r"(tagm[3]), "+l"(xp), "+l"(fout));
            uint4 w[8];
#pragma unroll
            for (int i = 0; i < 8; i++) w[i] = make_uint4(0, 0, 0, 0);
#pragma unroll
            for (int part = 0; part <= XN; part++) {
                if (part) {
#pragma unroll
                    for (int i = (part - 1) * 8 / XN; i < part * 8 / XN; i++) ldg_nc_if(w[i], xp + (i & 1) * 8192 + (i >> 1) * 64, early);
                }
#pragma unroll 1
                for (int step = part ? XLD + (part - 1) * XD : 1; step < (part < XN ? XLD + part * XD : SP0); step++) {
                    mbar_wait(sb + B_FULL + 8 * slot, ph);
                    const uint32_t a = da0 + slot * 1024, b = db0 + b_addr(0) / 16 + slot * 1024;
                    wg_fence();
                    wgmma128(acc, desc_lo(a), desc_lo(b), 1);
                    wg_commit();
                    wg_wait<1>();
                    mbar_arrive_if(sb + B_EMPTY + 8 * pslot, lead);
                    mbar_arrive_cluster_if(rE + 8 * pslot, lead);
                    pslot = slot;
                    if (++slot == NST) { slot = 0; ph ^= 1; }
                    wg_fence();
#pragma unroll
                    for (int kk = 1; kk < 4; kk++) wgmma128(acc, desc_lo(a + kk * 2), desc_lo(b + kk * 128), 1);
                    wg_commit();
                }
            }
            uint32_t par;
            float g0, g1;
#define GATES() do { par = lds32(sb + M_PAR); g0 = __uint_as_float(lds32(sb + M_G + (wg * 64 + r0) * 4)); g1 = __uint_as_float(lds32(sb + M_G + (wg * 64 + r0 + 8) * 4)); } while (0)
            if (early) {
                WAITFULL(SP0);
                wg_fence();
                MMA_A(SP0, 0); MMA_A(SP0, 1);
                wg_commit();
                wg_wait<1>();
                mbar_arrive_if(sb + B_EMPTY + 8 * ((SP0 - 1) % NST), lead);
                bool ok = TESTFULL(SP0 + 1);
                MMA_A(SP0, 2); MMA_A(SP0, 3);
                wg_commit();
#pragma unroll
                for (int s = SP0 + 1; s < 32; s++) {
                    if (!ok) { WAITFULL(s); if (s == 29) mbar_wait(sb + B_GATE, 0); }
                    wg_fence();
                    MMA_A(s, 0); MMA_A(s, 1);
                    if (s == 29) GATES();
                    if (s >= 30) { wg_commit(); wg_wait<1>(); mbar_arrive_if(sb + (s == 30 ? B_S0 : B_S1), lead); wg_fence(); }
                    if (s < 31) ok = TESTFULL(s + 1) & (s != 28 || mbar_test(sb + B_GATE, 0));
                    MMA_A(s, 2); MMA_A(s, 3);
                    wg_commit();
                }
                wg_wait<0>();
                mbar_arrive_if(sb + B_EA, lead);
            } else {
                wg_wait<0>();
                mbar_arrive_if(sb + B_EMPTY + 8 * ((SP0 - 1) % NST), lead);
#pragma unroll
                for (int s = SP0; s < 32; s++) WAITFULL(s);
                mbar_wait(sb + B_GATE, 0);
                GATES();
                mbar_wait(sb + B_S1, 0);
                wg_fence();
#pragma unroll
                for (int s = SP0; s < 32; s++) {
                    MMA_A(s, 0); MMA_A(s, 1);
                    if (s > SP0) {
                        wg_commit();
                        wg_wait<1>();
                        mbar_arrive_n_if<2>(sb + B_EMPTY + 8 * ((s - 1) % NST), lead);
                        if (s == 31) mbar_arrive_if(sb + B_S3, lead);
                        if (s == 30) WAITD(0);
                        wg_fence();
                    }
                    MMA_A(s, 2); MMA_A(s, 3);
                    wg_commit();
                }
                wg_wait<0>();
                mbar_arrive_n_if<2>(sb + B_EMPTY + 8 * (31 % NST), lead);
            }
            fence_regs<0, 64>(acc);
            uint4 f[8];
#define TAG(v, c) (((v) & ~tagm[c]) | (par & tagm[c]))
#define PACK(k) f[k] = make_uint4(TAG(pack_bf16(acc[8 * (k)], acc[8 * (k) + 1]), 0), TAG(pack_bf16(acc[8 * (k) + 2], acc[8 * (k) + 3]), 2), \
                                  TAG(pack_bf16(acc[8 * (k) + 4], acc[8 * (k) + 5]), 1), TAG(pack_bf16(acc[8 * (k) + 6], acc[8 * (k) + 7]), 3))
#define SEND(k) do { st_relaxed(fout + 512 * (k), f[k].x); st_relaxed(fout + 512 * (k) + 32, f[k].z);                        \
                     st_relaxed(fout + 512 * (k) + 64, f[k].y); st_relaxed(fout + 512 * (k) + 96, f[k].w); } while (0)
#define OWN(k) wgmma128rs(acc, f[k], desc_lo(dd0 + d_addr((k) >> 2) / 16 + ((k) & 3) * 2), (k) != 0)
            const uint32_t dfa = sbd + 0x80000 + (early ? comp * 512 : NST * 1024), dfb = sbd + 0x80000 + (early ? (1 - comp) * 512 : NST * 1024 + 512);
#define MMA_F(pos, kk) wgmma128<0>(acc, (uint64_t)(((pos) < 5 ? dfa : dfb) + a_addr(29 + ((pos) - 2) % 3) / 16 + (kk) * 128) | (0x10ull << 32), \
                                   desc_lo(dd0 + d_addr(pos) / 16 + (kk) * 2), 1)
#define WAITF(pos) mbar_wait(vb + 8 * ((pos) - 2), 0)
            const uint32_t vb = sb + B_VAL + (early ? 0 : 48);
            const uint32_t ts = clk();
            if (early) {
                PACK(0); SEND(0); PACK(1); SEND(1); PACK(2); SEND(2); PACK(3); SEND(3);
                until(ts);
                PACK(4); PACK(5); PACK(6); PACK(7);
                const float s0 = comp ? -g0 : g0, s1 = comp ? -g1 : g1;
                const uint32_t og0 = pack_bf16(1.f - g0, 1.f - g0), og1 = pack_bf16(1.f - g1, 1.f - g1);
                const int rr = 0x7fff - (int)(lds32(sb + M_KEY) & 0x7fffu) - (tm * 128 + wg * 64 + r0);
#pragma unroll
                for (int k = 4; k < 8; k++) {
                    if (k < ESEND) { until(ts + ET1 + (k - 4) * STP); SEND(k); }
#pragma unroll
                    for (int i = 2 * k - 8; i < 2 * k - 6; i++) {
                        const uint32_t og = (i & 1) ? og1 : og0;
                        w[i] = make_uint4(hmul2_bf16(og, w[i].x), hmul2_bf16(og, w[i].y), hmul2_bf16(og, w[i].z), hmul2_bf16(og, w[i].w));
                        asm volatile("" : "+r"(w[i].x), "+r"(w[i].y), "+r"(w[i].z), "+r"(w[i].w));
                    }
                }
                WAITD(0);
                mbar_wait(sb + B_S3, 0);
                wg_fence();
#pragma unroll
                for (int k = 0; k < 8; k++) {
                    OWN(k);
                    if (k >= 1 && k + ESEND - 1 < 8) { wg_commit(); until(ts + ET1 + (k + ESEND - 5) * STP); SEND(k + ESEND - 1); wg_fence(); }
                }
                wg_commit();
                WAITD(2);
                bool ok = false;
#pragma unroll
                for (int pos = 2; pos < 8; pos++) {
                    if (!ok) {
                        if (pos >= 4) WAITD(pos);
                        WAITF(pos);
                    }
                    wg_fence();
                    MMA_F(pos, 0); MMA_F(pos, 1);
                    if (pos == 6) { wg_commit(); wg_wait<1>(); mbar_arrive_cluster_if(mapa(sb + B_XF, rank ^ 1), lead); wg_fence(); }
                    if (pos == 7) mbar_arrive_if(sb + B_S2, lead);
                    if (pos < 7) ok = mbar_test(vb + 8 * (pos - 1), 0) & (pos < 3 || mbar_test(sb + B_DL + 8 * (pos - 3), 0));
                    MMA_F(pos, 2); MMA_F(pos, 3);
                    wg_commit();
                }
                const uint32_t xd = mapa(sb + a_addr(29) + (tid & 127) * 16, rank ^ 1), xb = mapa(sb + B_X, rank ^ 1);
                if (rr == 0 || rr == 8) {
                    mbar_wait(sb + B_SIDE, 0);
#pragma unroll
                    for (int j = 0; j < 4; j++) {
                        const float4 ua = *(const float4*)(smem + M_RED + j * 128 + q * 32), ub = *(const float4*)(smem + M_RED + j * 128 + q * 32 + 16);
                        uint4 v = rr ? w[2 * j + 1] : w[2 * j];
                        v = make_uint4(pack_bf16(ua.x + bflo(v.x), ua.y + bfhi(v.x)), pack_bf16(ua.z + bflo(v.y), ua.w + bfhi(v.y)),
                                       pack_bf16(ub.x + bflo(v.z), ub.y + bfhi(v.z)), pack_bf16(ub.z + bflo(v.w), ub.w + bfhi(v.w)));
                        if (rr) w[2 * j + 1] = v; else w[2 * j] = v;
                    }
                }
                __syncwarp();
                mbar_wait(sb + B_XF, 0);
                wg_wait<0>();
                fence_regs<0, 64>(acc);
                keep_regs<0, 8>(f);
#pragma unroll
                for (int i = 0; i < 8; i++) {
                    const uint4 z = scale_add((i & 1) ? s1 : s0, acc, 16 * (i >> 1) + 2 * (i & 1), w[i]);
                    st_async16(xd + i * 2048, z.x, z.y, z.z, z.w, xb + 2 * (i & 4));
                    if (i & 1) until(ts);
                }
            } else {
#pragma unroll
                for (int k = 0; k < 4; k++) {
                    PACK(2 * k); PACK(2 * k + 1);
                    if (k < LPRE) { until(ts + LT0 + k * LTP); SEND(k); }
                }
                wg_fence();
#pragma unroll
                for (int k = 0; k < 8; k++) {
                    OWN(k);
                    if ((k & 1) && k / 2 < LSEND) { wg_commit(); until(ts + LT0 + (LPRE + k / 2) * LTP); SEND(LPRE + k / 2); wg_fence(); }
                }
                wg_commit();
#pragma unroll
                for (int k = LPRE + LSEND; k < 8; k++) { until(ts + LT0 + k * LTP); SEND(k); }
                float s0 = comp ? -g0 : g0, s1 = comp ? -g1 : g1;
                uint32_t xs = sb + a_addr(29) + (tid & 127) * 16;
                char* op = pout + ooff;
                asm volatile("" : "+f"(s0), "+f"(s1), "+r"(xs), "+l"(op));
                wg_wait<0>();
                keep_regs<0, 8>(f);
                WAITF(2);
                mbar_wait(sb + B_S2, 0);
                bool there = false, there1 = false, ok = true;
#pragma unroll
                for (int pos = 2; pos < 8; pos++) {
                    if (!ok) WAITF(pos);
                    wg_fence();
                    MMA_F(pos, 0);
                    if (pos == XPOS) there = mbar_test(sb + B_X, 0);
                    MMA_F(pos, 1);
                    if (pos == XPOS) {
#pragma unroll
                        for (int i = 0; i < 4; i++) lds128_if(w[i], xs + i * 2048, there);
                    }
                    if (pos < 7) ok = mbar_test(vb + 8 * (pos - 1), 0);
                    MMA_F(pos, 2); MMA_F(pos, 3);
                    wg_commit();
                }
                if (!there) {
                    mbar_wait(sb + B_X, 0);
#pragma unroll
                    for (int i = 0; i < 4; i++) w[i] = lds128(xs + i * 2048);
                }
                there1 = mbar_test(sb + B_X + 8, 0);
                float z[32];
#pragma unroll
                for (int i = 0; i < 4; i++) {
                    z[8 * i] = bflo(w[i].x); z[8 * i + 1] = bfhi(w[i].x); z[8 * i + 2] = bflo(w[i].y); z[8 * i + 3] = bfhi(w[i].y);
                    z[8 * i + 4] = bflo(w[i].z); z[8 * i + 5] = bfhi(w[i].z); z[8 * i + 6] = bflo(w[i].w); z[8 * i + 7] = bfhi(w[i].w);
                }
                fence_regs<0, 32>(z);
#pragma unroll 1
                for (int n = there1; n > 0; n--) {
#pragma unroll
                    for (int i = 4; i < 8; i++) w[i] = lds128(xs + i * 2048);
                }
                wg_wait<0>();
                fence_regs<0, 64>(acc);
#pragma unroll
                for (int i = 0; i < 8; i++) {
                    const int o = 16 * (i >> 1) + 2 * (i & 1);
                    const float s = (i & 1) ? s1 : s0;
                    if (i == XW && !there1) {
                        mbar_wait(sb + B_X + 8, 0);
#pragma unroll
                        for (int k = 4; k < 8; k++) w[k] = lds128(xs + k * 2048);
                    }
                    stg_off<0>(op + (i & 1) * 8192 + (i >> 1) * 64,
                               i >= 4 ? scale_add(s, acc, o, w[i])
                                      : make_uint4(pack_bf16(fmaf(s, acc[o], z[8 * (i & 3)]), fmaf(s, acc[o + 1], z[8 * (i & 3) + 1])),
                                                   pack_bf16(fmaf(s, acc[o + 4], z[8 * (i & 3) + 2]), fmaf(s, acc[o + 5], z[8 * (i & 3) + 3])),
                                                   pack_bf16(fmaf(s, acc[o + 8], z[8 * (i & 3) + 4]), fmaf(s, acc[o + 9], z[8 * (i & 3) + 5])),
                                                   pack_bf16(fmaf(s, acc[o + 12], z[8 * (i & 3) + 6]), fmaf(s, acc[o + 13], z[8 * (i & 3) + 7]))));
                    __syncwarp();
                }
            }
        }
    } else {
        if (wu >= 14) {
            const uint32_t b = blockIdx.x;
            const char* q = wu == 14 ? pcr + (uint32_t)((b >> 1) * 32 + lane) * (S_ * 2) + 128 : px + (uint32_t)(b * 4 + lane) * 128 + 65536;
            until(tstart + P_1);
            if (b < 128 && (wu == 14 || lane < 4)) prefetch_l2(q);
        } else if (wu == 13 && !spare) {
            if (lane == 0) ARM(1);
            __syncwarp();
            until(tstart + T_1);
            STEP0(1);
        }
        if (lane == 0) ARM(wu - 10);
        asm volatile("fence.mbarrier_init.release.cluster;" ::: "memory");
        __syncwarp();
        asm volatile("barrier.cluster.arrive.relaxed.aligned;" ::: "memory");
        if (spare) return;
        asm volatile("setmaxnreg.dec.sync.aligned.u32 " STR(RU) ";");
        if (wu < 14) {
            until(tstart + T_2 + (wu - 12) * PACE);
            STEP0(wu - 10);
        }
        asm volatile("barrier.cluster.wait.acquire.aligned;" ::: "memory");
        if (wu == 13) {
            const CUtensorMap* mD = comp ? &p.mDim : &p.mDre;
#pragma unroll
            for (int step = 4; step < NST; step++) {
                until(tstart + T_2 + (step - 2) * PACE);
                tma3d_elect(sb + b_addr(step), &p.mX2, step * 64, tn * 2, sb + B_FULL + 8 * step);
            }
#pragma unroll 1
            for (int step = NST, slot = 0, ph = 0; step < 32; step++) {
                mbar_wait(sb + B_EMPTY + 8 * slot, ph);
                mbar_wait(sb + B_EMPR + 8 * slot, ph);
                tma2d_pair_elect(sb + b_addr(0) + slot * 16384 + rank * 8192, &p.mX, tn * 128 + rank * 64, step * 64, sb + B_FULL + 8 * slot);
                if (++slot == NST) { slot = 0; ph ^= 1; }
            }
#pragma unroll
            for (int c = 0; c < 4; c += 2) {
                const uint32_t bar = sb + (c ? B_D6 : B_FULL + 8 * (32 % NST));
                if (c) mbar_wait(sb + B_R6, 0);
                else mbar_wait(sb + B_EMPTY + 8 * (26 % NST), (26 / NST) & 1);
                tma5d_elect(sb + d_addr(c), mD, dcol(c, tn), tn * 4, bar);
                tma5d_elect(sb + d_addr(c + 1), mD, dcol(c + 1, tn), tn * 4, bar);
                mbar_expect_tx_elect(bar, 32768);
            }
#pragma unroll
            for (int c = 0; c < 4; c++) mbar_expect_tx_elect(sb + B_DL + 8 * c, 16384);
            mbar_wait(sb + B_S1, 0);
            const uint32_t tq = clk();
#pragma unroll
            for (int c = 0; c < 4; c++) {
                if (!(c & 1)) mbar_wait(sb + B_EMPTY + 8 * ((27 + c / 2) % NST), ((27 + c / 2) / NST) & 1);
                if (c) until(tq + (c == 1 ? T_D5 : c == 2 ? T_D6 : T_D7));
                tma5d_elect(sb + d_addr(4 + c), mD, dcol(4 + c, tn), tn * 4, sb + B_DL + 8 * c);
            }
        } else {
            if (wu == 12) {
#pragma unroll
                for (int step = 4; step < NST; step++) {
                    until(tstart + T_2 + (step - 2) * PACE);
                    tma2d_elect(sb + a_addr(step), mC, step * 64, tm * 128, sb + B_FULL + 8 * step);
                }
#pragma unroll 1
                for (int step = NST, slot = 0, ph = 0; step < 32; step++) {
                    mbar_wait(sb + B_EMPTY + 8 * slot, ph);
                    tma2d_elect(sb + slot * 16384, mC, step * 64, tm * 128, sb + B_FULL + 8 * slot);
                    mbar_expect_tx_elect(sb + B_FULL + 8 * slot, 32768);
                    if (++slot == NST) { slot = 0; ph ^= 1; }
                }
            } else if (wu == 14) {
                if (lane == 0) {
                    asm volatile("prefetch.tensormap [%0];" ::"l"(&p.mX) : "memory");
                    asm volatile("prefetch.tensormap [%0];" ::"l"(&p.mF) : "memory");
                    asm volatile("prefetch.tensormap [%0];" ::"l"(comp ? &p.mDim : &p.mDre) : "memory");
                    asm volatile("st.shared::cluster.u32 [%0], %1;" ::"r"(mapa(sb + M_ROLE, rank ^ 1)), "r"(role) : "memory");
                }
                nap_until(tstart + KEY_T0 - 1000);
                const uint32_t epoch = ld_relaxed(g->epoch + cta) + 1u, par = epoch & 1u;
                if (lane < 8) stg_off<0>(g->stamp + cta * 32 + lane * 4, make_uint4(par ^ 1u, 0, 0, 0));
                nap_until(tstart + KEY_T0);
                const uint32_t k = best_key(g->keys + ((tm + (tm >> 3)) & 7) * NCTA, par);
                const uint4 xr = ldg_nc_off<0>(px + (0x7fff - (k & 0x7fffu)) * (D_ * 2) + rank * 512 + lane * 16);
                const uint4 g4 = wait_tags(g->gate + tm * 128 + lane * 4, par);
                sts128(sb + M_G + lane * 16, make_uint4(g4.x & ~1u, g4.y & ~1u, g4.z & ~1u, g4.w & ~1u));
                sts128(sb + M_UPD + lane * 16, xr);
                if (lane == 0) {
                    *(volatile uint32_t*)(smem + M_KEY) = k;
                    *(volatile uint32_t*)(smem + M_PAR) = par;
                    st_relaxed(g->epoch + cta, epoch);
                }
                mbar_arrive_warp(sb + B_GATE);
            } else {
                const int fr = ffn_pair(role);
                const uint32_t t1 = tstart + FFN_T0 + (rank + ((fr >> 2) & 6)) * (FFN_DT / 8);
                if (!((NOFFN_MASK >> role) & 1)) {
#pragma unroll 1
                    for (int i = 0; i < 12; i++) {
                        const int qu = i < 4 ? 2 + (i >> 1) : (i - 4) >> 1;
                        const uint32_t bar = sb + B_FFN + 8 * (i < 4 ? 3 : qu), dst = sb + R6 + (i & 1) * 16384 + qu * 4096;
                        if (i == 8) mbar_wait(sb + B_VD, 0);
                        if (i == 0 || (i >= 4 && !(i & 1))) mbar_expect_tx_elect(bar, i ? 8192 : 16384);
                        nap_until(t1 + i * FFN_DT);
                        tma2d_elect(dst, i < 4 ? &p.mWd : (i & 1) ? &p.mWu : &p.mWg, i < 4 ? rank * 256 : fr * 32, i < 4 ? fr * 32 + i * 8 : rank * 256 + qu * 64, bar);
                    }
                }
            }
            __syncwarp();
            mbar_wait(sb + B_GATE, 0);
            fetch_job<0>(p, g, smem, sb, cta, wu == 12 ? 2 : wu - 14, lds32(sb + M_PAR));
        }
    }
}

typedef CUresult (*EncodeTiledFn)(CUtensorMap*, CUtensorMapDataType, cuuint32_t, void*, const cuuint64_t*, const cuuint64_t*,
                                  const cuuint32_t*, const cuuint32_t*, CUtensorMapInterleave, CUtensorMapSwizzle,
                                  CUtensorMapL2promotion, CUtensorMapFloatOOBfill);

static void make_map(EncodeTiledFn enc, CUtensorMap* m, const void* base, uint64_t cols, uint64_t rows, uint32_t box_rows,
                     CUtensorMapSwizzle sw = CU_TENSOR_MAP_SWIZZLE_128B, uint32_t box_cols = 64) {
    cuuint64_t dims[2] = {cols, rows};
    cuuint64_t str[1] = {cols * 2};
    cuuint32_t box[2] = {box_cols, box_rows};
    cuuint32_t es[2] = {1, 1};
    enc(m, CU_TENSOR_MAP_DATA_TYPE_BFLOAT16, 2, (void*)base, dims, str, box, es, CU_TENSOR_MAP_INTERLEAVE_NONE,
        sw, CU_TENSOR_MAP_L2_PROMOTION_L2_128B, CU_TENSOR_MAP_FLOAT_OOB_FILL_NONE);
}

static void make_map_chunks(EncodeTiledFn enc, CUtensorMap* m, const void* base, uint64_t rows) {
    cuuint64_t dims[3] = {64, rows, D_ / 64};
    cuuint64_t str[2] = {D_ * 2, 128};
    cuuint32_t box[3] = {64, 64, 2};
    cuuint32_t es[3] = {1, 1, 1};
    enc(m, CU_TENSOR_MAP_DATA_TYPE_BFLOAT16, 3, (void*)base, dims, str, box, es, CU_TENSOR_MAP_INTERLEAVE_NONE,
        CU_TENSOR_MAP_SWIZZLE_128B, CU_TENSOR_MAP_L2_PROMOTION_L2_128B, CU_TENSOR_MAP_FLOAT_OOB_FILL_NONE);
}

static void make_map_perm(EncodeTiledFn enc, CUtensorMap* m, const void* base) {
    cuuint64_t dims[5] = {D_, 2, 4, 4, D_ / 32};
    cuuint64_t str[4] = {D_ * 2, 8 * D_ * 2, 2 * D_ * 2, 32 * D_ * 2};
    cuuint32_t box[5] = {64, 2, 4, 4, 4};
    cuuint32_t es[5] = {1, 1, 1, 1, 1};
    enc(m, CU_TENSOR_MAP_DATA_TYPE_BFLOAT16, 5, (void*)base, dims, str, box, es, CU_TENSOR_MAP_INTERLEAVE_NONE,
        CU_TENSOR_MAP_SWIZZLE_128B, CU_TENSOR_MAP_L2_PROMOTION_L2_128B, CU_TENSOR_MAP_FLOAT_OOB_FILL_NONE);
}

extern "C" void kernel_launch(void* const* d_in, const int* in_sizes, int n_in, void* d_out, int out_size) {
    (void)in_sizes; (void)n_in; (void)out_size;
    static EncodeTiledFn enc = nullptr;
    static bool fused_ok = false;
    static void* scr = nullptr;
    if (!enc) {
        void* fn = nullptr;
        cudaDriverEntryPointQueryResult q;
        cudaGetDriverEntryPoint("cuTensorMapEncodeTiled", &fn, cudaEnableDefault, &q);
        enc = (EncodeTiledFn)fn;
        cudaGetSymbolAddress(&scr, g_scr);
        cudaFuncSetAttribute(fused_kernel, cudaFuncAttributeMaxDynamicSharedMemorySize, SMEM_BYTES);
        int dev = 0, nsm = 0, ncl = 0;
        cudaGetDevice(&dev);
        cudaDeviceGetAttribute(&nsm, cudaDevAttrMultiProcessorCount, dev);
        cudaLaunchConfig_t cfg = {};
        cfg.gridDim = dim3(132); cfg.blockDim = dim3(NTHREADS); cfg.dynamicSmemBytes = SMEM_BYTES;
        cudaLaunchAttribute at;
        at.id = cudaLaunchAttributeClusterDimension;
        at.val.clusterDim.x = 2; at.val.clusterDim.y = 1; at.val.clusterDim.z = 1;
        cfg.attrs = &at; cfg.numAttrs = 1;
        fused_ok = cudaOccupancyMaxActiveClusters(&ncl, fused_kernel, &cfg) == cudaSuccess && nsm == 132 && ncl == 66;
        (void)cudaGetLastError();
    }
    if (!fused_ok) {
        const bf16* const* in = (const bf16* const*)d_in;
        fb_hidden<<<S_, D_, 0, cudaStreamPerThread>>>(in[0], in[3], in[4], in[10], in[6]);
        fb_ffn1<<<F_ / 128, 128, 0, cudaStreamPerThread>>>(in[0], in[7], in[8]);
        fb_ffn2<<<D_ / 64, 64, 0, cudaStreamPerThread>>>(in[9]);
        fb_seq<<<S_, D_, 0, cudaStreamPerThread>>>(in[0], in[1], in[2], (bf16*)d_out);
        return;
    }
    Params p;
    p.dre = (const bf16*)d_in[3];
    p.dim = (const bf16*)d_in[4];
    p.w_r = (const bf16*)d_in[6];
    p.gate_w = (const bf16*)d_in[10];
    make_map_chunks(enc, &p.mX2, d_in[0], S_);
    make_map(enc, &p.mX, d_in[0], D_, S_, 64);
    make_map(enc, &p.mCre, d_in[1], S_, S_, 128);
    make_map(enc, &p.mCim, d_in[2], S_, S_, 128);
    make_map_perm(enc, &p.mDre, d_in[3]);
    make_map_perm(enc, &p.mDim, d_in[4]);
    make_map(enc, &p.mF, scr, 64, NCTA * 256, 64, CU_TENSOR_MAP_SWIZZLE_NONE);
    make_map(enc, &p.mWg, d_in[7], F_, D_, 64, CU_TENSOR_MAP_SWIZZLE_NONE, 32);
    make_map(enc, &p.mWu, d_in[8], F_, D_, 64, CU_TENSOR_MAP_SWIZZLE_NONE, 32);
    make_map(enc, &p.mWd, d_in[9], D_, F_, 8, CU_TENSOR_MAP_SWIZZLE_NONE, 256);
    fused_kernel<<<132, NTHREADS, SMEM_BYTES, cudaStreamPerThread>>>(CPtr{{(const char*)d_in[1], (const char*)d_in[2]}}, (const char*)d_in[0], (char*)d_out, (Scratch*)scr, p);
}
```

```cpp
#include <cuda_runtime.h>
#include <cuda.h>
#include <cuda_bf16.h>
#include <stdint.h>

typedef __nv_bfloat16 bf16;

constexpr int S_ = 2048, D_ = 512, F_ = 1792;
constexpr int NCTA = 128;
constexpr int NTHREADS = 512;
constexpr int NST = 6;
constexpr int SP0 = 27;
constexpr int FFN_CTAS = F_ / 16;
constexpr uint32_t SPIN_LIMIT = 1u << 16;

#define P_1 450
#define T_1 500
#define T_2 1050
#define PACE 420
#define SIDE_T0 2800
#define ROUTER_T0 3000
#define ROUTER_DT 280
#define KEY_T0 9800
#define FFN_T0 5200
#define FFN_DT 640
#define XLD 14
#define XN 8
#define XD 1
#define PFD_T0 11900
#define PFD_DT 250
#define SUM_T0 15500
#define ET1 600
#define STP 170
#define ESEND 6
#define LT0 200
#define LTP 170
#define LPRE 2
#define LSEND 3
#define SDEL 280
#define E_RD0 1350
#define E_RD1 2180
#define L_RD0 3200
#define L_RD1 3880
#define SG 130
#define T_D5 1500
#define T_D6 1700
#define T_D7 2400
#define XPOS 7
#define XW 4
#define RC 168
#define RS_ 112
#define RU 64
#define NOFFN_MASK 0xf00c880000000000ull
#define STR2(x) #x
#define STR(x) STR2(x)

__host__ __device__ constexpr int a_addr(int s) { return s % NST * 16384; }
__host__ __device__ constexpr int b_addr(int s) { return (NST + s % NST) * 16384; }
constexpr int R6 = 2 * NST * 16384;
__host__ __device__ constexpr int d_addr(int p) { return p / 2 == 1 ? R6 + (p & 1) * 16384 : (p & 1) ? b_addr(26 + p / 3) : a_addr(26 + p / 3); }
static_assert(d_addr(0) == a_addr(26) && d_addr(4) == a_addr(27) && d_addr(6) == a_addr(28), "");
constexpr int OFF_MISC = R6 + 32768;
constexpr int B_FULL = OFF_MISC;
constexpr int B_EMPTY = B_FULL + 48;
constexpr int B_EMPR = B_EMPTY + 48;
constexpr int B_VD = B_EMPR + 48;
constexpr int B_X = B_VD + 8;
constexpr int B_HX = B_X + 16;
constexpr int B_XF = B_HX + 8;
constexpr int B_S0 = B_XF + 8;
constexpr int B_S1 = B_S0 + 8;
constexpr int B_EA = B_S1 + 8;
constexpr int B_S2 = B_EA + 8;
constexpr int B_S3 = B_S2 + 8;
constexpr int B_D6 = B_S3 + 8;
constexpr int B_DL = B_D6 + 8;
constexpr int B_GATE = B_DL + 32;
constexpr int B_SIDE = B_GATE + 8;
constexpr int B_FFN = B_SIDE + 8;
constexpr int B_R6 = B_FFN + 32;
constexpr int B_LAND = B_R6 + 8;
constexpr int B_VAL = B_LAND + 48;
constexpr int B_TH = B_VAL + 96;
constexpr int M_TH = B_TH + 24;
constexpr int NBAR = (M_TH - B_EMPTY) / 8;
constexpr int M_KEY = M_TH + 12;
constexpr int M_PAR = M_KEY + 4;
constexpr int M_ROLE = M_PAR + 4;
constexpr int M_HX = OFF_MISC + 544;
constexpr int M_G = M_HX + 256;
constexpr int M_UPD = M_G + 512;
constexpr int M_RED = M_UPD + 512;
constexpr int SMEM_BYTES = 232448;
static_assert(M_RED + 512 <= SMEM_BYTES && M_ROLE + 4 <= M_HX, "smem");

struct Params {
    const bf16 *gate_w, *w_r, *dre, *dim;
    CUtensorMap mCre, mCim, mX2, mX, mDre, mDim, mF, mWg, mWu, mWd;
};

struct CPtr { const char* c[2]; };

struct Scratch {
    uint32_t frag[NCTA * 2 * 4096];
    uint32_t stamp[NCTA * 32];
    uint32_t gate[S_];
    uint32_t keys[8 * NCTA];
    uint32_t part[FFN_CTAS / 2 * D_];
    uint32_t phint[4 * 8 * 8];
    uint32_t upd[D_];
    uint32_t epoch[NCTA + 4];
};
__device__ __align__(1024) Scratch g_scr;

__device__ __forceinline__ uint32_t smem_u32(const void* p) { return (uint32_t)__cvta_generic_to_shared(p); }
__device__ __forceinline__ void mbar_init(uint32_t bar, uint32_t cnt) {
    asm volatile("mbarrier.init.shared::cta.b64 [%0], %1;" ::"r"(bar), "r"(cnt) : "memory");
}
__device__ __forceinline__ void mbar_expect_tx(uint32_t bar, uint32_t bytes) {
    asm volatile("mbarrier.arrive.expect_tx.shared::cta.b64 _, [%0], %1;" ::"r"(bar), "r"(bytes) : "memory");
}
__device__ __forceinline__ void mbar_arrive(uint32_t bar) {
    asm volatile("mbarrier.arrive.shared::cta.b64 _, [%0];" ::"r"(bar) : "memory");
}
template <int N>
__device__ __forceinline__ void mbar_arrive_n_if(uint32_t bar, bool pred) {
    asm volatile("{.reg .pred p; setp.ne.b32 p, %1, 0; @p mbarrier.arrive.shared::cta.b64 _, [%0], %2;}" ::"r"(bar), "r"((int)pred), "n"(N) : "memory");
}
__device__ __forceinline__ void mbar_arrive_if(uint32_t bar, bool pred) {
    asm volatile("{.reg .pred p; setp.ne.b32 p, %1, 0; @p mbarrier.arrive.shared::cta.b64 _, [%0];}" ::"r"(bar), "r"((int)pred) : "memory");
}
__device__ __forceinline__ void mbar_arrive_warp(uint32_t bar) {
    __syncwarp();
    mbar_arrive_if(bar, (threadIdx.x & 31) == 0);
}
__device__ __forceinline__ void mbar_arrive_cluster_if(uint32_t bar, bool pred) {
    asm volatile("{.reg .pred p; setp.ne.b32 p, %1, 0; @p mbarrier.arrive.shared::cluster.b64 _, [%0], 1;}"
                 ::"r"(bar), "r"((int)pred) : "memory");
}
__device__ __forceinline__ uint32_t mapa(uint32_t a, uint32_t cta) {
    uint32_t r;
    asm volatile("mapa.shared::cluster.u32 %0, %1, %2;" : "=r"(r) : "r"(a), "r"(cta));
    return r;
}
__device__ __forceinline__ bool mbar_try(uint32_t bar, uint32_t parity) {
    uint32_t ok;
    asm volatile("{.reg .pred p; mbarrier.try_wait.parity.shared::cta.b64 p, [%1], %2; selp.u32 %0,1,0,p;}"
                 : "=r"(ok) : "r"(bar), "r"(parity) : "memory");
    return ok;
}
__device__ __forceinline__ bool mbar_test(uint32_t bar, uint32_t parity) {
    uint32_t ok;
    asm volatile("{.reg .pred p; mbarrier.test_wait.parity.shared::cta.b64 p, [%1], %2; selp.u32 %0,1,0,p;}"
                 : "=r"(ok) : "r"(bar), "r"(parity) : "memory");
    return ok;
}
__device__ __forceinline__ void mbar_wait(uint32_t bar, uint32_t parity) {
    uint32_t n = 0;
#pragma unroll 1
    while (!mbar_try(bar, parity)) { if (++n > SPIN_LIMIT) __trap(); }
}
__device__ __forceinline__ void mbar_wait_mma(uint32_t bar, uint32_t parity) {
    uint32_t n = 0;
#pragma unroll 1
    while (!mbar_try(bar, parity)) { if (++n > 2 * SPIN_LIMIT) break; }
}
__device__ __forceinline__ void tma2d_elect(uint32_t dst, const CUtensorMap* m, int c0, int c1, uint32_t bar) {
    asm volatile("{.reg .pred p; elect.sync _|p, 0xffffffff;"
                 " @p cp.async.bulk.tensor.2d.shared::cluster.global.mbarrier::complete_tx::bytes [%0], [%1, {%3,%4}], [%2];}"
                 ::"r"(dst), "l"(m), "r"(bar), "r"(c0), "r"(c1) : "memory");
}
__device__ __forceinline__ void tma2d_pair_elect(uint32_t dst, const CUtensorMap* m, int c0, int c1, uint32_t bar) {
    asm volatile("{.reg .pred p; elect.sync _|p, 0xffffffff;"
                 " @p cp.async.bulk.tensor.2d.shared::cluster.global.mbarrier::complete_tx::bytes.multicast::cluster"
                 " [%0], [%1, {%3,%4}], [%2], %5;}" ::"r"(dst), "l"(m), "r"(bar), "r"(c0), "r"(c1), "h"((uint16_t)3) : "memory");
}
__device__ __forceinline__ void tma3d_elect(uint32_t dst, const CUtensorMap* m, int row, int chunk, uint32_t bar) {
    asm volatile("{.reg .pred p; elect.sync _|p, 0xffffffff;"
                 " @p cp.async.bulk.tensor.3d.shared::cluster.global.mbarrier::complete_tx::bytes [%0], [%1, {%3,%4,%5}], [%2];}"
                 ::"r"(dst), "l"(m), "r"(bar), "r"(0), "r"(row), "r"(chunk) : "memory");
}
__device__ __forceinline__ void tma5d_elect(uint32_t dst, const CUtensorMap* m, int c0, int c4, uint32_t bar) {
    asm volatile("{.reg .pred p; elect.sync _|p, 0xffffffff;"
                 " @p cp.async.bulk.tensor.5d.shared::cluster.global.mbarrier::complete_tx::bytes [%0], [%1, {%3,%5,%5,%5,%4}], [%2];}"
                 ::"r"(dst), "l"(m), "r"(bar), "r"(c0), "r"(c4), "r"(0) : "memory");
}
__device__ __forceinline__ void mbar_expect_tx_elect(uint32_t bar, uint32_t bytes) {
    asm volatile("{.reg .pred p; elect.sync _|p, 0xffffffff; @p mbarrier.arrive.expect_tx.shared::cta.b64 _, [%0], %1;}"
                 ::"r"(bar), "r"(bytes) : "memory");
}
__device__ __forceinline__ void prefetch_l2(const void* p) { asm volatile("prefetch.global.L2 [%0];" ::"l"(p)); }
__device__ __forceinline__ uint32_t ld_relaxed(const void* p) {
    uint32_t v;
    asm volatile("ld.relaxed.gpu.global.u32 %0, [%1];" : "=r"(v) : "l"(p) : "memory");
    return v;
}
__device__ __forceinline__ uint4 ld_relaxed4(const void* p) {
    uint4 v;
    asm volatile("ld.relaxed.gpu.global.v4.u32 {%0,%1,%2,%3}, [%4];" : "=r"(v.x), "=r"(v.y), "=r"(v.z), "=r"(v.w) : "l"(p) : "memory");
    return v;
}
__device__ __forceinline__ void st_relaxed(unsigned int* p, uint32_t v) {
    asm volatile("st.relaxed.gpu.global.u32 [%0], %1;" ::"l"(p), "r"(v) : "memory");
}
__device__ __forceinline__ uint32_t tagf(float v, uint32_t par) { return (__float_as_uint(v) & ~1u) | par; }
template <int BIT = 0>
__device__ __forceinline__ uint4 wait_tags(const unsigned int* p, uint32_t par) {
    uint32_t n = 0;
#pragma unroll 1
    while (true) {
        const uint4 v = ld_relaxed4(p);
        const uint32_t m = par ? (v.x & v.y & v.z & v.w) : ~(v.x | v.y | v.z | v.w);
        if (__all_sync(0xffffffffu, (m >> BIT) & 1u)) return v;
        __nanosleep(100);
        if (++n > SPIN_LIMIT) __trap();
    }
}
__device__ __forceinline__ uint32_t best_key(const uint32_t* keys, uint32_t par) {
    const uint4 k = wait_tags<15>(keys + (threadIdx.x & 31) * 4, par);
    return __reduce_max_sync(0xffffffffu, max(max(k.x, k.y), max(k.z, k.w)));
}
__device__ __forceinline__ void named_bar(int id, int n) { asm volatile("bar.sync %0, %1;" ::"r"(id), "r"(n) : "memory"); }
template <int OFF>
__device__ __forceinline__ uint4 ldg_nc_off(const void* p) {
    uint4 v;
    asm volatile("ld.global.nc.v4.u32 {%0,%1,%2,%3}, [%4+%5];" : "=r"(v.x), "=r"(v.y), "=r"(v.z), "=r"(v.w) : "l"(p), "n"(OFF));
    return v;
}
__device__ __forceinline__ void ldg_nc_if(uint4& v, const void* a, bool pred) {
    asm volatile("{.reg .pred p; setp.ne.b32 p, %5, 0; @p ld.global.nc.v4.u32 {%0,%1,%2,%3}, [%4];}"
                 : "+r"(v.x), "+r"(v.y), "+r"(v.z), "+r"(v.w) : "l"(a), "r"((int)pred) : "memory");
}
template <int OFF>
__device__ __forceinline__ void stg_off(void* p, const uint4& v) {
    asm volatile("st.global.v4.u32 [%0+%5], {%1,%2,%3,%4};" ::"l"(p), "r"(v.x), "r"(v.y), "r"(v.z), "r"(v.w), "n"(OFF) : "memory");
}
__device__ __forceinline__ void sts128(uint32_t a, const uint4& v) {
    asm volatile("st.shared.v4.u32 [%0], {%1,%2,%3,%4};" ::"r"(a), "r"(v.x), "r"(v.y), "r"(v.z), "r"(v.w) : "memory");
}
__device__ __forceinline__ uint4 lds128(uint32_t a) {
    uint4 v;
    asm volatile("ld.shared.v4.u32 {%0,%1,%2,%3}, [%4];" : "=r"(v.x), "=r"(v.y), "=r"(v.z), "=r"(v.w) : "r"(a) : "memory");
    return v;
}
__device__ __forceinline__ void lds128_if(uint4& v, uint32_t a, bool pred) {
    asm volatile("{.reg .pred p; setp.ne.b32 p, %5, 0; @p ld.shared.v4.u32 {%0,%1,%2,%3}, [%4];}"
                 : "+r"(v.x), "+r"(v.y), "+r"(v.z), "+r"(v.w) : "r"(a), "r"((int)pred) : "memory");
}
__device__ __forceinline__ uint32_t lds32(uint32_t a) {
    uint32_t v;
    asm volatile("ld.shared.u32 %0, [%1];" : "=r"(v) : "r"(a) : "memory");
    return v;
}
__device__ __forceinline__ void st_async16(uint32_t dst, uint32_t x, uint32_t y, uint32_t z, uint32_t w, uint32_t bar) {
    asm volatile("st.async.weak.shared::cluster.mbarrier::complete_tx::bytes.v4.b32 [%0], {%1,%2,%3,%4}, [%5];"
                 ::"r"(dst), "r"(x), "r"(y), "r"(z), "r"(w), "r"(bar) : "memory");
}
__device__ __forceinline__ int sel(int a, int b, bool p) {
    int r;
    asm("{.reg .pred q; setp.ne.b32 q, %3, 0; selp.b32 %0, %1, %2, q;}" : "=r"(r) : "r"(a), "r"(b), "r"((int)p));
    return r;
}
__device__ __forceinline__ float selpf(float a, float b, bool p) {
    float r;
    asm("{.reg .pred q; setp.ne.b32 q, %3, 0; selp.f32 %0, %1, %2, q;}" : "=f"(r) : "f"(a), "f"(b), "r"((int)p));
    return r;
}
template <int N, int MASK, int SZ>
__device__ __forceinline__ void halve(float (&a)[SZ]) {
    const bool up = threadIdx.x & MASK;
#pragma unroll
    for (int j = 0; j < N; j++) a[j] = selpf(a[N + j], a[j], up) + __shfl_xor_sync(0xffffffffu, selpf(a[j], a[N + j], up), MASK);
}
__device__ __forceinline__ float bflo(uint32_t u) { return __uint_as_float(u << 16); }
__device__ __forceinline__ float bfhi(uint32_t u) { return __uint_as_float(u & 0xffff0000u); }
__device__ __forceinline__ uint32_t pack_bf16(float lo, float hi) {
    uint32_t r;
    asm("cvt.rn.bf16x2.f32 %0, %1, %2;" : "=r"(r) : "f"(hi), "f"(lo));
    return r;
}
__device__ __forceinline__ uint32_t hmul2_bf16(uint32_t a, uint32_t b) {
    uint32_t r;
    asm("mul.rn.bf16x2 %0, %1, %2;" : "=r"(r) : "r"(a), "r"(b));
    return r;
}
__device__ __forceinline__ float sigmoidf_(float v) { return 1.0f / (1.0f + __expf(-v)); }
__device__ __forceinline__ void wg_fence() { asm volatile("wgmma.fence.sync.aligned;" ::: "memory"); }
__device__ __forceinline__ void wg_commit() { asm volatile("wgmma.commit_group.sync.aligned;" ::: "memory"); }
template <int N> __device__ __forceinline__ void wg_wait() { asm volatile("wgmma.wait_group.sync.aligned %0;" ::"n"(N) : "memory"); }
__device__ __forceinline__ uint64_t desc_lo(uint32_t lo) { return (uint64_t)lo | (0x40000040ull << 32); }
template <int LO, int HI, int N>
__device__ __forceinline__ void fence_regs(float (&d)[N]) {
#pragma unroll
    for (int i = LO; i < HI; i++) asm volatile("" : "+f"(d[i])::"memory");
}
template <int LO, int HI, int N>
__device__ __forceinline__ void keep_regs(uint4 (&f)[N]) {
#pragma unroll
    for (int i = LO; i < HI; i++) asm volatile("" ::"r"(f[i].x), "r"(f[i].y), "r"(f[i].z), "r"(f[i].w) : "memory");
}
template <int TB = 1>
__device__ __forceinline__ void wgmma128(float (&d)[64], uint64_t da, uint64_t db, int scaleD) {
    asm volatile(
        "{ .reg .pred p; setp.ne.b32 p, %66, 0;\n"
        "wgmma.mma_async.sync.aligned.m64n128k16.f32.bf16.bf16 "
        "{%0,%1,%2,%3,%4,%5,%6,%7,%8,%9,%10,%11,%12,%13,%14,%15,%16,%17,%18,%19,%20,%21,%22,%23,%24,%25,%26,%27,%28,%29,%30,%31,"
        "%32,%33,%34,%35,%36,%37,%38,%39,%40,%41,%42,%43,%44,%45,%46,%47,%48,%49,%50,%51,%52,%53,%54,%55,%56,%57,%58,%59,%60,%61,%62,%63}, "
        "%64, %65, p, 1, 1, 0, %67;\n}"
        : "+f"(d[0]), "+f"(d[1]), "+f"(d[2]), "+f"(d[3]), "+f"(d[4]), "+f"(d[5]), "+f"(d[6]), "+f"(d[7]),
          "+f"(d[8]), "+f"(d[9]), "+f"(d[10]), "+f"(d[11]), "+f"(d[12]), "+f"(d[13]), "+f"(d[14]), "+f"(d[15]),
          "+f"(d[16]), "+f"(d[17]), "+f"(d[18]), "+f"(d[19]), "+f"(d[20]), "+f"(d[21]), "+f"(d[22]), "+f"(d[23]),
          "+f"(d[24]), "+f"(d[25]), "+f"(d[26]), "+f"(d[27]), "+f"(d[28]), "+f"(d[29]), "+f"(d[30]), "+f"(d[31]),
          "+f"(d[32]), "+f"(d[33]), "+f"(d[34]), "+f"(d[35]), "+f"(d[36]), "+f"(d[37]), "+f"(d[38]), "+f"(d[39]),
          "+f"(d[40]), "+f"(d[41]), "+f"(d[42]), "+f"(d[43]), "+f"(d[44]), "+f"(d[45]), "+f"(d[46]), "+f"(d[47]),
          "+f"(d[48]), "+f"(d[49]), "+f"(d[50]), "+f"(d[51]), "+f"(d[52]), "+f"(d[53]), "+f"(d[54]), "+f"(d[55]),
          "+f"(d[56]), "+f"(d[57]), "+f"(d[58]), "+f"(d[59]), "+f"(d[60]), "+f"(d[61]), "+f"(d[62]), "+f"(d[63])
        : "l"(da), "l"(db), "r"(scaleD), "n"(TB));
}
__device__ __forceinline__ void wgmma128rs(float (&d)[64], const uint4& a, uint64_t db, int scaleD) {
    asm volatile(
        "{ .reg .pred p; setp.ne.b32 p, %69, 0;\n"
        "wgmma.mma_async.sync.aligned.m64n128k16.f32.bf16.bf16 "
        "{%0,%1,%2,%3,%4,%5,%6,%7,%8,%9,%10,%11,%12,%13,%14,%15,%16,%17,%18,%19,%20,%21,%22,%23,%24,%25,%26,%27,%28,%29,%30,%31,"
        "%32,%33,%34,%35,%36,%37,%38,%39,%40,%41,%42,%43,%44,%45,%46,%47,%48,%49,%50,%51,%52,%53,%54,%55,%56,%57,%58,%59,%60,%61,%62,%63}, "
        "{%64,%65,%66,%67}, %68, p, 1, 1, 0;\n}"
        : "+f"(d[0]), "+f"(d[1]), "+f"(d[2]), "+f"(d[3]), "+f"(d[4]), "+f"(d[5]), "+f"(d[6]), "+f"(d[7]),
          "+f"(d[8]), "+f"(d[9]), "+f"(d[10]), "+f"(d[11]), "+f"(d[12]), "+f"(d[13]), "+f"(d[14]), "+f"(d[15]),
          "+f"(d[16]), "+f"(d[17]), "+f"(d[18]), "+f"(d[19]), "+f"(d[20]), "+f"(d[21]), "+f"(d[22]), "+f"(d[23]),
          "+f"(d[24]), "+f"(d[25]), "+f"(d[26]), "+f"(d[27]), "+f"(d[28]), "+f"(d[29]), "+f"(d[30]), "+f"(d[31]),
          "+f"(d[32]), "+f"(d[33]), "+f"(d[34]), "+f"(d[35]), "+f"(d[36]), "+f"(d[37]), "+f"(d[38]), "+f"(d[39]),
          "+f"(d[40]), "+f"(d[41]), "+f"(d[42]), "+f"(d[43]), "+f"(d[44]), "+f"(d[45]), "+f"(d[46]), "+f"(d[47]),
          "+f"(d[48]), "+f"(d[49]), "+f"(d[50]), "+f"(d[51]), "+f"(d[52]), "+f"(d[53]), "+f"(d[54]), "+f"(d[55]),
          "+f"(d[56]), "+f"(d[57]), "+f"(d[58]), "+f"(d[59]), "+f"(d[60]), "+f"(d[61]), "+f"(d[62]), "+f"(d[63])
        : "r"(a.x), "r"(a.y), "r"(a.z), "r"(a.w), "l"(db), "r"(scaleD));
}
__device__ __forceinline__ uint32_t clk() { uint64_t c; asm volatile("mov.u64 %0, %%clock64;" : "=l"(c)::"memory"); return (uint32_t)c; }
__device__ __forceinline__ uint32_t gtime() { uint64_t t; asm volatile("mov.u64 %0, %%globaltimer;" : "=l"(t)::"memory"); return (uint32_t)t; }
__device__ __forceinline__ void until(uint32_t t) { while (t - clk() < 0x8000u) {} }
__device__ __forceinline__ void nap_until(uint32_t t) { while (t - clk() < 0x8000u) __nanosleep(20); }
__device__ __forceinline__ uint4 scale_add(float s, const float (&a)[64], int o, const uint4& w) {
    return make_uint4(pack_bf16(fmaf(s, a[o], bflo(w.x)), fmaf(s, a[o + 1], bfhi(w.x))), pack_bf16(fmaf(s, a[o + 4], bflo(w.y)), fmaf(s, a[o + 5], bfhi(w.y))),
                      pack_bf16(fmaf(s, a[o + 8], bflo(w.z)), fmaf(s, a[o + 9], bfhi(w.z))), pack_bf16(fmaf(s, a[o + 12], bflo(w.w)), fmaf(s, a[o + 13], bfhi(w.w))));
}

__device__ __forceinline__ uint32_t router_key(float score, int row) {
    const float r = score + 0.0f;
    uint32_t u = pack_bf16(r, 0.f) & 0xffffu;
    u = (u & 0x8000u) ? (~u & 0xffffu) : (u | 0x8000u);
    if (r != r) u = 0;
    return (u << 16) | (uint32_t)(0x7fff - row);
}

#define g_ab g_scr.frag
#define g_fb_h ((float*)g_scr.part)
#define g_fb_upd (g_fb_h + 2048)
#define g_fb_gate (g_fb_h + 4096)
#define g_fb_keys (g_scr.part + 8192)
__global__ void fb_hidden(const bf16* x, const bf16* dre, const bf16* dim, const bf16* gw, const bf16* wr) {
    __shared__ float xs[D_];
    const int s = blockIdx.x, t = threadIdx.x;
    xs[t] = __bfloat162float(x[s * D_ + t]);
    __syncthreads();
    float a = 0.f, b = 0.f;
    for (int d = 0; d < D_; d++) { a = fmaf(xs[d], __bfloat162float(dre[t * D_ + d]), a); b = fmaf(xs[d], __bfloat162float(dim[t * D_ + d]), b); }
    ((bf16*)g_ab)[s * 1024 + t] = __float2bfloat16(a);
    ((bf16*)g_ab)[s * 1024 + 512 + t] = __float2bfloat16(b);
    if (t == 0) {
        float u = 0.f, v = 0.f;
        for (int d = 0; d < D_; d++) { u += bfhi(pack_bf16(0.f, xs[d] * __bfloat162float(gw[d]))); v = fmaf(xs[d], __bfloat162float(wr[d]), v); }
        g_fb_gate[s] = bfhi(pack_bf16(0.f, sigmoidf_(bfhi(pack_bf16(0.f, u)))));
        g_fb_keys[s] = router_key(v, s);
    }
}
__device__ uint32_t fb_best() {
    uint32_t k = 0;
    for (int i = 0; i < S_; i++) k = max(k, g_fb_keys[i]);
    return k;
}
__global__ void fb_ffn1(const bf16* x, const bf16* wg, const bf16* wu) {
    const int f = blockIdx.x * blockDim.x + threadIdx.x, idx = 0x7fff - (int)(fb_best() & 0x7fffu);
    float a = 0.f, b = 0.f;
    for (int d = 0; d < D_; d++) {
        const float xv = __bfloat162float(x[idx * D_ + d]);
        a = fmaf(xv, __bfloat162float(wg[d * F_ + f]), a); b = fmaf(xv, __bfloat162float(wu[d * F_ + f]), b);
    }
    g_fb_h[f] = a * sigmoidf_(a) * b;
}
__global__ void fb_ffn2(const bf16* wd) {
    const int e = blockIdx.x * blockDim.x + threadIdx.x;
    const uint32_t u = fb_best() >> 16, rb = (u & 0x8000u) ? (u & 0x7fffu) : (~u & 0xffffu);
    float a = 0.f;
    for (int f = 0; f < F_; f++) a = fmaf(g_fb_h[f], __bfloat162float(wd[f * D_ + e]), a);
    g_fb_upd[e] = a * sigmoidf_(__uint_as_float(rb << 16));
}
__global__ void fb_seq(const bf16* x, const bf16* cre, const bf16* cim, bf16* out) {
    __shared__ float c[2][S_];
    __shared__ int idx;
    const int t = blockIdx.x, e = threadIdx.x;
    for (int i = e; i < S_; i += D_) { c[0][i] = __bfloat162float(cre[t * S_ + i]); c[1][i] = __bfloat162float(cim[t * S_ + i]); }
    if (e == 0) idx = 0x7fff - (int)(fb_best() & 0x7fffu);
    __syncthreads();
    float y = 0.f;
    for (int s = 0; s < S_; s++)
        y += c[0][s] * __bfloat162float(((const bf16*)g_ab)[s * 1024 + e]) - c[1][s] * __bfloat162float(((const bf16*)g_ab)[s * 1024 + 512 + e]);
    const float g = g_fb_gate[t];
    out[t * D_ + e] = __float2bfloat16(g * y + (1.f - g) * (__bfloat162float(x[t * D_ + e]) + (t == idx ? g_fb_upd[e] : 0.f)));
}

__device__ __forceinline__ void spare_job(const Params& p, Scratch* g, unsigned char* smem, int sp, uint32_t tstart) {
    const int tid = threadIdx.x, warp = tid >> 5, lane = tid & 31;
    if (warp >= 8) {
#pragma unroll 1
        for (int i = 0; i < 16; i++) {
            nap_until(tstart + PFD_T0 + i * (PFD_DT / 2));
            prefetch_l2((const char*)((sp & 2) ? p.dim : p.dre) + (sp & 1) * 262144 + i * 16384 + (tid - 256) * 128);
        }
        return;
    }
    named_bar(2, 288);
    mbar_wait(smem_u32(smem) + B_FULL, 0);
    nap_until(tstart + SUM_T0 - 2000);
    const uint32_t e1 = ld_relaxed(g->epoch + NCTA + sp) + 1u, par = e1 & 1u;
    const uint32_t u = best_key(g->keys + warp * NCTA, par) >> 16;
    const float rs = sigmoidf_(__uint_as_float(((u & 0x8000u) ? (u & 0x7fffu) : (~u & 0xffffu)) << 16));
    nap_until(tstart + SUM_T0);
    uint32_t n = 0;
#pragma unroll 1
    while ((int)(ld_relaxed(g->phint + (sp * 8 + warp) * 8) - e1 * 14u) < 0) {
        __nanosleep(40);
        if (++n > SPIN_LIMIT) __trap();
    }
    const unsigned int* src = g->part + warp * 7 * D_ + sp * 128 + lane * 4;
    uint4 v[7];
#pragma unroll 1
    while (true) {
        uint32_t bad = 0;
#pragma unroll
        for (int i = 0; i < 7; i++) v[i] = ld_relaxed4(src + i * D_);
#pragma unroll
        for (int i = 0; i < 7; i++) bad |= (v[i].x ^ par) | (v[i].y ^ par) | (v[i].z ^ par) | (v[i].w ^ par);
        if (!__any_sync(0xffffffffu, bad & 1u)) break;
        if (++n > SPIN_LIMIT) __trap();
    }
    float4 s = make_float4(0.f, 0.f, 0.f, 0.f);
#pragma unroll
    for (int i = 0; i < 7; i++) {
        s.x += __uint_as_float(v[i].x); s.y += __uint_as_float(v[i].y);
        s.z += __uint_as_float(v[i].z); s.w += __uint_as_float(v[i].w);
    }
    float* acc = (float*)(smem + R6);
    *(float4*)&acc[warp * 128 + lane * 4] = s;
    named_bar(1, 256);
    if (tid < 128) {
        float t = 0.f;
#pragma unroll
        for (int i = 0; i < 8; i++) t += acc[i * 128 + tid];
        st_relaxed(&g->upd[sp * 128 + tid], tagf(t * rs, par));
        if (tid == 0) st_relaxed(g->epoch + NCTA + sp, e1);
    }
}

__device__ __forceinline__ int ffn_pair(int role) { return role - __popcll(NOFFN_MASK & ((1ull << role) - 1)); }
__device__ __forceinline__ int other(int i, int tn) { return i + (i >= tn); }
__device__ __forceinline__ int dcol(int p, int tn) { return p < 2 ? tn * 128 + p * 64 : other((p - 2) % 3, tn) * 128 + (p >= 5 ? 64 : 0); }

template <int H>
__device__ __forceinline__ void fetch_job(const Params& p, Scratch* g, unsigned char* smem, uint32_t sb, int cta, int i, uint32_t par) {
    const int lane = threadIdx.x & 31, comp = cta & 1;
    const int j = other(i, (cta >> 1) & 3), src = (cta & ~6) + 2 * j;
    const int slot = i == 0 ? 29 % NST : i - 1;
    const uint32_t land = sb + B_LAND + 8 * (3 * H + i);
    uint32_t ph = 0, th;
    mbar_expect_tx_elect(land, 8192);
    if (H == 0) {
        mbar_wait(sb + B_S0, 0);
        const uint32_t t0 = clk();
        if (i == 0) {
            mbar_wait(sb + B_FULL + 8 * (31 % NST), (31 / NST) & 1);
            const uint32_t t1 = t0 + max(clk() - t0, 180u) - 180u;
            asm volatile("{.reg .pred p; .reg .b64 t; setp.eq.b32 p, %3, 0; mov.b64 t, {%1, %2}; @p st.relaxed.gpu.global.b64 [%0], t;}"
                         ::"l"(g->stamp + cta * 32), "r"((t1 & ~1u) | par), "r"(gtime()), "r"(lane) : "memory");
        }
        until(t0 + SDEL);
        uint32_t gt;
#pragma unroll 1
        for (uint32_t n = 0;; n++) {
            asm volatile("{.reg .b64 t; ld.relaxed.gpu.global.b64 t, [%2]; mov.b64 {%0,%1}, t;}" : "=r"(th), "=r"(gt) : "l"(g->stamp + src * 32) : "memory");
            if (!__any_sync(0xffffffffu, (th ^ par) & 1u)) break;
            if (n > SPIN_LIMIT) __trap();
        }
        const uint32_t ns = min(gtime() - gt, 4096u), now = clk();
        if (now - th >= 8192u) th = now - (ns + (ns >> 1) + (ns >> 4));
        th += SG * j;
        if (lane == 0) { *(volatile uint32_t*)(smem + M_TH + 4 * i) = th; mbar_arrive(sb + B_TH + 8 * i); }
        __syncwarp();
    } else {
        mbar_wait(sb + B_TH + 8 * i, 0);
        th = lds32(sb + M_TH + 4 * i);
    }
    mbar_wait(sb + B_EA, 0);
#pragma unroll 1
    for (int c = 0; c < 2; c++) {
        const uint32_t dst = sb + slot * 16384 + (c ? NST * 16384 + H * 8192 : (comp ^ H) * 8192);
        if (c != H) mbar_wait(sb + B_EMPTY + 8 * slot, i != 0);
        until(th + (c ? (H ? L_RD1 : L_RD0) : (H ? E_RD1 : E_RD0)));
#pragma unroll 1
        for (uint32_t r = 0;; r++) {
            tma2d_elect(dst, &p.mF, 0, (src * 2 + (comp ^ c)) * 128 + H * 64, land);
            mbar_wait(land, ph);
            ph ^= 1;
            const uint32_t a = dst + (lane >> 2) * 132 + (lane & 3) * 32;
            uint32_t v[8], m0 = 0, m1 = ~0u;
#pragma unroll
            for (int k = 0; k < 8; k++) v[k] = lds32(a + k * 1024);
#pragma unroll
            for (int k = 0; k < 8; k++) { m0 |= v[k]; m1 &= v[k]; }
            if (__all_sync(0xffffffffu, (par ? m1 : ~m0) & 1u)) break;
            if (r > SPIN_LIMIT) __trap();
            mbar_expect_tx_elect(land, 8192);
        }
        mbar_arrive_if(sb + B_VAL + 8 * (6 * c + 3 * H + i), lane == 0);
        if (c == 0) mbar_expect_tx_elect(land, 8192);
    }
}

__global__ void __cluster_dims__(2, 1, 1) __launch_bounds__(NTHREADS, 1)
fused_kernel(const __grid_constant__ CPtr pc, const char* px, char* pout, Scratch* g, const __grid_constant__ Params p) {
    extern __shared__ __align__(1024) unsigned char smem[];
    const uint32_t sb = smem_u32(smem);
    const int tid = threadIdx.x, warp = tid >> 5, lane = tid & 31;
    const int rank = blockIdx.x & 1;
    const char* pcr = pc.c[rank];
    asm volatile("{.reg .pred p; setp.lt.u32 p, %1, 32; @p prefetch.global.L2 [%0];}"
                 ::"l"(pcr + (uint32_t)(((blockIdx.x << 16) & 0x7e0000) + (tid << 12))), "r"(tid));
    const uint32_t tstart = clk();
    asm volatile("{.reg .pred p; setp.lt.u32 p, %1, 4; @p prefetch.global.L2 [%0];}"
                 ::"l"(px + (uint32_t)(((blockIdx.x << 9) & 0xfe00) + (tid << 7))), "r"(tid));
    uint32_t smid;
    asm volatile("mov.u32 %0, %%smid;" : "=r"(smid));
    const int u = smid >> 1;
    const int code = sel(u, sel(((u - 32) * 293) >> 8, 8 * u - 489, u < 60), u < 32);
    const int tn = code >> 3, tm = (code & 7) + sel(0, 8, u < 32);
    const int comp = rank;
    const CUtensorMap* mC = &p.mCre + comp;
#define ARM(j) do { mbar_init(sb + B_FULL + 8 * (j), 1); mbar_expect_tx(sb + B_FULL + 8 * (j), 32768); } while (0)
#define STEP0(j) do { tma2d_elect(sb + (j) * 16384, mC, (j) * 64, tm * 128, sb + B_FULL + 8 * (j));                            \
                      tma3d_elect(sb + (NST + (j)) * 16384, &p.mX2, (j) * 64, tn * 2, sb + B_FULL + 8 * (j)); } while (0)
    if (__all_sync(0xffffffffu, warp == 12)) {
        asm volatile("{.reg .pred p; elect.sync _|p, 0xffffffff; @p mbarrier.init.shared::cta.b64 [%0], 1;}" ::"r"(sb + B_FULL) : "memory");
        STEP0(0);
        mbar_expect_tx_elect(sb + B_FULL, 32768);
        asm volatile("bar.arrive 2, 288;" ::: "memory");
    }
    const bool spare = tn < 0;
    const int role = tm * 4 + tn, cta = role * 2 + rank;
    const int wu = __shfl_sync(0xffffffffu, warp, 0);
    if (wu < 12) {
        if (lane == 0) {
            mbar_init(sb + B_EMPTY + 8 * wu, 2);
            mbar_init(sb + B_VD + 8 * wu, wu ? 1 : 4);
#pragma unroll
            for (int i = 24; i < NBAR; i += 12) if (i + 12 <= NBAR || wu < NBAR - i) mbar_init(sb + B_EMPTY + 8 * (i + wu), 1);
            if (wu >= 1 && wu < 4) mbar_expect_tx(sb + B_VD + 8 * wu, wu < 3 ? 8192 : 256);
        }
        asm volatile("fence.mbarrier_init.release.cluster;" ::: "memory");
        __syncwarp();
        asm volatile("barrier.cluster.arrive.relaxed.aligned;" ::: "memory");
        if (spare) {
            spare_job(p, g, smem, smid & 3, tstart);
        } else if (wu >= 8) {
            asm volatile("setmaxnreg.dec.sync.aligned.u32 " STR(RS_) ";");
            asm volatile("barrier.cluster.wait.acquire.aligned;" ::: "memory");
            const int t = tid - 256, w = wu - 8, fr = ffn_pair(role);
            const bool ffn = !((NOFFN_MASK >> role) & 1);
            nap_until(tstart + SIDE_T0);
            const uint4 gw0 = ldg_nc_off<0>(p.gate_w + lane * 8), gw1 = ldg_nc_off<512>(p.gate_w + lane * 8);
            const uint4 rw0 = ldg_nc_off<0>(p.w_r + lane * 8), rw1 = ldg_nc_off<512>(p.w_r + lane * 8);
            const uint32_t par = ~ld_relaxed(g->epoch + cta) & 1u;
            nap_until(tstart + ROUTER_T0 + (2 * w + rank) * ROUTER_DT);
            {
                const int row0 = cta * 16 + w * 4;
                const char* xp = px + (uint32_t)row0 * (D_ * 2) + lane * 16;
                uint4 xa[4], xb[4];
                xa[0] = ldg_nc_off<0>(xp);    xb[0] = ldg_nc_off<512>(xp);  xa[1] = ldg_nc_off<1024>(xp); xb[1] = ldg_nc_off<1536>(xp);
                xa[2] = ldg_nc_off<2048>(xp); xb[2] = ldg_nc_off<2560>(xp); xa[3] = ldg_nc_off<3072>(xp); xb[3] = ldg_nc_off<3584>(xp);
                float a[8];
#pragma unroll
                for (int i = 0; i < 4; i++) {
                    const uint32_t xv[8] = {xa[i].x, xa[i].y, xa[i].z, xa[i].w, xb[i].x, xb[i].y, xb[i].z, xb[i].w};
                    const uint32_t gv[8] = {gw0.x, gw0.y, gw0.z, gw0.w, gw1.x, gw1.y, gw1.z, gw1.w};
                    const uint32_t rv[8] = {rw0.x, rw0.y, rw0.z, rw0.w, rw1.x, rw1.y, rw1.z, rw1.w};
                    float uu = 0.f, vv = 0.f;
#pragma unroll
                    for (int j = 0; j < 8; j++) {
                        const uint32_t pr = hmul2_bf16(xv[j], gv[j]);
                        uu += bflo(pr); uu += bfhi(pr);
                        vv = fmaf(bflo(xv[j]), bflo(rv[j]), vv); vv = fmaf(bfhi(xv[j]), bfhi(rv[j]), vv);
                    }
                    a[i] = uu; a[4 + i] = vv;
                }
                halve<4, 16>(a); halve<2, 8>(a); halve<1, 4>(a);
                {
                    const float b1 = __shfl_xor_sync(0xffffffffu, a[0], 1), b2 = __shfl_xor_sync(0xffffffffu, a[0], 2),
                                b3 = __shfl_xor_sync(0xffffffffu, a[0], 3);
                    a[0] = (a[0] + b1) + (b2 + b3);
                }
                const int row = row0 + ((lane >> 2) & 3);
                const uint32_t best = __reduce_max_sync(0xffffffffu, lane >= 16 && (lane & 3) == 0 ? router_key(a[0], row) : 0u);
                if (lane <= 16 && (lane & 3) == 0)
                    *(volatile uint32_t*)(smem + M_RED + (lane < 16 ? w * 16 + lane : 64 + w * 4)) = lane < 16 ? pack_bf16(0.f, sigmoidf_(bfhi(pack_bf16(0.f, a[0])))) | par : best;
                named_bar(1, 128);
                if (t < 8) {
                    const uint4 k = lds128(sb + M_RED + 64);
                    asm volatile("{.reg .b32 old; atom.relaxed.gpu.global.exch.b32 old, [%0], %1;}"
                                 ::"l"(g->keys + t * NCTA + cta), "r"(max(max(k.x, k.y), max(k.z, k.w)) | (par << 15)) : "memory");
                }
                if (w == 1 && lane < 16) st_relaxed(g->gate + cta * 16 + lane, lds32(sb + M_RED + lane * 4));
            }
            uint32_t vd[32];
            if (ffn) {
                mbar_wait(sb + B_FFN + 24, 0);
#pragma unroll
                for (int j = 0; j < 32; j++) vd[j] = lds32(sb + R6 + ((j >> 3) & 1) * 16384 + (2 + (j >> 4)) * 4096 + (j & 7) * 512 + t * 4);
                mbar_arrive_warp(sb + B_VD);
            }
            mbar_wait(sb + B_GATE, 0);
            const int idx = 0x7fff - (int)(*(volatile uint32_t*)(smem + M_KEY) & 0x7fffu);
            if (ffn) {
                float a[16];
#pragma unroll
                for (int i = 0; i < 16; i++) a[i] = 0.f;
#pragma unroll 1
                for (int qu = 0; qu < 4; qu++) {
                    mbar_wait(sb + B_FFN + 8 * qu, qu == 3);
#pragma unroll
                    for (int i = 2 * qu; i < 2 * qu + 2; i++) {
                        const float xs = __bfloat162float(((const bf16*)(smem + M_UPD))[32 * i + (t >> 2)]);
                        const uint4 vg = lds128(sb + R6 + i * 2048 + t * 16);
                        const uint4 vu = lds128(sb + R6 + 16384 + i * 2048 + t * 16);
                        const uint32_t g4[4] = {vg.x, vg.y, vg.z, vg.w};
                        const uint32_t u4[4] = {vu.x, vu.y, vu.z, vu.w};
#pragma unroll
                        for (int j = 0; j < 4; j++) {
                            a[2 * j] = fmaf(xs, bflo(g4[j]), a[2 * j]);         a[2 * j + 1] = fmaf(xs, bfhi(g4[j]), a[2 * j + 1]);
                            a[8 + 2 * j] = fmaf(xs, bflo(u4[j]), a[8 + 2 * j]); a[9 + 2 * j] = fmaf(xs, bfhi(u4[j]), a[9 + 2 * j]);
                        }
                    }
                }
                named_bar(1, 128);
                mbar_arrive_if(sb + B_R6, t == 0);
                halve<8, 16>(a); halve<4, 8>(a); halve<2, 4>(a);
                float* red = (float*)(smem + M_UPD);
                *(float2*)&red[w * 64 + (lane >> 4) * 32 + (lane & 3) * 8 + ((lane >> 2) & 3) * 2] = make_float2(a[0], a[1]);
                named_bar(1, 128);
                const float sg = red[lane] + red[64 + lane] + red[128 + lane] + red[192 + lane];
                const float su = red[32 + lane] + red[96 + lane] + red[160 + lane] + red[224 + lane];
                if (w < 2) {
                    asm volatile("st.async.weak.shared::cluster.mbarrier::complete_tx::bytes.f32 [%0], %1, [%2];"
                                 ::"r"(mapa(sb + M_HX + t * 4, rank ^ 1)), "f"(w ? su : sg), "r"(mapa(sb + B_HX, rank ^ 1)) : "memory");
                }
                named_bar(1, 128);
                mbar_wait(sb + B_HX, 0);
                const float pg = ((const float*)(smem + M_HX))[lane], pu = ((const float*)(smem + M_HX))[32 + lane];
                const float gs = sg + pg, us = su + pu;
                float* hrow = red + w * 32;
                hrow[lane] = gs * sigmoidf_(gs) * us;
                __syncwarp();
                float o0 = 0.f, o1 = 0.f;
#pragma unroll
                for (int j4 = 0; j4 < 8; j4++) {
                    const float4 hv = *(const float4*)&hrow[j4 * 4];
                    o0 = fmaf(hv.x, bflo(vd[4 * j4]), o0);     o1 = fmaf(hv.x, bfhi(vd[4 * j4]), o1);
                    o0 = fmaf(hv.y, bflo(vd[4 * j4 + 1]), o0); o1 = fmaf(hv.y, bfhi(vd[4 * j4 + 1]), o1);
                    o0 = fmaf(hv.z, bflo(vd[4 * j4 + 2]), o0); o1 = fmaf(hv.z, bfhi(vd[4 * j4 + 2]), o1);
                    o0 = fmaf(hv.w, bflo(vd[4 * j4 + 3]), o0); o1 = fmaf(hv.w, bfhi(vd[4 * j4 + 3]), o1);
                }
                asm volatile("st.relaxed.gpu.global.v2.u32 [%0], {%1,%2};" ::"l"(&g->part[fr * D_ + rank * 256 + t * 2]),
                             "r"(tagf(o0, par)), "r"(tagf(o1, par)) : "memory");
                if (lane == 0) asm volatile("red.relaxed.gpu.global.add.u32 [%0], 1;" ::"l"(g->phint + ((rank * 2 + (w >> 1)) * 8 + fr / 7) * 8) : "memory");
            }
            if (!ffn) mbar_arrive_if(sb + B_R6, t == 0);
            if (w < 3) {
                fetch_job<1>(p, g, smem, sb, cta, w, par);
            } else {
                if (lds32(sb + M_ROLE) != (uint32_t)role) __trap();
                if ((idx >> 6) == 2 * tm + comp) {
                    const float og = bfhi(pack_bf16(0.f, 1.f - ((const float*)(smem + M_G))[idx & 127]));
                    const uint4 u4 = wait_tags(g->upd + tn * 128 + lane * 4, par);
                    *(float4*)(smem + M_RED + lane * 16) = make_float4(og * __uint_as_float(u4.x), og * __uint_as_float(u4.y),
                                                                       og * __uint_as_float(u4.z), og * __uint_as_float(u4.w));
                    mbar_arrive_warp(sb + B_SIDE);
                }
            }
        } else {
            const int wg = wu >> 2;
            const uint32_t sbd = (sb & 0x3FFFF) >> 4;
            const bool lead = (tid & 127) == 0;
            const bool early = wg == comp;
            const int q = lane & 3;
            const int r0 = (warp & 3) * 16 + (lane >> 2);
            float acc[64];
            const uint32_t da0 = sbd + 0x10000 + wg * 512, db0 = sbd + 0x2000000, dd0 = sbd + 0x10000;
            const uint32_t rE = mapa(sb + B_EMPR, rank ^ 1);
#define WAITFULL(s) mbar_wait_mma(sb + B_FULL + 8 * ((s) % NST), ((s) / NST) & 1)
#define TESTFULL(s) mbar_test(sb + B_FULL + 8 * ((s) % NST), ((s) / NST) & 1)
#define WAITD(pos) do { if ((pos) >= 4) mbar_wait_mma(sb + B_DL + 8 * ((pos) & 3), 0); else if ((pos) >= 2) mbar_wait_mma(sb + B_D6, 0); else WAITFULL(32); } while (0)
#define MMA_A(s, kk) wgmma128(acc, desc_lo(da0 + a_addr(s) / 16 + (kk) * 2), desc_lo(db0 + b_addr(s) / 16 + (kk) * 128), 1)
            named_bar(2, 288);
            WAITFULL(0);
            wg_fence();
#pragma unroll
            for (int kk = 0; kk < 4; kk++) wgmma128(acc, desc_lo(da0 + kk * 2), desc_lo(db0 + b_addr(0) / 16 + kk * 128), kk != 0);
            wg_commit();
            asm volatile("setmaxnreg.inc.sync.aligned.u32 " STR(RC) ";");
            asm volatile("barrier.cluster.wait.acquire.aligned;" ::: "memory");
            int slot = 1, ph = 0, pslot = 0;
            const uint32_t ooff = (uint32_t)((tm * 128 + wg * 64 + r0) * D_ + tn * 128 + q * 8) * 2u;
            uint32_t* fout = g->frag + (cta * 2 + wg) * 4096 + (warp & 3) * 128 + lane;
            uint32_t tagm[4];
#pragma unroll
            for (int c = 0; c < 4; c++) tagm[c] = (lane & 7) == (warp & 1) * 4 + c;
            const char* xp = px + ooff;
            asm volatile("" : "+r"(tagm[0]), "+r"(tagm[1]), "+r"(tagm[2]), "+r"(tagm[3]), "+l"(xp), "+l"(fout));
            uint4 w[8];
#pragma unroll
            for (int i = 0; i < 8; i++) w[i] = make_uint4(0, 0, 0, 0);
#pragma unroll
            for (int part = 0; part <= XN; part++) {
                if (part) {
#pragma unroll
                    for (int i = (part - 1) * 8 / XN; i < part * 8 / XN; i++) ldg_nc_if(w[i], xp + (i & 1) * 8192 + (i >> 1) * 64, early);
                }
#pragma unroll 1
                for (int step = part ? XLD + (part - 1) * XD : 1; step < (part < XN ? XLD + part * XD : SP0); step++) {
                    mbar_wait_mma(sb + B_FULL + 8 * slot, ph);
                    const uint32_t a = da0 + slot * 1024, b = db0 + b_addr(0) / 16 + slot * 1024;
                    wg_fence();
                    wgmma128(acc, desc_lo(a), desc_lo(b), 1);
                    wg_commit();
                    wg_wait<1>();
                    mbar_arrive_if(sb + B_EMPTY + 8 * pslot, lead);
                    mbar_arrive_cluster_if(rE + 8 * pslot, lead);
                    pslot = slot;
                    if (++slot == NST) { slot = 0; ph ^= 1; }
                    wg_fence();
#pragma unroll
                    for (int kk = 1; kk < 4; kk++) wgmma128(acc, desc_lo(a + kk * 2), desc_lo(b + kk * 128), 1);
                    wg_commit();
                }
            }
            uint32_t par;
            float g0, g1;
#define GATES() do { par = lds32(sb + M_PAR); g0 = __uint_as_float(lds32(sb + M_G + (wg * 64 + r0) * 4)); g1 = __uint_as_float(lds32(sb + M_G + (wg * 64 + r0 + 8) * 4)); } while (0)
            if (early) {
                WAITFULL(SP0);
                wg_fence();
                MMA_A(SP0, 0); MMA_A(SP0, 1);
                wg_commit();
                wg_wait<1>();
                mbar_arrive_if(sb + B_EMPTY + 8 * ((SP0 - 1) % NST), lead);
                bool ok = TESTFULL(SP0 + 1);
                MMA_A(SP0, 2); MMA_A(SP0, 3);
                wg_commit();
#pragma unroll
                for (int s = SP0 + 1; s < 32; s++) {
                    if (!ok) { WAITFULL(s); if (s == 29) mbar_wait_mma(sb + B_GATE, 0); }
                    wg_fence();
                    MMA_A(s, 0); MMA_A(s, 1);
                    if (s == 29) GATES();
                    if (s >= 30) { wg_commit(); wg_wait<1>(); mbar_arrive_if(sb + (s == 30 ? B_S0 : B_S1), lead); wg_fence(); }
                    if (s < 31) ok = TESTFULL(s + 1) & (s != 28 || mbar_test(sb + B_GATE, 0));
                    MMA_A(s, 2); MMA_A(s, 3);
                    wg_commit();
                }
                wg_wait<0>();
                mbar_arrive_if(sb + B_EA, lead);
            } else {
                wg_wait<0>();
                mbar_arrive_if(sb + B_EMPTY + 8 * ((SP0 - 1) % NST), lead);
#pragma unroll
                for (int s = SP0; s < 32; s++) WAITFULL(s);
                mbar_wait_mma(sb + B_GATE, 0);
                GATES();
                mbar_wait_mma(sb + B_S1, 0);
                wg_fence();
#pragma unroll
                for (int s = SP0; s < 32; s++) {
                    MMA_A(s, 0); MMA_A(s, 1);
                    if (s > SP0) {
                        wg_commit();
                        wg_wait<1>();
                        mbar_arrive_n_if<2>(sb + B_EMPTY + 8 * ((s - 1) % NST), lead);
                        if (s == 31) mbar_arrive_if(sb + B_S3, lead);
                        if (s == 30) WAITD(0);
                        wg_fence();
                    }
                    MMA_A(s, 2); MMA_A(s, 3);
                    wg_commit();
                }
                wg_wait<0>();
                mbar_arrive_n_if<2>(sb + B_EMPTY + 8 * (31 % NST), lead);
            }
            fence_regs<0, 64>(acc);
            uint4 f[8];
#define TAG(v, c) (((v) & ~tagm[c]) | (par & tagm[c]))
#define PACK(k) f[k] = make_uint4(TAG(pack_bf16(acc[8 * (k)], acc[8 * (k) + 1]), 0), TAG(pack_bf16(acc[8 * (k) + 2], acc[8 * (k) + 3]), 2), \
                                  TAG(pack_bf16(acc[8 * (k) + 4], acc[8 * (k) + 5]), 1), TAG(pack_bf16(acc[8 * (k) + 6], acc[8 * (k) + 7]), 3))
#define SEND(k) do { st_relaxed(fout + 512 * (k), f[k].x); st_relaxed(fout + 512 * (k) + 32, f[k].z);                        \
                     st_relaxed(fout + 512 * (k) + 64, f[k].y); st_relaxed(fout + 512 * (k) + 96, f[k].w); } while (0)
#define OWN(k) wgmma128rs(acc, f[k], desc_lo(dd0 + d_addr((k) >> 2) / 16 + ((k) & 3) * 2), (k) != 0)
            const uint32_t dfa = sbd + 0x80000 + (early ? comp * 512 : NST * 1024), dfb = sbd + 0x80000 + (early ? (1 - comp) * 512 : NST * 1024 + 512);
#define MMA_F(pos, kk) wgmma128<0>(acc, (uint64_t)(((pos) < 5 ? dfa : dfb) + a_addr(29 + ((pos) - 2) % 3) / 16 + (kk) * 128) | (0x10ull << 32), \
                                   desc_lo(dd0 + d_addr(pos) / 16 + (kk) * 2), 1)
#define WAITF(pos) mbar_wait_mma(vb + 8 * ((pos) - 2), 0)
            const uint32_t vb = sb + B_VAL + (early ? 0 : 48);
            const uint32_t ts = clk();
            if (early) {
                PACK(0); SEND(0); PACK(1); SEND(1); PACK(2); SEND(2); PACK(3); SEND(3);
                until(ts);
                PACK(4); PACK(5); PACK(6); PACK(7);
                const float s0 = comp ? -g0 : g0, s1 = comp ? -g1 : g1;
                const uint32_t og0 = pack_bf16(1.f - g0, 1.f - g0), og1 = pack_bf16(1.f - g1, 1.f - g1);
                const int rr = 0x7fff - (int)(lds32(sb + M_KEY) & 0x7fffu) - (tm * 128 + wg * 64 + r0);
#pragma unroll
                for (int k = 4; k < 8; k++) {
                    if (k < ESEND) { until(ts + ET1 + (k - 4) * STP); SEND(k); }
#pragma unroll
                    for (int i = 2 * k - 8; i < 2 * k - 6; i++) {
                        const uint32_t og = (i & 1) ? og1 : og0;
                        w[i] = make_uint4(hmul2_bf16(og, w[i].x), hmul2_bf16(og, w[i].y), hmul2_bf16(og, w[i].z), hmul2_bf16(og, w[i].w));
                        asm volatile("" : "+r"(w[i].x), "+r"(w[i].y), "+r"(w[i].z), "+r"(w[i].w));
                    }
                }
                WAITD(0);
                mbar_wait_mma(sb + B_S3, 0);
                wg_fence();
#pragma unroll
                for (int k = 0; k < 8; k++) {
                    OWN(k);
                    if (k >= 1 && k + ESEND - 1 < 8) { wg_commit(); until(ts + ET1 + (k + ESEND - 5) * STP); SEND(k + ESEND - 1); wg_fence(); }
                }
                wg_commit();
                WAITD(2);
                bool ok = false;
#pragma unroll
                for (int pos = 2; pos < 8; pos++) {
                    if (!ok) {
                        if (pos >= 4) WAITD(pos);
                        WAITF(pos);
                    }
                    wg_fence();
                    MMA_F(pos, 0); MMA_F(pos, 1);
                    if (pos == 6) { wg_commit(); wg_wait<1>(); mbar_arrive_cluster_if(mapa(sb + B_XF, rank ^ 1), lead); wg_fence(); }
                    if (pos == 7) mbar_arrive_if(sb + B_S2, lead);
                    if (pos < 7) ok = mbar_test(vb + 8 * (pos - 1), 0) & (pos < 3 || mbar_test(sb + B_DL + 8 * (pos - 3), 0));
                    MMA_F(pos, 2); MMA_F(pos, 3);
                    wg_commit();
                }
                const uint32_t xd = mapa(sb + a_addr(29) + (tid & 127) * 16, rank ^ 1), xb = mapa(sb + B_X, rank ^ 1);
                if (rr == 0 || rr == 8) {
                    mbar_wait_mma(sb + B_SIDE, 0);
#pragma unroll
                    for (int j = 0; j < 4; j++) {
                        const float4 ua = *(const float4*)(smem + M_RED + j * 128 + q * 32), ub = *(const float4*)(smem + M_RED + j * 128 + q * 32 + 16);
                        uint4 v = rr ? w[2 * j + 1] : w[2 * j];
                        v = make_uint4(pack_bf16(ua.x + bflo(v.x), ua.y + bfhi(v.x)), pack_bf16(ua.z + bflo(v.y), ua.w + bfhi(v.y)),
                                       pack_bf16(ub.x + bflo(v.z), ub.y + bfhi(v.z)), pack_bf16(ub.z + bflo(v.w), ub.w + bfhi(v.w)));
                        if (rr) w[2 * j + 1] = v; else w[2 * j] = v;
                    }
                }
                __syncwarp();
                mbar_wait_mma(sb + B_XF, 0);
                wg_wait<0>();
                fence_regs<0, 64>(acc);
                keep_regs<0, 8>(f);
#pragma unroll
                for (int i = 0; i < 8; i++) {
                    const uint4 z = scale_add((i & 1) ? s1 : s0, acc, 16 * (i >> 1) + 2 * (i & 1), w[i]);
                    st_async16(xd + i * 2048, z.x, z.y, z.z, z.w, xb + 2 * (i & 4));
                    if (i & 1) until(ts);
                }
            } else {
#pragma unroll
                for (int k = 0; k < 4; k++) {
                    PACK(2 * k); PACK(2 * k + 1);
                    if (k < LPRE) { until(ts + LT0 + k * LTP); SEND(k); }
                }
                wg_fence();
#pragma unroll
                for (int k = 0; k < 8; k++) {
                    OWN(k);
                    if ((k & 1) && k / 2 < LSEND) { wg_commit(); until(ts + LT0 + (LPRE + k / 2) * LTP); SEND(LPRE + k / 2); wg_fence(); }
                }
                wg_commit();
#pragma unroll
                for (int k = LPRE + LSEND; k < 8; k++) { until(ts + LT0 + k * LTP); SEND(k); }
                float s0 = comp ? -g0 : g0, s1 = comp ? -g1 : g1;
                uint32_t xs = sb + a_addr(29) + (tid & 127) * 16;
                char* op = pout + ooff;
                asm volatile("" : "+f"(s0), "+f"(s1), "+r"(xs), "+l"(op));
                wg_wait<0>();
                keep_regs<0, 8>(f);
                WAITF(2);
                mbar_wait_mma(sb + B_S2, 0);
                bool there = false, there1 = false, ok = true;
#pragma unroll
                for (int pos = 2; pos < 8; pos++) {
                    if (!ok) WAITF(pos);
                    wg_fence();
                    MMA_F(pos, 0);
                    if (pos == XPOS) there = mbar_test(sb + B_X, 0);
                    MMA_F(pos, 1);
                    if (pos == XPOS) {
#pragma unroll
                        for (int i = 0; i < 4; i++) lds128_if(w[i], xs + i * 2048, there);
                    }
                    if (pos < 7) ok = mbar_test(vb + 8 * (pos - 1), 0);
                    MMA_F(pos, 2); MMA_F(pos, 3);
                    wg_commit();
                }
                if (!there) {
                    mbar_wait_mma(sb + B_X, 0);
#pragma unroll
                    for (int i = 0; i < 4; i++) w[i] = lds128(xs + i * 2048);
                }
                there1 = mbar_test(sb + B_X + 8, 0);
                float z[32];
#pragma unroll
                for (int i = 0; i < 4; i++) {
                    z[8 * i] = bflo(w[i].x); z[8 * i + 1] = bfhi(w[i].x); z[8 * i + 2] = bflo(w[i].y); z[8 * i + 3] = bfhi(w[i].y);
                    z[8 * i + 4] = bflo(w[i].z); z[8 * i + 5] = bfhi(w[i].z); z[8 * i + 6] = bflo(w[i].w); z[8 * i + 7] = bfhi(w[i].w);
                }
                fence_regs<0, 32>(z);
#pragma unroll 1
                for (int n = there1; n > 0; n--) {
#pragma unroll
                    for (int i = 4; i < 8; i++) w[i] = lds128(xs + i * 2048);
                }
                wg_wait<0>();
                fence_regs<0, 64>(acc);
#pragma unroll
                for (int i = 0; i < 8; i++) {
                    const int o = 16 * (i >> 1) + 2 * (i & 1);
                    const float s = (i & 1) ? s1 : s0;
                    if (i == XW && !there1) {
                        mbar_wait_mma(sb + B_X + 8, 0);
#pragma unroll
                        for (int k = 4; k < 8; k++) w[k] = lds128(xs + k * 2048);
                    }
                    stg_off<0>(op + (i & 1) * 8192 + (i >> 1) * 64,
                               i >= 4 ? scale_add(s, acc, o, w[i])
                                      : make_uint4(pack_bf16(fmaf(s, acc[o], z[8 * (i & 3)]), fmaf(s, acc[o + 1], z[8 * (i & 3) + 1])),
                                                   pack_bf16(fmaf(s, acc[o + 4], z[8 * (i & 3) + 2]), fmaf(s, acc[o + 5], z[8 * (i & 3) + 3])),
                                                   pack_bf16(fmaf(s, acc[o + 8], z[8 * (i & 3) + 4]), fmaf(s, acc[o + 9], z[8 * (i & 3) + 5])),
                                                   pack_bf16(fmaf(s, acc[o + 12], z[8 * (i & 3) + 6]), fmaf(s, acc[o + 13], z[8 * (i & 3) + 7]))));
                    __syncwarp();
                }
            }
        }
    } else {
        if (wu >= 14) {
            const uint32_t b = blockIdx.x;
            const char* q = wu == 14 ? pcr + (uint32_t)((b >> 1) * 32 + lane) * (S_ * 2) + 128 : px + (uint32_t)(b * 4 + lane) * 128 + 65536;
            until(tstart + P_1);
            if (b < 128 && (wu == 14 || lane < 4)) prefetch_l2(q);
        } else if (wu == 13 && !spare) {
            if (lane == 0) ARM(1);
            __syncwarp();
            until(tstart + T_1);
            STEP0(1);
        }
        if (lane == 0) ARM(wu - 10);
        asm volatile("fence.mbarrier_init.release.cluster;" ::: "memory");
        __syncwarp();
        asm volatile("barrier.cluster.arrive.relaxed.aligned;" ::: "memory");
        if (spare) return;
        asm volatile("setmaxnreg.dec.sync.aligned.u32 " STR(RU) ";");
        if (wu < 14) {
            until(tstart + T_2 + (wu - 12) * PACE);
            STEP0(wu - 10);
        }
        asm volatile("barrier.cluster.wait.acquire.aligned;" ::: "memory");
        if (wu == 13) {
            const CUtensorMap* mD = comp ? &p.mDim : &p.mDre;
#pragma unroll
            for (int step = 4; step < NST; step++) {
                until(tstart + T_2 + (step - 2) * PACE);
                tma3d_elect(sb + b_addr(step), &p.mX2, step * 64, tn * 2, sb + B_FULL + 8 * step);
            }
#pragma unroll 1
            for (int step = NST, slot = 0, ph = 0; step < 32; step++) {
                mbar_wait(sb + B_EMPTY + 8 * slot, ph);
                mbar_wait(sb + B_EMPR + 8 * slot, ph);
                tma2d_pair_elect(sb + b_addr(0) + slot * 16384 + rank * 8192, &p.mX, tn * 128 + rank * 64, step * 64, sb + B_FULL + 8 * slot);
                if (++slot == NST) { slot = 0; ph ^= 1; }
            }
#pragma unroll
            for (int c = 0; c < 4; c += 2) {
                const uint32_t bar = sb + (c ? B_D6 : B_FULL + 8 * (32 % NST));
                if (c) mbar_wait(sb + B_R6, 0);
                else mbar_wait(sb + B_EMPTY + 8 * (26 % NST), (26 / NST) & 1);
                tma5d_elect(sb + d_addr(c), mD, dcol(c, tn), tn * 4, bar);
                tma5d_elect(sb + d_addr(c + 1), mD, dcol(c + 1, tn), tn * 4, bar);
                mbar_expect_tx_elect(bar, 32768);
            }
#pragma unroll
            for (int c = 0; c < 4; c++) mbar_expect_tx_elect(sb + B_DL + 8 * c, 16384);
            mbar_wait(sb + B_S1, 0);
            const uint32_t tq = clk();
#pragma unroll
            for (int c = 0; c < 4; c++) {
                if (!(c & 1)) mbar_wait(sb + B_EMPTY + 8 * ((27 + c / 2) % NST), ((27 + c / 2) / NST) & 1);
                if (c) until(tq + (c == 1 ? T_D5 : c == 2 ? T_D6 : T_D7));
                tma5d_elect(sb + d_addr(4 + c), mD, dcol(4 + c, tn), tn * 4, sb + B_DL + 8 * c);
            }
        } else {
            if (wu == 12) {
#pragma unroll
                for (int step = 4; step < NST; step++) {
                    until(tstart + T_2 + (step - 2) * PACE);
                    tma2d_elect(sb + a_addr(step), mC, step * 64, tm * 128, sb + B_FULL + 8 * step);
                }
#pragma unroll 1
                for (int step = NST, slot = 0, ph = 0; step < 32; step++) {
                    mbar_wait(sb + B_EMPTY + 8 * slot, ph);
                    tma2d_elect(sb + slot * 16384, mC, step * 64, tm * 128, sb + B_FULL + 8 * slot);
                    mbar_expect_tx_elect(sb + B_FULL + 8 * slot, 32768);
                    if (++slot == NST) { slot = 0; ph ^= 1; }
                }
            } else if (wu == 14) {
                if (lane == 0) {
                    asm volatile("prefetch.tensormap [%0];" ::"l"(&p.mX) : "memory");
                    asm volatile("prefetch.tensormap [%0];" ::"l"(&p.mF) : "memory");
                    asm volatile("prefetch.tensormap [%0];" ::"l"(comp ? &p.mDim : &p.mDre) : "memory");
                    asm volatile("st.shared::cluster.u32 [%0], %1;" ::"r"(mapa(sb + M_ROLE, rank ^ 1)), "r"(role) : "memory");
                }
                nap_until(tstart + KEY_T0 - 1000);
                const uint32_t epoch = ld_relaxed(g->epoch + cta) + 1u, par = epoch & 1u;
                if (lane < 8) stg_off<0>(g->stamp + cta * 32 + lane * 4, make_uint4(par ^ 1u, 0, 0, 0));
                nap_until(tstart + KEY_T0);
                const uint32_t k = best_key(g->keys + ((tm + (tm >> 3)) & 7) * NCTA, par);
                const uint4 xr = ldg_nc_off<0>(px + (0x7fff - (k & 0x7fffu)) * (D_ * 2) + rank * 512 + lane * 16);
                const uint4 g4 = wait_tags(g->gate + tm * 128 + lane * 4, par);
                sts128(sb + M_G + lane * 16, make_uint4(g4.x & ~1u, g4.y & ~1u, g4.z & ~1u, g4.w & ~1u));
                sts128(sb + M_UPD + lane * 16, xr);
                if (lane == 0) {
                    *(volatile uint32_t*)(smem + M_KEY) = k;
                    *(volatile uint32_t*)(smem + M_PAR) = par;
                    st_relaxed(g->epoch + cta, epoch);
                }
                mbar_arrive_warp(sb + B_GATE);
            } else {
                const int fr = ffn_pair(role);
                const uint32_t t1 = tstart + FFN_T0 + (rank + ((fr >> 2) & 6)) * (FFN_DT / 8);
                if (!((NOFFN_MASK >> role) & 1)) {
#pragma unroll 1
                    for (int i = 0; i < 12; i++) {
                        const int qu = i < 4 ? 2 + (i >> 1) : (i - 4) >> 1;
                        const uint32_t bar = sb + B_FFN + 8 * (i < 4 ? 3 : qu), dst = sb + R6 + (i & 1) * 16384 + qu * 4096;
                        if (i == 8) mbar_wait(sb + B_VD, 0);
                        if (i == 0 || (i >= 4 && !(i & 1))) mbar_expect_tx_elect(bar, i ? 8192 : 16384);
                        nap_until(t1 + i * FFN_DT);
                        tma2d_elect(dst, i < 4 ? &p.mWd : (i & 1) ? &p.mWu : &p.mWg, i < 4 ? rank * 256 : fr * 32, i < 4 ? fr * 32 + i * 8 : rank * 256 + qu * 64, bar);
                    }
                }
            }
            __syncwarp();
            mbar_wait(sb + B_GATE, 0);
            fetch_job<0>(p, g, smem, sb, cta, wu == 12 ? 2 : wu - 14, lds32(sb + M_PAR));
        }
    }
}

typedef CUresult (*EncodeTiledFn)(CUtensorMap*, CUtensorMapDataType, cuuint32_t, void*, const cuuint64_t*, const cuuint64_t*,
                                  const cuuint32_t*, const cuuint32_t*, CUtensorMapInterleave, CUtensorMapSwizzle,
                                  CUtensorMapL2promotion, CUtensorMapFloatOOBfill);

static void make_map(EncodeTiledFn enc, CUtensorMap* m, const void* base, uint64_t cols, uint64_t rows, uint32_t box_rows,
                     CUtensorMapSwizzle sw = CU_TENSOR_MAP_SWIZZLE_128B, uint32_t box_cols = 64) {
    cuuint64_t dims[2] = {cols, rows};
    cuuint64_t str[1] = {cols * 2};
    cuuint32_t box[2] = {box_cols, box_rows};
    cuuint32_t es[2] = {1, 1};
    enc(m, CU_TENSOR_MAP_DATA_TYPE_BFLOAT16, 2, (void*)base, dims, str, box, es, CU_TENSOR_MAP_INTERLEAVE_NONE,
        sw, CU_TENSOR_MAP_L2_PROMOTION_L2_128B, CU_TENSOR_MAP_FLOAT_OOB_FILL_NONE);
}

static void make_map_chunks(EncodeTiledFn enc, CUtensorMap* m, const void* base, uint64_t rows) {
    cuuint64_t dims[3] = {64, rows, D_ / 64};
    cuuint64_t str[2] = {D_ * 2, 128};
    cuuint32_t box[3] = {64, 64, 2};
    cuuint32_t es[3] = {1, 1, 1};
    enc(m, CU_TENSOR_MAP_DATA_TYPE_BFLOAT16, 3, (void*)base, dims, str, box, es, CU_TENSOR_MAP_INTERLEAVE_NONE,
        CU_TENSOR_MAP_SWIZZLE_128B, CU_TENSOR_MAP_L2_PROMOTION_L2_128B, CU_TENSOR_MAP_FLOAT_OOB_FILL_NONE);
}

static void make_map_perm(EncodeTiledFn enc, CUtensorMap* m, const void* base) {
    cuuint64_t dims[5] = {D_, 2, 4, 4, D_ / 32};
    cuuint64_t str[4] = {D_ * 2, 8 * D_ * 2, 2 * D_ * 2, 32 * D_ * 2};
    cuuint32_t box[5] = {64, 2, 4, 4, 4};
    cuuint32_t es[5] = {1, 1, 1, 1, 1};
    enc(m, CU_TENSOR_MAP_DATA_TYPE_BFLOAT16, 5, (void*)base, dims, str, box, es, CU_TENSOR_MAP_INTERLEAVE_NONE,
        CU_TENSOR_MAP_SWIZZLE_128B, CU_TENSOR_MAP_L2_PROMOTION_L2_128B, CU_TENSOR_MAP_FLOAT_OOB_FILL_NONE);
}

extern "C" void kernel_launch(void* const* d_in, const int* in_sizes, int n_in, void* d_out, int out_size) {
    (void)in_sizes; (void)n_in; (void)out_size;
    static EncodeTiledFn enc = nullptr;
    static bool fused_ok = false;
    static void* scr = nullptr;
    if (!enc) {
        void* fn = nullptr;
        cudaDriverEntryPointQueryResult q;
        cudaGetDriverEntryPoint("cuTensorMapEncodeTiled", &fn, cudaEnableDefault, &q);
        enc = (EncodeTiledFn)fn;
        cudaGetSymbolAddress(&scr, g_scr);
        cudaFuncSetAttribute(fused_kernel, cudaFuncAttributeMaxDynamicSharedMemorySize, SMEM_BYTES);
        int dev = 0, nsm = 0, ncl = 0;
        cudaGetDevice(&dev);
        cudaDeviceGetAttribute(&nsm, cudaDevAttrMultiProcessorCount, dev);
        cudaLaunchConfig_t cfg = {};
        cfg.gridDim = dim3(132); cfg.blockDim = dim3(NTHREADS); cfg.dynamicSmemBytes = SMEM_BYTES;
        cudaLaunchAttribute at;
        at.id = cudaLaunchAttributeClusterDimension;
        at.val.clusterDim.x = 2; at.val.clusterDim.y = 1; at.val.clusterDim.z = 1;
        cfg.attrs = &at; cfg.numAttrs = 1;
        fused_ok = cudaOccupancyMaxActiveClusters(&ncl, fused_kernel, &cfg) == cudaSuccess && nsm == 132 && ncl == 66;
        (void)cudaGetLastError();
    }
    if (!fused_ok) {
        const bf16* const* in = (const bf16* const*)d_in;
        fb_hidden<<<S_, D_, 0, cudaStreamPerThread>>>(in[0], in[3], in[4], in[10], in[6]);
        fb_ffn1<<<F_ / 128, 128, 0, cudaStreamPerThread>>>(in[0], in[7], in[8]);
        fb_ffn2<<<D_ / 64, 64, 0, cudaStreamPerThread>>>(in[9]);
        fb_seq<<<S_, D_, 0, cudaStreamPerThread>>>(in[0], in[1], in[2], (bf16*)d_out);
        return;
    }
    Params p;
    p.dre = (const bf16*)d_in[3];
    p.dim = (const bf16*)d_in[4];
    p.w_r = (const bf16*)d_in[6];
    p.gate_w = (const bf16*)d_in[10];
    make_map_chunks(enc, &p.mX2, d_in[0], S_);
    make_map(enc, &p.mX, d_in[0], D_, S_, 64);
    make_map(enc, &p.mCre, d_in[1], S_, S_, 128);
    make_map(enc, &p.mCim, d_in[2], S_, S_, 128);
    make_map_perm(enc, &p.mDre, d_in[3]);
    make_map_perm(enc, &p.mDim, d_in[4]);
    make_map(enc, &p.mF, scr, 64, NCTA * 256, 64, CU_TENSOR_MAP_SWIZZLE_NONE);
    make_map(enc, &p.mWg, d_in[7], F_, D_, 64, CU_TENSOR_MAP_SWIZZLE_NONE, 32);
    make_map(enc, &p.mWu, d_in[8], F_, D_, 64, CU_TENSOR_MAP_SWIZZLE_NONE, 32);
    make_map(enc, &p.mWd, d_in[9], D_, F_, 8, CU_TENSOR_MAP_SWIZZLE_NONE, 256);
    fused_kernel<<<132, NTHREADS, SMEM_BYTES, cudaStreamPerThread>>>(CPtr{{(const char*)d_in[1], (const char*)d_in[2]}}, (const char*)d_in[0], (char*)d_out, (Scratch*)scr, p);
}
```
